```python
import torch

def _softmax(x, axis=-1):
    return torch.softmax(x, dim=axis)
def _gelu(x):
    return torch.nn.functional.gelu(x, approximate="tanh")
def _silu(x):
    return torch.nn.functional.silu(x)
def _sigmoid(x):
    return torch.sigmoid(x)
def _layernorm(x, axis=-1, eps=1e-5):
    m = x.mean(dim=axis, keepdim=True)
    v = x.var(dim=axis, keepdim=True, unbiased=False)
    return (x - m) / torch.sqrt(v + eps)
def _scatter_add(tgt, idx, src, axis=0):
    return tgt.clone().index_add_(axis, idx, src)
def _segment_sum(src, seg, n):
    out = torch.zeros((n,) + src.shape[1:], dtype=src.dtype)
    return out.index_add_(0, seg, src)
def _pad(x, pw):
    flat = tuple(v for pair in reversed(pw) for v in pair)
    return torch.nn.functional.pad(x, flat)

kernel_name = 'sequential_preLN__softmax_full_mha__moe_arch_mod__prompt'

def setup_inputs():

    _w = (lambda a: (lambda t: t.to(torch.bfloat16) if t.is_floating_point() else t)(torch.as_tensor(a)))
    def _A_setup():
        B, S, D = 1, 2048, 512
        return {
            "x": _w((lambda *s: torch.randn(*s, dtype=torch.bfloat16) * 0.05)(B, S, D)),
            "wqkv": _w((lambda *s: torch.randn(*s, dtype=torch.bfloat16) * 0.05)(D, 3 * D)),
            "wo": _w((lambda *s: torch.randn(*s, dtype=torch.bfloat16) * 0.05)(D, D)),
        }
    _A_in = _A_setup()

    def _B_setup():
        B, S, D, F, C = 1, 2048, 512, 1792, 2
        return {
            "x": _w((lambda *s: torch.randn(*s, dtype=torch.bfloat16) * 0.05)(B, S, D)),
            "w_r": _w((lambda *s: torch.randn(*s, dtype=torch.bfloat16) * 0.05)(D)),
            "w_gate": _w((lambda *s: torch.randn(*s, dtype=torch.bfloat16) * 0.05)(D, F)),
            "w_up": _w((lambda *s: torch.randn(*s, dtype=torch.bfloat16) * 0.05)(D, F)),
            "w_down": _w((lambda *s: torch.randn(*s, dtype=torch.bfloat16) * 0.05)(F, D)),
        }
    _B_in = _B_setup()

    return {
        "A_x": _A_in["x"],
        "A_wqkv": _A_in["wqkv"],
        "A_wo": _A_in["wo"],
        "B_x": _B_in["x"],
        "B_w_r": _B_in["w_r"],
        "B_w_gate": _B_in["w_gate"],
        "B_w_up": _B_in["w_up"],
        "B_w_down": _B_in["w_down"],
    }

def reference(A_x, A_wqkv, A_wo, B_x, B_w_r, B_w_gate, B_w_up, B_w_down):
    def _A_ref(x, wqkv, wo):
        B, S, D = x.shape
        H = 32; Dh = D // H
        qkv = (lambda x, *d: x.permute(*d))((x @ wqkv).reshape(B, S, 3, H, Dh), 2, 0, 3, 1, 4)
        q, k, v = qkv[0], qkv[1], qkv[2]
        scale = Dh ** -0.5
        scores = torch.einsum("bhqd,bhkd->bhqk", q, k) * scale
        p = _softmax(scores, axis=-1)
        o = torch.einsum("bhqk,bhkd->bhqd", p, v)
        return (lambda x, *d: x.permute(*d))(o, 0, 2, 1, 3).reshape(B, S, D) @ wo

    def _B_ref(x, w_r, w_gate, w_up, w_down):
        B, S, D = x.shape
        C = 2
        r = x @ w_r
        idx = torch.argsort(-r, axis=-1)[:, :C]
        idx_e = (lambda x, n, axis: torch.repeat_interleave(x, n, dim=axis))(idx.reshape(B, C, 1), D, axis=2)
        x_sel = (lambda x, i, axis: torch.take_along_dim(x, i, dim=axis))(x, idx_e, axis=1)
        g = _silu(x_sel @ w_gate)
        u = x_sel @ w_up
        y = (g * u) @ w_down
        r_sel = _sigmoid((lambda x, i, axis: torch.take_along_dim(x, i, dim=axis))(r, idx, axis=1))
        y = y * r_sel.reshape(B, C, 1)
        b_off = (torch.arange(B) * S).reshape(B, 1)
        flat_idx = (idx + b_off).reshape(B * C)
        zero = (x * 0.0).reshape(B * S, D)
        upd = _scatter_add(zero, flat_idx, y.reshape(B * C, D), axis=0)
        return x + upd.reshape(B, S, D)

    x = A_x
    h = x + _A_ref(_layernorm(x, axis=-1), A_wqkv, A_wo)
    h2 = h + _B_ref(_layernorm(h, axis=-1), B_w_r, B_w_gate, B_w_up, B_w_down)
    return h2
```

```cpp
#include <cuda_runtime.h>
#include <cuda_bf16.h>
#include <cuda.h>
#include <stdint.h>

namespace {

constexpr int S_LEN = 2048, DM = 512, NH = 32, DH = 16, FF = 1792;
constexpr float LN_EPS = 1e-5f;
constexpr float QSCALE = 0.25f * 1.4426950408889634f;

__device__ __align__(1024) __nv_bfloat16 gQ[NH * S_LEN * DH];
__device__ __align__(1024) __nv_bfloat16 gK[NH * S_LEN * DH];
__device__ __align__(1024) __nv_bfloat16 gV[NH * S_LEN * DH];
__device__ __align__(1024) __nv_bfloat16 gO[S_LEN * DM];
__device__ __align__(1024) __nv_bfloat16 gH[S_LEN * DM];
__device__ float gNorm[16 * NH * 4];
__device__ float gMu1[S_LEN];
__device__ __align__(16) float gStats[S_LEN * 4];
__device__ __align__(16) float gY[2 * DM];
__device__ unsigned int gCounter;

__device__ __forceinline__ uint32_t smem_u32(const void* p) { return (uint32_t)__cvta_generic_to_shared(p); }
__device__ __forceinline__ void mbar_init(uint32_t bar, uint32_t cnt) {
    asm volatile("mbarrier.init.shared::cta.b64 [%0], %1;" ::"r"(bar), "r"(cnt));
}
__device__ __forceinline__ void mbar_expect_tx(uint32_t bar, uint32_t bytes) {
    asm volatile("mbarrier.arrive.expect_tx.shared::cta.b64 _, [%0], %1;" ::"r"(bar), "r"(bytes) : "memory");
}
__device__ __forceinline__ void mbar_arrive(uint32_t bar) {
    asm volatile("mbarrier.arrive.shared::cta.b64 _, [%0];" ::"r"(bar) : "memory");
}
__device__ __forceinline__ void mbar_wait(uint32_t bar, uint32_t parity) {
    uint32_t done = 0;
    int it = 0;
    while (true) {
        asm volatile("{.reg .pred p; mbarrier.try_wait.parity.shared::cta.b64 p, [%1], %2; selp.u32 %0, 1, 0, p;}"
                     : "=r"(done) : "r"(bar), "r"(parity) : "memory");
        if (done) break;
        if (++it > (1 << 22)) __trap();
    }
}
__device__ __forceinline__ void bulk_g2s(uint32_t dst, const void* src, uint32_t bytes, uint32_t bar) {
    asm volatile("cp.async.bulk.shared::cluster.global.mbarrier::complete_tx::bytes [%0], [%1], %2, [%3];"
                 ::"r"(dst), "l"(src), "r"(bytes), "r"(bar) : "memory");
}
__device__ __forceinline__ void tma_2d(uint32_t dst, const CUtensorMap* tm, int c0, int c1, uint32_t bar) {
    asm volatile("cp.async.bulk.tensor.2d.shared::cluster.global.mbarrier::complete_tx::bytes [%0], [%1, {%3, %4}], [%2];"
                 ::"r"(dst), "l"(tm), "r"(bar), "r"(c0), "r"(c1) : "memory");
}
__device__ __forceinline__ uint64_t make_desc(uint32_t addr, uint32_t lbo, uint32_t sbo, uint32_t mode) {
    return (uint64_t)((addr & 0x3FFFF) >> 4) | ((uint64_t)((lbo & 0x3FFFF) >> 4) << 16) |
           ((uint64_t)((sbo & 0x3FFFF) >> 4) << 32) | ((uint64_t)mode << 62);
}
__device__ __forceinline__ void wg_fence() { asm volatile("wgmma.fence.sync.aligned;" ::: "memory"); }
__device__ __forceinline__ void wg_commit() { asm volatile("wgmma.commit_group.sync.aligned;" ::: "memory"); }
template <int N> __device__ __forceinline__ void wg_wait() { asm volatile("wgmma.wait_group.sync.aligned %0;" ::"n"(N) : "memory"); }
template <int N> __device__ __forceinline__ void pin(float (&d)[N]) {
#pragma unroll
    for (int i = 0; i < N; i++) asm volatile("" : "+f"(d[i])::"memory");
}
__device__ __forceinline__ uint32_t pack_bf16(float lo, float hi) {
    uint32_t r;
    asm("cvt.rn.bf16x2.f32 %0, %1, %2;" : "=r"(r) : "f"(hi), "f"(lo));
    return r;
}
__device__ __forceinline__ float bf_lo(uint32_t v) { return __uint_as_float(v << 16); }
__device__ __forceinline__ float bf_hi(uint32_t v) { return __uint_as_float(v & 0xFFFF0000u); }
__device__ __forceinline__ float ex2_mufu(float x) {
    float y;
    asm("ex2.approx.ftz.f32 %0, %1;" : "=f"(y) : "f"(x));
    return y;
}

#define ACC8(d, o) "+f"(d[o + 0]), "+f"(d[o + 1]), "+f"(d[o + 2]), "+f"(d[o + 3]), "+f"(d[o + 4]), "+f"(d[o + 5]), "+f"(d[o + 6]), "+f"(d[o + 7])
#define OUT8(d, o) "=f"(d[o + 0]), "=f"(d[o + 1]), "=f"(d[o + 2]), "=f"(d[o + 3]), "=f"(d[o + 4]), "=f"(d[o + 5]), "=f"(d[o + 6]), "=f"(d[o + 7])

__device__ __forceinline__ void wgmma_n192(float (&d)[96], uint64_t da, uint64_t db, int scale_d) {
    asm volatile(
        "{.reg .pred p; setp.ne.b32 p, %98, 0;\n"
        "wgmma.mma_async.sync.aligned.m64n192k16.f32.bf16.bf16 "
        "{%0,%1,%2,%3,%4,%5,%6,%7,%8,%9,%10,%11,%12,%13,%14,%15,%16,%17,%18,%19,%20,%21,%22,%23,%24,%25,%26,%27,%28,%29,%30,%31,"
        "%32,%33,%34,%35,%36,%37,%38,%39,%40,%41,%42,%43,%44,%45,%46,%47,%48,%49,%50,%51,%52,%53,%54,%55,%56,%57,%58,%59,%60,%61,%62,%63,"
        "%64,%65,%66,%67,%68,%69,%70,%71,%72,%73,%74,%75,%76,%77,%78,%79,%80,%81,%82,%83,%84,%85,%86,%87,%88,%89,%90,%91,%92,%93,%94,%95},"
        "%96, %97, p, 1, 1, 0, 1;}"
        : ACC8(d, 0), ACC8(d, 8), ACC8(d, 16), ACC8(d, 24), ACC8(d, 32), ACC8(d, 40), ACC8(d, 48), ACC8(d, 56),
          ACC8(d, 64), ACC8(d, 72), ACC8(d, 80), ACC8(d, 88)
        : "l"(da), "l"(db), "r"(scale_d));
}
__device__ __forceinline__ void wgmma_n128(float (&d)[64], uint64_t da, uint64_t db, int scale_d) {
    asm volatile(
        "{.reg .pred p; setp.ne.b32 p, %66, 0;\n"
        "wgmma.mma_async.sync.aligned.m64n128k16.f32.bf16.bf16 "
        "{%0,%1,%2,%3,%4,%5,%6,%7,%8,%9,%10,%11,%12,%13,%14,%15,%16,%17,%18,%19,%20,%21,%22,%23,%24,%25,%26,%27,%28,%29,%30,%31,"
        "%32,%33,%34,%35,%36,%37,%38,%39,%40,%41,%42,%43,%44,%45,%46,%47,%48,%49,%50,%51,%52,%53,%54,%55,%56,%57,%58,%59,%60,%61,%62,%63},"
        "%64, %65, p, 1, 1, 0, 1;}"
        : ACC8(d, 0), ACC8(d, 8), ACC8(d, 16), ACC8(d, 24), ACC8(d, 32), ACC8(d, 40), ACC8(d, 48), ACC8(d, 56)
        : "l"(da), "l"(db), "r"(scale_d));
}
__device__ __forceinline__ void wgmma_qk128(float (&d)[64], const uint32_t (&a)[4], uint64_t desc) {
    asm volatile(
        "wgmma.mma_async.sync.aligned.m64n128k16.f32.bf16.bf16 "
        "{%0,%1,%2,%3,%4,%5,%6,%7,%8,%9,%10,%11,%12,%13,%14,%15,%16,%17,%18,%19,%20,%21,%22,%23,%24,%25,%26,%27,%28,%29,%30,%31,"
        "%32,%33,%34,%35,%36,%37,%38,%39,%40,%41,%42,%43,%44,%45,%46,%47,%48,%49,%50,%51,%52,%53,%54,%55,%56,%57,%58,%59,%60,%61,%62,%63},"
        "{%64,%65,%66,%67}, %68, 0, 1, 1, 0;"
        : OUT8(d, 0), OUT8(d, 8), OUT8(d, 16), OUT8(d, 24), OUT8(d, 32), OUT8(d, 40), OUT8(d, 48), OUT8(d, 56)
        : "r"(a[0]), "r"(a[1]), "r"(a[2]), "r"(a[3]), "l"(desc));
}
__device__ __forceinline__ void wgmma_pv24(float (&o)[12], uint32_t a0, uint32_t a1, uint32_t a2, uint32_t a3, uint64_t desc) {
    asm volatile(
        "wgmma.mma_async.sync.aligned.m64n24k16.f32.bf16.bf16 "
        "{%0,%1,%2,%3,%4,%5,%6,%7,%8,%9,%10,%11}, {%12,%13,%14,%15}, %16, 1, 1, 1, 1;"
        : ACC8(o, 0), "+f"(o[8]), "+f"(o[9]), "+f"(o[10]), "+f"(o[11])
        : "r"(a0), "r"(a1), "r"(a2), "r"(a3), "l"(desc));
}

__device__ __forceinline__ uint32_t ex2_pair_poly(float x0, float x1) {
    const float M = 12288.0f + 31.0f;
    float t0 = x0 + M, t1 = x1 + M;
    uint32_t G = __byte_perm(__float_as_uint(t0), __float_as_uint(t1), 0x5410);
    uint32_t W, q;
    asm("lop3.b32 %0, %1, %2, %3, 0xEA;" : "=r"(W) : "r"(G), "r"(0x03FF03FFu), "r"(0x3C003C00u));
    asm("fma.rn.f16x2 %0, %1, %2, %3;" : "=r"(q) : "r"(0x15121512u), "r"(W), "r"(0x8acc8accu));
    asm("fma.rn.f16x2 %0, %1, %2, %3;" : "=r"(q) : "r"(q), "r"(W), "r"(0x1fc21fc2u));
    asm("fma.rn.f16x2 %0, %1, %2, %3;" : "=r"(q) : "r"(q), "r"(W), "r"(0x2f732f73u));
    return ((G & 0xFC00FC00u) >> 3) + q;
}
constexpr int NPP = 18;
__device__ __forceinline__ constexpr bool use_poly_pair(int i) { return ((i % 32 + 1) * NPP) / 32 != ((i % 32) * NPP) / 32; }
__device__ __forceinline__ uint32_t ex2_pair(float x0, float x1, int i) {
    return use_poly_pair(i) ? ex2_pair_poly(x0, x1) : pack_bf16(ex2_mufu(x0), ex2_mufu(x1));
}

constexpr int K1_STAGES = 5;
constexpr int K1_STAGE_BYTES = 16384 + 24576;
constexpr int K1_SMEM = K1_STAGES * K1_STAGE_BYTES + 1024;

__global__ void __launch_bounds__(512, 1)
k1_qkv(const __grid_constant__ CUtensorMap tmX, const __grid_constant__ CUtensorMap tmW) {
    extern __shared__ __align__(1024) char smem_raw[];
    char* smem = smem_raw + ((1024 - (smem_u32(smem_raw) & 1023)) & 1023);
    __shared__ __align__(8) uint64_t full[K1_STAGES], empty[K1_STAGES];
    __shared__ float sMu[128], sRs[128], sCs[192];
    __shared__ unsigned int sNorm[4 * 3];

    const int rb = blockIdx.x >> 3, hg = blockIdx.x & 7;
    const int tid = threadIdx.x, wg = tid >> 7, warp = tid >> 5, lane = tid & 31;

    if (tid == 0) {
        for (int i = 0; i < K1_STAGES; i++) { mbar_init(smem_u32(&full[i]), 1); mbar_init(smem_u32(&empty[i]), 15); }
        asm volatile("fence.mbarrier_init.release.cluster;" ::: "memory");
    }
    if (tid < 12) sNorm[tid] = 0;
    if (hg == 0 && tid < 128) *reinterpret_cast<float4*>(&gStats[(rb * 128 + tid) * 4]) = make_float4(0.f, 0.f, 0.f, 0.f);
    if (blockIdx.x == 1) { gY[tid] = 0.f; gY[512 + tid] = 0.f; if (tid == 0) gCounter = 0; }
    __syncthreads();

    float acc[96];
    if (wg < 2) {
        for (int kc = 0; kc < 8; kc++) {
            const int s = kc % K1_STAGES;
            mbar_wait(smem_u32(&full[s]), (kc / K1_STAGES) & 1);
            const uint32_t sa = smem_u32(smem + s * K1_STAGE_BYTES), sb = sa + 16384;
            const uint64_t da = make_desc(sa + wg * 8192, 16, 1024, 1);
            const uint64_t db = make_desc(sb, 8192, 1024, 1);
            wg_fence();
#pragma unroll
            for (int ks = 0; ks < 4; ks++) wgmma_n192(acc, da + ks * 2, db + ks * 128, (kc | ks) != 0);
            wg_commit();
            if (kc > 0) {
                wg_wait<1>();
                if (lane == 0) mbar_arrive(smem_u32(&empty[(kc - 1) % K1_STAGES]));
            }
        }
        wg_wait<0>();
        pin(acc);
    } else if (wg == 2) {
        const int r = tid - 256;
        float c = 0.f, s1 = 0.f, s2 = 0.f;
        for (int kc = 0; kc < 8; kc++) {
            const int s = kc % K1_STAGES;
            mbar_wait(smem_u32(&full[s]), (kc / K1_STAGES) & 1);
            const char* row = smem + s * K1_STAGE_BYTES + r * 128;
#pragma unroll
            for (int j = 0; j < 8; j++) {
                const uint4 v = *reinterpret_cast<const uint4*>(row + ((j ^ (r & 7)) << 4));
                if (kc == 0 && j == 0) c = bf_lo(v.x);
                const uint32_t w[4] = {v.x, v.y, v.z, v.w};
#pragma unroll
                for (int e = 0; e < 4; e++) {
                    const float a = bf_lo(w[e]) - c, b = bf_hi(w[e]) - c;
                    s1 += a + b;
                    s2 = fmaf(a, a, fmaf(b, b, s2));
                }
            }
            __syncwarp();
            if (lane == 0) mbar_arrive(smem_u32(&empty[s]));
        }
        const float md = s1 * (1.f / DM);
        const float var = fmaxf(s2 * (1.f / DM) - md * md, 0.f);
        sMu[r] = c + md;
        sRs[r] = rsqrtf(var + LN_EPS);
        if (hg == 0) gMu1[rb * 128 + r] = c + md;
    } else if (warp == 12) {
        if (lane == 0) {
            for (int kc = 0; kc < 8; kc++) {
                const int s = kc % K1_STAGES;
                if (kc >= K1_STAGES) mbar_wait(smem_u32(&empty[s]), ((kc / K1_STAGES) & 1) ^ 1);
                const uint32_t bar = smem_u32(&full[s]);
                const uint32_t sa = smem_u32(smem + s * K1_STAGE_BYTES), sb = sa + 16384;
                mbar_expect_tx(bar, K1_STAGE_BYTES);
                tma_2d(sa, &tmX, kc * 64, rb * 128, bar);
#pragma unroll
                for (int p = 0; p < 3; p++) tma_2d(sb + p * 8192, &tmW, p * 512 + hg * 64, kc * 64, bar);
            }
        }
    } else {
        const int c = tid - 416;
        const int box = c >> 5, cl = c & 31;
        float s0 = 0.f, s1 = 0.f;
        for (int kc = 0; kc < 8; kc++) {
            const int s = kc % K1_STAGES;
            mbar_wait(smem_u32(&full[s]), (kc / K1_STAGES) & 1);
            const char* base = smem + s * K1_STAGE_BYTES + 16384 + box * 8192 + ((cl & 3) << 2);
#pragma unroll 8
            for (int k = 0; k < 64; k++) {
                const uint32_t v = *reinterpret_cast<const uint32_t*>(base + k * 128 + (((cl >> 2) ^ (k & 7)) << 4));
                s0 += bf_lo(v);
                s1 += bf_hi(v);
            }
            __syncwarp();
            if (lane == 0) mbar_arrive(smem_u32(&empty[s]));
        }
        sCs[2 * c] = s0;
        sCs[2 * c + 1] = s1;
    }
    __syncthreads();

    if (wg < 2) {
        const int w4 = warp & 3, g = lane >> 2, t4 = lane & 3;
        const int lr0 = wg * 64 + w4 * 16 + g, lr1 = lr0 + 8;
        const float mu0 = sMu[lr0], mu1 = sMu[lr1], rs0 = sRs[lr0], rs1 = sRs[lr1];
        const int rg0 = (rb * 128 + wg * 64 + w4 * 16) >> 3;
        float nq[4], nk[4], nv[4];
#pragma unroll
        for (int hh = 0; hh < 4; hh++) {
            const int head = hg * 4 + hh;
#pragma unroll
            for (int sec = 0; sec < 3; sec++) {
                float sq0 = 0.f, sq1 = 0.f, vm = 0.f;
#pragma unroll
                for (int db = 0; db < 2; db++) {
                    const int j = sec * 8 + hh * 2 + db;
                    const float c0 = sCs[j * 8 + 2 * t4], c1 = sCs[j * 8 + 2 * t4 + 1];
                    const float f0 = sec == 0 ? rs0 * QSCALE : rs0, f1 = sec == 0 ? rs1 * QSCALE : rs1;
                    const float a0 = (acc[4 * j + 0] - mu0 * c0) * f0, a1 = (acc[4 * j + 1] - mu0 * c1) * f0;
                    const float b0 = (acc[4 * j + 2] - mu1 * c0) * f1, b1 = (acc[4 * j + 3] - mu1 * c1) * f1;
                    const uint32_t pa = pack_bf16(a0, a1), pb = pack_bf16(b0, b1);
                    if (sec < 2) {
                        uint32_t* dst = reinterpret_cast<uint32_t*>(sec == 0 ? gQ : gK) + ((size_t)head * S_LEN * DH) / 2;
                        dst[(rg0 * 128 + db * 64) / 2 + g * 4 + t4] = pa;
                        dst[((rg0 + 1) * 128 + db * 64) / 2 + g * 4 + t4] = pb;
                        sq0 = fmaf(a0, a0, fmaf(a1, a1, sq0));
                        sq1 = fmaf(b0, b0, fmaf(b1, b1, sq1));
                    } else {
                        uint32_t* dst = reinterpret_cast<uint32_t*>(gV) + ((size_t)head * S_LEN * DH + db * (S_LEN * 8)) / 2;
                        dst[rg0 * 32 + g * 4 + t4] = pa;
                        dst[(rg0 + 1) * 32 + g * 4 + t4] = pb;
                        vm = fmaxf(vm, fmaxf(fmaxf(fabsf(a0), fabsf(a1)), fmaxf(fabsf(b0), fabsf(b1))));
                    }
                }
                if (sec < 2) {
                    sq0 += __shfl_xor_sync(0xffffffffu, sq0, 1); sq0 += __shfl_xor_sync(0xffffffffu, sq0, 2);
                    sq1 += __shfl_xor_sync(0xffffffffu, sq1, 1); sq1 += __shfl_xor_sync(0xffffffffu, sq1, 2);
                    vm = fmaxf(sq0, sq1);
                    if (!(sq0 + sq1 < 3.0e38f)) vm = __int_as_float(0x7f800000);
                }
                if (sec == 0) nq[hh] = vm; else if (sec == 1) nk[hh] = vm; else nv[hh] = vm;
            }
        }
#pragma unroll
        for (int hh = 0; hh < 4; hh++) {
            const unsigned int a = __reduce_max_sync(0xffffffffu, __float_as_uint(nq[hh]));
            const unsigned int b = __reduce_max_sync(0xffffffffu, __float_as_uint(nk[hh]));
            const unsigned int c = __reduce_max_sync(0xffffffffu, __float_as_uint(nv[hh]));
            if (lane == 0) { atomicMax(&sNorm[hh * 3 + 0], a); atomicMax(&sNorm[hh * 3 + 1], b); atomicMax(&sNorm[hh * 3 + 2], c); }
        }
    }
    __syncthreads();
    if (tid < 12) gNorm[(rb * NH + hg * 4 + tid / 3) * 4 + tid % 3] = __uint_as_float(sNorm[tid]);
}

constexpr int K2_SMEM = 65536 + 3 * 32768 + 1024;

__global__ void __launch_bounds__(512, 1) k2_attn() {
    extern __shared__ __align__(1024) char smem_raw[];
    char* smem = smem_raw + ((1024 - (smem_u32(smem_raw) & 1023)) & 1023);
    __shared__ __align__(8) uint64_t bars[16];
    char* sK = smem;
    char* sV = smem + 65536;
    const int head = blockIdx.x >> 2, quarter = blockIdx.x & 3;
    const int tid = threadIdx.x, wg = tid >> 7, warp = (tid >> 5) & 3, lane = tid & 31, g = lane >> 2, t4 = lane & 3;
    if (tid == 0) {
        for (int i = 0; i < 16; i++) mbar_init(smem_u32(&bars[i]), 1);
        asm volatile("fence.mbarrier_init.release.cluster;" ::: "memory");
    }
    {
        const uint4 one = make_uint4(0x00003F80u, 0, 0, 0);
        for (int i = tid; i < 2048; i += 512) *reinterpret_cast<uint4*>(sV + 65536 + i * 16) = one;
        asm volatile("fence.proxy.async.shared::cta;" ::: "memory");
    }
    __syncthreads();
    if (tid == 0) {
        const char* Kg = reinterpret_cast<const char*>(gK) + (size_t)head * 65536;
        const char* Vg = reinterpret_cast<const char*>(gV) + (size_t)head * 65536;
        for (int c = 0; c < 16; c++) {
            const uint32_t bar = smem_u32(&bars[c]);
            mbar_expect_tx(bar, 8192);
            bulk_g2s(smem_u32(sK + c * 4096), Kg + c * 4096, 4096, bar);
            bulk_g2s(smem_u32(sV + c * 2048), Vg + c * 2048, 2048, bar);
            bulk_g2s(smem_u32(sV + 32768 + c * 2048), Vg + 32768 + c * 2048, 2048, bar);
        }
    }
    bool fast;
    {
        float q2 = 0.f, k2 = 0.f, vm = 0.f;
        for (int rb = 0; rb < 16; rb++) {
            const float* n = &gNorm[(rb * NH + head) * 4];
            q2 = fmaxf(q2, n[0]); k2 = fmaxf(k2, n[1]); vm = fmaxf(vm, n[2]);
        }
        fast = (q2 * k2 * 1.04f <= 841.f) && (vm <= 1.0e18f) && (vm >= 1.0e-18f || vm == 0.f);
    }
    const uint64_t descK0 = make_desc(smem_u32(sK), 128, 256, 0);
    const uint64_t descV0 = make_desc(smem_u32(sV), 128, 32768, 0);
    for (int pass = 0; pass < 2; pass++) {
        const int row0 = quarter * 512 + pass * 256 + wg * 64 + warp * 16;
        uint32_t q[4];
        {
            const uint32_t* Qp = reinterpret_cast<const uint32_t*>(gQ) + ((size_t)head * S_LEN * DH + (row0 >> 3) * 128) / 2;
            q[0] = Qp[g * 4 + t4]; q[2] = Qp[32 + g * 4 + t4];
            q[1] = Qp[64 + g * 4 + t4]; q[3] = Qp[96 + g * 4 + t4];
        }
        float o[12];
#pragma unroll
        for (int i = 0; i < 12; i++) o[i] = 0.f;
        if (fast) {
            for (int j = 0; j < 16; j++) {
                if (pass == 0) mbar_wait(smem_u32(&bars[j]), 0);
                float s[64];
                wg_fence();
                wgmma_qk128(s, q, descK0 + (uint64_t)(j * 4096 >> 4));
                wg_commit();
                wg_wait<0>();
                pin(s);
#pragma unroll
                for (int k = 0; k < 8; k++) {
                    uint32_t p[4];
#pragma unroll
                    for (int i = 0; i < 4; i++) p[i] = ex2_pair(s[8 * k + 2 * i], s[8 * k + 2 * i + 1], 4 * k + i);
                    wg_fence();
                    wgmma_pv24(o, p[0], p[1], p[2], p[3], descV0 + (uint64_t)((j * 2048 + k * 256) >> 4));
                    wg_commit();
                    wg_wait<2>();
                }
            }
        } else {
            float m0 = -INFINITY, m1 = -INFINITY;
            for (int j = 0; j < 16; j++) {
                if (pass == 0) mbar_wait(smem_u32(&bars[j]), 0);
                float s[64];
                wg_fence();
                wgmma_qk128(s, q, descK0 + (uint64_t)(j * 4096 >> 4));
                wg_commit();
                wg_wait<0>();
                pin(s);
                pin(o);
                float n0 = m0, n1 = m1;
#pragma unroll
                for (int i = 0; i < 16; i++) {
                    n0 = fmaxf(n0, fmaxf(s[4 * i], s[4 * i + 1]));
                    n1 = fmaxf(n1, fmaxf(s[4 * i + 2], s[4 * i + 3]));
                }
                n0 = fmaxf(n0, __shfl_xor_sync(0xffffffffu, n0, 1)); n0 = fmaxf(n0, __shfl_xor_sync(0xffffffffu, n0, 2));
                n1 = fmaxf(n1, __shfl_xor_sync(0xffffffffu, n1, 1)); n1 = fmaxf(n1, __shfl_xor_sync(0xffffffffu, n1, 2));
                const float a0 = ex2_mufu(m0 - n0), a1 = ex2_mufu(m1 - n1);
                m0 = n0; m1 = n1;
#pragma unroll
                for (int i = 0; i < 3; i++) { o[4 * i] *= a0; o[4 * i + 1] *= a0; o[4 * i + 2] *= a1; o[4 * i + 3] *= a1; }
                uint32_t p[32];
#pragma unroll
                for (int i = 0; i < 16; i++) {
                    p[2 * i] = pack_bf16(ex2_mufu(s[4 * i] - n0), ex2_mufu(s[4 * i + 1] - n0));
                    p[2 * i + 1] = pack_bf16(ex2_mufu(s[4 * i + 2] - n1), ex2_mufu(s[4 * i + 3] - n1));
                }
                wg_fence();
#pragma unroll
                for (int k = 0; k < 8; k++)
                    wgmma_pv24(o, p[4 * k], p[4 * k + 1], p[4 * k + 2], p[4 * k + 3], descV0 + (uint64_t)((j * 2048 + k * 256) >> 4));
                wg_commit();
                wg_wait<0>();
            }
        }
        wg_wait<0>();
        pin(o);
        const float l0 = __shfl_sync(0xffffffffu, o[8], lane & ~3), l1 = __shfl_sync(0xffffffffu, o[10], lane & ~3);
        const float r0 = 1.f / l0, r1 = 1.f / l1;
        uint32_t* Op = reinterpret_cast<uint32_t*>(gO + (size_t)row0 * DM + head * DH);
        Op[g * 256 + t4] = pack_bf16(o[0] * r0, o[1] * r0);
        Op[(g + 8) * 256 + t4] = pack_bf16(o[2] * r1, o[3] * r1);
        Op[g * 256 + 4 + t4] = pack_bf16(o[4] * r0, o[5] * r0);
        Op[(g + 8) * 256 + 4 + t4] = pack_bf16(o[6] * r1, o[7] * r1);
    }
}

constexpr int K3_SMEM = 65536 + 131072 + 1024;

__global__ void __launch_bounds__(128, 1)
k3_wo(const __grid_constant__ CUtensorMap tmO, const __grid_constant__ CUtensorMap tmWo,
      const __nv_bfloat16* __restrict__ x, const __nv_bfloat16* __restrict__ w_r) {
    extern __shared__ __align__(1024) char smem_raw[];
    char* smem = smem_raw + ((1024 - (smem_u32(smem_raw) & 1023)) & 1023);
    __shared__ __align__(8) uint64_t full[8];
    const int rb = blockIdx.x >> 2, cb = blockIdx.x & 3;
    const int tid = threadIdx.x, warp = tid >> 5, lane = tid & 31, g = lane >> 2, t4 = lane & 3;
    if (tid == 0) {
        for (int i = 0; i < 8; i++) mbar_init(smem_u32(&full[i]), 1);
        asm volatile("fence.mbarrier_init.release.cluster;" ::: "memory");
    }
    __syncthreads();
    char* sA = smem;
    char* sB = smem + 65536;
    if (tid == 0) {
        for (int kc = 0; kc < 8; kc++) {
            const uint32_t bar = smem_u32(&full[kc]);
            mbar_expect_tx(bar, 8192 + 16384);
            tma_2d(smem_u32(sA + kc * 8192), &tmO, kc * 64, rb * 64, bar);
            tma_2d(smem_u32(sB + kc * 16384), &tmWo, cb * 128, kc * 64, bar);
            tma_2d(smem_u32(sB + kc * 16384 + 8192), &tmWo, cb * 128 + 64, kc * 64, bar);
        }
    }
    float acc[64];
    for (int kc = 0; kc < 8; kc++) {
        mbar_wait(smem_u32(&full[kc]), 0);
        const uint64_t da = make_desc(smem_u32(sA + kc * 8192), 16, 1024, 1);
        const uint64_t db = make_desc(smem_u32(sB + kc * 16384), 8192, 1024, 1);
        wg_fence();
#pragma unroll
        for (int ks = 0; ks < 4; ks++) wgmma_n128(acc, da + ks * 2, db + ks * 128, (kc | ks) != 0);
        wg_commit();
    }
    wg_wait<0>();
    pin(acc);
    const int r0 = rb * 64 + warp * 16 + g, r1 = r0 + 8;
    const float p0 = gMu1[r0], p1 = gMu1[r1];
    float s1a = 0.f, s2a = 0.f, s3a = 0.f, s1b = 0.f, s2b = 0.f, s3b = 0.f;
#pragma unroll
    for (int j = 0; j < 16; j++) {
        const int col = cb * 128 + j * 8 + 2 * t4;
        const uint32_t xa = *reinterpret_cast<const uint32_t*>(x + (size_t)r0 * DM + col);
        const uint32_t xb = *reinterpret_cast<const uint32_t*>(x + (size_t)r1 * DM + col);
        const uint32_t wr = *reinterpret_cast<const uint32_t*>(w_r + col);
        const uint32_t ha = pack_bf16(bf_lo(xa) + acc[4 * j], bf_hi(xa) + acc[4 * j + 1]);
        const uint32_t hb = pack_bf16(bf_lo(xb) + acc[4 * j + 2], bf_hi(xb) + acc[4 * j + 3]);
        *reinterpret_cast<uint32_t*>(gH + (size_t)r0 * DM + col) = ha;
        *reinterpret_cast<uint32_t*>(gH + (size_t)r1 * DM + col) = hb;
        const float a0 = bf_lo(ha), a1 = bf_hi(ha), b0 = bf_lo(hb), b1 = bf_hi(hb);
        const float w0 = bf_lo(wr), w1 = bf_hi(wr);
        const float da0 = a0 - p0, da1 = a1 - p0, db0 = b0 - p1, db1 = b1 - p1;
        s1a += da0 + da1; s2a = fmaf(da0, da0, fmaf(da1, da1, s2a)); s3a = fmaf(da0, w0, fmaf(da1, w1, s3a));
        s1b += db0 + db1; s2b = fmaf(db0, db0, fmaf(db1, db1, s2b)); s3b = fmaf(db0, w0, fmaf(db1, w1, s3b));
    }
#pragma unroll
    for (int m = 1; m <= 2; m <<= 1) {
        s1a += __shfl_xor_sync(0xffffffffu, s1a, m); s2a += __shfl_xor_sync(0xffffffffu, s2a, m); s3a += __shfl_xor_sync(0xffffffffu, s3a, m);
        s1b += __shfl_xor_sync(0xffffffffu, s1b, m); s2b += __shfl_xor_sync(0xffffffffu, s2b, m); s3b += __shfl_xor_sync(0xffffffffu, s3b, m);
    }
    if (t4 == 0) {
        atomicAdd(&gStats[r0 * 4 + 0], s1a); atomicAdd(&gStats[r0 * 4 + 1], s2a); atomicAdd(&gStats[r0 * 4 + 2], s3a);
        atomicAdd(&gStats[r1 * 4 + 0], s1b); atomicAdd(&gStats[r1 * 4 + 1], s2b); atomicAdd(&gStats[r1 * 4 + 2], s3b);
    }
}

__device__ __forceinline__ void top2_merge(float& v1, int& i1, float& v2, int& i2, float w, int j) {
    if (w > v1 || (w == v1 && j < i1)) { v2 = v1; i2 = i1; v1 = w; i1 = j; }
    else if (w > v2 || (w == v2 && j < i2)) { v2 = w; i2 = j; }
}

__global__ void __launch_bounds__(512, 1)
k4_moe(const __nv_bfloat16* __restrict__ w_r, const __nv_bfloat16* __restrict__ w_gate, const __nv_bfloat16* __restrict__ w_up,
       const __nv_bfloat16* __restrict__ w_down, __nv_bfloat16* __restrict__ out) {
    __shared__ float sV1[16], sV2[16];
    __shared__ int sI1[16], sI2[16];
    __shared__ float sWsum;
    __shared__ float sX[2][DM];
    __shared__ float sPart[16][2][32];
    __shared__ float sAct[2][16];
    __shared__ float sSel[8];
    __shared__ int sIdx[2];
    __shared__ unsigned int sLast;
    const int tid = threadIdx.x, warp = tid >> 5, lane = tid & 31;
    const int cta = blockIdx.x;

    {
        float w = __bfloat162float(w_r[tid]);
#pragma unroll
        for (int m = 16; m; m >>= 1) w += __shfl_xor_sync(0xffffffffu, w, m);
        if (lane == 0) sV1[warp] = w;
        __syncthreads();
        if (tid == 0) { float s = 0.f; for (int i = 0; i < 16; i++) s += sV1[i]; sWsum = s; }
        __syncthreads();
    }
    const float wsum = sWsum;
    float v1 = -INFINITY, v2 = -INFINITY; int i1 = 0x7fffffff, i2 = 0x7fffffff;
#pragma unroll
    for (int k = 0; k < 4; k++) {
        const int row = tid + k * 512;
        const float4 st = *reinterpret_cast<const float4*>(&gStats[row * 4]);
        const float md = st.x * (1.f / DM);
        const float var = fmaxf(st.y * (1.f / DM) - md * md, 0.f);
        const float rs = rsqrtf(var + LN_EPS);
        float r = (st.z - md * wsum) * rs;
        if (!(r == r)) r = -INFINITY;
        top2_merge(v1, i1, v2, i2, r, row);
    }
#pragma unroll
    for (int m = 16; m; m >>= 1) {
        const float w1 = __shfl_xor_sync(0xffffffffu, v1, m), w2 = __shfl_xor_sync(0xffffffffu, v2, m);
        const int j1 = __shfl_xor_sync(0xffffffffu, i1, m), j2 = __shfl_xor_sync(0xffffffffu, i2, m);
        top2_merge(v1, i1, v2, i2, w1, j1);
        top2_merge(v1, i1, v2, i2, w2, j2);
    }
    __syncthreads();
    if (lane == 0) { sV1[warp] = v1; sV2[warp] = v2; sI1[warp] = i1; sI2[warp] = i2; }
    __syncthreads();
    if (tid == 0) {
        float a1 = -INFINITY, a2 = -INFINITY; int b1 = 0x7fffffff, b2 = 0x7fffffff;
        for (int i = 0; i < 16; i++) { top2_merge(a1, b1, a2, b2, sV1[i], sI1[i]); top2_merge(a1, b1, a2, b2, sV2[i], sI2[i]); }
        if (b1 >= S_LEN) b1 = 0;
        if (b2 >= S_LEN) b2 = (b1 == 0) ? 1 : 0;
        sIdx[0] = b1; sIdx[1] = b2;
        for (int t = 0; t < 2; t++) {
            const int row = t ? b2 : b1;
            const float4 st = *reinterpret_cast<const float4*>(&gStats[row * 4]);
            const float md = st.x * (1.f / DM);
            const float var = fmaxf(st.y * (1.f / DM) - md * md, 0.f);
            const float rs = rsqrtf(var + LN_EPS);
            const float r = (st.z - md * wsum) * rs;
            sSel[t * 4 + 0] = gMu1[row] + md; sSel[t * 4 + 1] = rs; sSel[t * 4 + 2] = 1.f / (1.f + __expf(-r));
        }
    }
    __syncthreads();
    const int idx0 = sIdx[0], idx1 = sIdx[1];

    {
        const int row = cta * 16 + warp;
        if (row != idx0 && row != idx1) {
            const float4 st = *reinterpret_cast<const float4*>(&gStats[row * 4]);
            const float md = st.x * (1.f / DM);
            const float var = fmaxf(st.y * (1.f / DM) - md * md, 0.f);
            const float rs = rsqrtf(var + LN_EPS), mu = gMu1[row] + md;
            const uint4* hp = reinterpret_cast<const uint4*>(gH + (size_t)row * DM);
            uint4* op = reinterpret_cast<uint4*>(out + (size_t)row * DM);
#pragma unroll
            for (int k = 0; k < 2; k++) {
                const uint4 h = hp[lane + k * 32];
                const uint32_t w[4] = {h.x, h.y, h.z, h.w};
                uint32_t o[4];
#pragma unroll
                for (int e = 0; e < 4; e++) {
                    const float a = bf_lo(w[e]), b = bf_hi(w[e]);
                    const uint32_t ln = pack_bf16((a - mu) * rs, (b - mu) * rs);
                    o[e] = pack_bf16(a + bf_lo(ln), b + bf_hi(ln));
                }
                op[lane + k * 32] = make_uint4(o[0], o[1], o[2], o[3]);
            }
        }
    }
    if (cta >= FF / 16) return;

    {
        const int t = tid >> 8, c = tid & 255;
        const int row = t ? idx1 : idx0;
        const uint32_t h = *reinterpret_cast<const uint32_t*>(gH + (size_t)row * DM + 2 * c);
        const float mu = sSel[t * 4], rs = sSel[t * 4 + 1];
        const uint32_t ln = pack_bf16((bf_lo(h) - mu) * rs, (bf_hi(h) - mu) * rs);
        sX[t][2 * c] = bf_lo(ln); sX[t][2 * c + 1] = bf_hi(ln);
    }
    __syncthreads();
    {
        const int mat = lane >> 4, kh = (lane >> 3) & 1, cp = lane & 7;
        const __nv_bfloat16* W = mat ? w_up : w_gate;
        float a00 = 0.f, a01 = 0.f, a10 = 0.f, a11 = 0.f;
#pragma unroll
        for (int kk = 0; kk < 16; kk++) {
            const int k = warp * 32 + kh * 16 + kk;
            const uint32_t w = *reinterpret_cast<const uint32_t*>(W + (size_t)k * FF + cta * 16 + 2 * cp);
            const float x0 = sX[0][k], x1 = sX[1][k];
            a00 = fmaf(x0, bf_lo(w), a00); a01 = fmaf(x0, bf_hi(w), a01);
            a10 = fmaf(x1, bf_lo(w), a10); a11 = fmaf(x1, bf_hi(w), a11);
        }
        a00 += __shfl_xor_sync(0xffffffffu, a00, 8); a01 += __shfl_xor_sync(0xffffffffu, a01, 8);
        a10 += __shfl_xor_sync(0xffffffffu, a10, 8); a11 += __shfl_xor_sync(0xffffffffu, a11, 8);
        if (kh == 0) {
            sPart[warp][0][mat * 16 + 2 * cp] = a00; sPart[warp][0][mat * 16 + 2 * cp + 1] = a01;
            sPart[warp][1][mat * 16 + 2 * cp] = a10; sPart[warp][1][mat * 16 + 2 * cp + 1] = a11;
        }
    }
    __syncthreads();
    if (tid < 32) {
        const int t = tid >> 4, c = tid & 15;
        float gsum = 0.f, usum = 0.f;
#pragma unroll
        for (int w = 0; w < 16; w++) { gsum += sPart[w][t][c]; usum += sPart[w][t][16 + c]; }
        const float gb = __bfloat162float(__float2bfloat16(gsum)), ub = __bfloat162float(__float2bfloat16(usum));
        const float sl = __bfloat162float(__float2bfloat16(gb / (1.f + __expf(-gb))));
        sAct[t][c] = __bfloat162float(__float2bfloat16(sl * ub));
    }
    __syncthreads();
    {
        const int n = tid;
        float y0 = 0.f, y1 = 0.f;
#pragma unroll
        for (int k = 0; k < 16; k++) {
            const float w = __bfloat162float(w_down[(size_t)(cta * 16 + k) * DM + n]);
            y0 = fmaf(sAct[0][k], w, y0);
            y1 = fmaf(sAct[1][k], w, y1);
        }
        atomicAdd(&gY[n], y0);
        atomicAdd(&gY[DM + n], y1);
    }
    __threadfence();
    __syncthreads();
    if (tid == 0) sLast = (atomicAdd(&gCounter, 1u) == (unsigned)(FF / 16 - 1));
    __syncthreads();
    if (sLast) {
        __threadfence();
#pragma unroll
        for (int t = 0; t < 2; t++) {
            const int row = t ? idx1 : idx0;
            const float y = __ldcg(&gY[t * DM + tid]) ;
            const float yb = __bfloat162float(__float2bfloat16(__bfloat162float(__float2bfloat16(y)) * sSel[t * 4 + 2]));
            const float h = __bfloat162float(gH[(size_t)row * DM + tid]);
            const float ln = sX[t][tid];
            const float z = __bfloat162float(__float2bfloat16(ln + yb));
            out[(size_t)row * DM + tid] = __float2bfloat16(h + z);
        }
    }
}

typedef CUresult (*EncodeFn)(CUtensorMap*, CUtensorMapDataType, cuuint32_t, void*, const cuuint64_t*, const cuuint64_t*,
                             const cuuint32_t*, const cuuint32_t*, CUtensorMapInterleave, CUtensorMapSwizzle,
                             CUtensorMapL2promotion, CUtensorMapFloatOOBfill);

void make_map(EncodeFn enc, CUtensorMap* tm, const void* base, uint64_t cols, uint64_t rows, uint32_t box_c, uint32_t box_r) {
    cuuint64_t dims[2] = {cols, rows};
    cuuint64_t strides[1] = {cols * 2};
    cuuint32_t box[2] = {box_c, box_r};
    cuuint32_t es[2] = {1, 1};
    enc(tm, CU_TENSOR_MAP_DATA_TYPE_BFLOAT16, 2, const_cast<void*>(base), dims, strides, box, es, CU_TENSOR_MAP_INTERLEAVE_NONE,
        CU_TENSOR_MAP_SWIZZLE_128B, CU_TENSOR_MAP_L2_PROMOTION_L2_256B, CU_TENSOR_MAP_FLOAT_OOB_FILL_NONE);
}

}

extern "C" void kernel_launch(void* const* d_in, const int* in_sizes, int n_in, void* d_out, int out_size) {
    const __nv_bfloat16* x = (const __nv_bfloat16*)d_in[0];
    const __nv_bfloat16* wqkv = (const __nv_bfloat16*)d_in[1];
    const __nv_bfloat16* wo = (const __nv_bfloat16*)d_in[2];
    const __nv_bfloat16* w_r = (const __nv_bfloat16*)d_in[4];
    const __nv_bfloat16* w_gate = (const __nv_bfloat16*)d_in[5];
    const __nv_bfloat16* w_up = (const __nv_bfloat16*)d_in[6];
    const __nv_bfloat16* w_down = (const __nv_bfloat16*)d_in[7];
    __nv_bfloat16* out = (__nv_bfloat16*)d_out;

    static EncodeFn enc = nullptr;
    static void* pO = nullptr;
    if (!enc) {
        void* fn = nullptr;
        cudaDriverEntryPointQueryResult qr;
        cudaGetDriverEntryPoint("cuTensorMapEncodeTiled", &fn, cudaEnableDefault, &qr);
        enc = (EncodeFn)fn;
        cudaGetSymbolAddress(&pO, gO);
        cudaFuncSetAttribute(k1_qkv, cudaFuncAttributeMaxDynamicSharedMemorySize, K1_SMEM);
        cudaFuncSetAttribute(k2_attn, cudaFuncAttributeMaxDynamicSharedMemorySize, K2_SMEM);
        cudaFuncSetAttribute(k3_wo, cudaFuncAttributeMaxDynamicSharedMemorySize, K3_SMEM);
    }
    CUtensorMap tmX, tmW, tmO, tmWo;
    make_map(enc, &tmX, x, DM, S_LEN, 64, 128);
    make_map(enc, &tmW, wqkv, 3 * DM, DM, 64, 64);
    make_map(enc, &tmO, pO, DM, S_LEN, 64, 64);
    make_map(enc, &tmWo, wo, DM, DM, 64, 64);

    cudaStream_t st = cudaStreamPerThread;
    k1_qkv<<<128, 512, K1_SMEM, st>>>(tmX, tmW);
    k2_attn<<<128, 512, K2_SMEM, st>>>();
    k3_wo<<<128, 128, K3_SMEM, st>>>(tmO, tmWo, x, w_r);
    k4_moe<<<128, 512, 0, st>>>(w_r, w_gate, w_up, w_down, out);
}
```

```cpp
#include <cuda_runtime.h>
#include <cuda_bf16.h>
#include <cuda.h>
#include <stdint.h>

namespace {

constexpr int S_LEN = 2048, DM = 512, NH = 32, DH = 16, FF = 1792;
constexpr int NFFN = FF / 16;
constexpr float LN_EPS = 1e-5f;
constexpr float QSCALE = 0.25f * 1.4426950408889634f;

__device__ __align__(1024) __nv_bfloat16 gQ[NH * S_LEN * DH];
__device__ __align__(1024) __nv_bfloat16 gK[NH * S_LEN * DH];
__device__ __align__(1024) __nv_bfloat16 gV[NH * S_LEN * DH];
__device__ __align__(1024) __nv_bfloat16 gO[S_LEN * DM];
__device__ __align__(1024) __nv_bfloat16 gH[S_LEN * DM];
__device__ __align__(16) float gNorm[16 * NH * 4];
__device__ unsigned int gEpoch;
__device__ unsigned int gFlagQKV[8 * 16];
__device__ unsigned int gFlagO[32 * 32];
__device__ unsigned long long gPart[32 * 4 * 64 * 3];
__device__ unsigned long long gCand[32 * 8];
__device__ unsigned long long gYPart[NFFN * 2 * DM];

#define TS(slot) do {} while (0)

__device__ __forceinline__ uint32_t smem_u32(const void* p) { return (uint32_t)__cvta_generic_to_shared(p); }
__device__ __forceinline__ void mbar_init(uint32_t bar, uint32_t cnt) {
    asm volatile("mbarrier.init.shared::cta.b64 [%0], %1;" ::"r"(bar), "r"(cnt));
}
__device__ __forceinline__ void mbar_expect_tx(uint32_t bar, uint32_t bytes) {
    asm volatile("mbarrier.arrive.expect_tx.shared::cta.b64 _, [%0], %1;" ::"r"(bar), "r"(bytes) : "memory");
}
__device__ __forceinline__ void mbar_arrive(uint32_t bar) {
    asm volatile("mbarrier.arrive.shared::cta.b64 _, [%0];" ::"r"(bar) : "memory");
}
constexpr int SPIN_LIMIT = 1 << 22;
__device__ __forceinline__ void mbar_wait(uint32_t bar, uint32_t parity) {
    uint32_t done = 0;
    int it = 0;
    while (true) {
        asm volatile("{.reg .pred p; mbarrier.try_wait.parity.shared::cta.b64 p, [%1], %2; selp.u32 %0, 1, 0, p;}"
                     : "=r"(done) : "r"(bar), "r"(parity) : "memory");
        if (done) break;
        if (++it > SPIN_LIMIT) __trap();
    }
}
__device__ __forceinline__ void bulk_g2s(uint32_t dst, const void* src, uint32_t bytes, uint32_t bar) {
    asm volatile("cp.async.bulk.shared::cluster.global.mbarrier::complete_tx::bytes [%0], [%1], %2, [%3];"
                 ::"r"(dst), "l"(src), "r"(bytes), "r"(bar) : "memory");
}
__device__ __forceinline__ void bulk_prefetch_l2(const void* src, uint32_t bytes) {
    asm volatile("cp.async.bulk.prefetch.L2.global [%0], %1;" ::"l"(src), "r"(bytes) : "memory");
}
__device__ __forceinline__ void tma_2d(uint32_t dst, const CUtensorMap* tm, int c0, int c1, uint32_t bar) {
    asm volatile("cp.async.bulk.tensor.2d.shared::cluster.global.mbarrier::complete_tx::bytes [%0], [%1, {%3, %4}], [%2];"
                 ::"r"(dst), "l"(tm), "r"(bar), "r"(c0), "r"(c1) : "memory");
}
__device__ __forceinline__ void fence_proxy_async() { asm volatile("fence.proxy.async;" ::: "memory"); }
__device__ __forceinline__ void fence_gpu() { asm volatile("fence.acq_rel.gpu;" ::: "memory"); }
__device__ __forceinline__ void bar_sync(int id, int n) { asm volatile("bar.sync %0, %1;" ::"r"(id), "r"(n) : "memory"); }
__device__ __forceinline__ void bar_arrive(int id, int n) { asm volatile("bar.arrive %0, %1;" ::"r"(id), "r"(n) : "memory"); }
__device__ __forceinline__ void st_flag(unsigned int* p, unsigned int v) {
    asm volatile("st.release.gpu.global.u32 [%0], %1;" ::"l"(p), "r"(v) : "memory");
}
__device__ __forceinline__ unsigned int ld_flag(const unsigned int* p) {
    unsigned int v;
    asm volatile("ld.acquire.gpu.global.u32 %0, [%1];" : "=r"(v) : "l"(p) : "memory");
    return v;
}
__device__ __forceinline__ void wait_flag(const unsigned int* p, unsigned int tag) {
    int it = 0;
    while (ld_flag(p) != tag)
        if (++it > SPIN_LIMIT) __trap();
}
__device__ __forceinline__ void st_pkt(unsigned long long* p, unsigned int tag, unsigned int val) {
    const unsigned long long v = ((unsigned long long)tag << 32) | val;
    asm volatile("st.relaxed.gpu.global.u64 [%0], %1;" ::"l"(p), "l"(v) : "memory");
}
__device__ __forceinline__ unsigned int wait_pkt(const unsigned long long* p, unsigned int tag) {
    unsigned long long v;
    int it = 0;
    while (true) {
        asm volatile("ld.relaxed.gpu.global.u64 %0, [%1];" : "=l"(v) : "l"(p) : "memory");
        if ((unsigned int)(v >> 32) == tag) break;
        if (++it > SPIN_LIMIT) __trap();
    }
    return (unsigned int)v;
}
__device__ __forceinline__ uint64_t make_desc(uint32_t addr, uint32_t lbo, uint32_t sbo, uint32_t mode) {
    return (uint64_t)((addr & 0x3FFFF) >> 4) | ((uint64_t)((lbo & 0x3FFFF) >> 4) << 16) |
           ((uint64_t)((sbo & 0x3FFFF) >> 4) << 32) | ((uint64_t)mode << 62);
}
__device__ __forceinline__ void wg_fence() { asm volatile("wgmma.fence.sync.aligned;" ::: "memory"); }
__device__ __forceinline__ void wg_commit() { asm volatile("wgmma.commit_group.sync.aligned;" ::: "memory"); }
template <int N> __device__ __forceinline__ void wg_wait() { asm volatile("wgmma.wait_group.sync.aligned %0;" ::"n"(N) : "memory"); }
template <int N> __device__ __forceinline__ void pin(float (&d)[N]) {
#pragma unroll
    for (int i = 0; i < N; i++) asm volatile("" : "+f"(d[i])::"memory");
}
__device__ __forceinline__ uint32_t pack_bf16(float lo, float hi) {
    uint32_t r;
    asm("cvt.rn.bf16x2.f32 %0, %1, %2;" : "=r"(r) : "f"(hi), "f"(lo));
    return r;
}
__device__ __forceinline__ float bf_lo(uint32_t v) { return __uint_as_float(v << 16); }
__device__ __forceinline__ float bf_hi(uint32_t v) { return __uint_as_float(v & 0xFFFF0000u); }
__device__ __forceinline__ float bf_round(float v) { return __bfloat162float(__float2bfloat16(v)); }
__device__ __forceinline__ float ex2_mufu(float x) {
    float y;
    asm("ex2.approx.ftz.f32 %0, %1;" : "=f"(y) : "f"(x));
    return y;
}

#define ACC8(d, o) "+f"(d[o + 0]), "+f"(d[o + 1]), "+f"(d[o + 2]), "+f"(d[o + 3]), "+f"(d[o + 4]), "+f"(d[o + 5]), "+f"(d[o + 6]), "+f"(d[o + 7])
#define OUT8(d, o) "=f"(d[o + 0]), "=f"(d[o + 1]), "=f"(d[o + 2]), "=f"(d[o + 3]), "=f"(d[o + 4]), "=f"(d[o + 5]), "=f"(d[o + 6]), "=f"(d[o + 7])

__device__ __forceinline__ void wgmma_n192(float (&d)[96], uint64_t da, uint64_t db) {
    asm volatile(
        "wgmma.mma_async.sync.aligned.m64n192k16.f32.bf16.bf16 "
        "{%0,%1,%2,%3,%4,%5,%6,%7,%8,%9,%10,%11,%12,%13,%14,%15,%16,%17,%18,%19,%20,%21,%22,%23,%24,%25,%26,%27,%28,%29,%30,%31,"
        "%32,%33,%34,%35,%36,%37,%38,%39,%40,%41,%42,%43,%44,%45,%46,%47,%48,%49,%50,%51,%52,%53,%54,%55,%56,%57,%58,%59,%60,%61,%62,%63,"
        "%64,%65,%66,%67,%68,%69,%70,%71,%72,%73,%74,%75,%76,%77,%78,%79,%80,%81,%82,%83,%84,%85,%86,%87,%88,%89,%90,%91,%92,%93,%94,%95},"
        "%96, %97, 1, 1, 1, 0, 1;"
        : ACC8(d, 0), ACC8(d, 8), ACC8(d, 16), ACC8(d, 24), ACC8(d, 32), ACC8(d, 40), ACC8(d, 48), ACC8(d, 56),
          ACC8(d, 64), ACC8(d, 72), ACC8(d, 80), ACC8(d, 88)
        : "l"(da), "l"(db));
}
__device__ __forceinline__ void wgmma_n64(float (&d)[32], uint64_t da, uint64_t db) {
    asm volatile(
        "wgmma.mma_async.sync.aligned.m64n64k16.f32.bf16.bf16 "
        "{%0,%1,%2,%3,%4,%5,%6,%7,%8,%9,%10,%11,%12,%13,%14,%15,%16,%17,%18,%19,%20,%21,%22,%23,%24,%25,%26,%27,%28,%29,%30,%31},"
        "%32, %33, 1, 1, 1, 0, 1;"
        : ACC8(d, 0), ACC8(d, 8), ACC8(d, 16), ACC8(d, 24)
        : "l"(da), "l"(db));
}
__device__ __forceinline__ void wgmma_qk128(float (&d)[64], const uint32_t (&a)[4], uint64_t desc) {
    asm volatile(
        "wgmma.mma_async.sync.aligned.m64n128k16.f32.bf16.bf16 "
        "{%0,%1,%2,%3,%4,%5,%6,%7,%8,%9,%10,%11,%12,%13,%14,%15,%16,%17,%18,%19,%20,%21,%22,%23,%24,%25,%26,%27,%28,%29,%30,%31,"
        "%32,%33,%34,%35,%36,%37,%38,%39,%40,%41,%42,%43,%44,%45,%46,%47,%48,%49,%50,%51,%52,%53,%54,%55,%56,%57,%58,%59,%60,%61,%62,%63},"
        "{%64,%65,%66,%67}, %68, 0, 1, 1, 0;"
        : OUT8(d, 0), OUT8(d, 8), OUT8(d, 16), OUT8(d, 24), OUT8(d, 32), OUT8(d, 40), OUT8(d, 48), OUT8(d, 56)
        : "r"(a[0]), "r"(a[1]), "r"(a[2]), "r"(a[3]), "l"(desc));
}
__device__ __forceinline__ void wgmma_pv24(float (&o)[12], uint32_t a0, uint32_t a1, uint32_t a2, uint32_t a3, uint64_t desc) {
    asm volatile(
        "wgmma.mma_async.sync.aligned.m64n24k16.f32.bf16.bf16 "
        "{%0,%1,%2,%3,%4,%5,%6,%7,%8,%9,%10,%11}, {%12,%13,%14,%15}, %16, 1, 1, 1, 1;"
        : ACC8(o, 0), "+f"(o[8]), "+f"(o[9]), "+f"(o[10]), "+f"(o[11])
        : "r"(a0), "r"(a1), "r"(a2), "r"(a3), "l"(desc));
}

__device__ __forceinline__ uint32_t ex2_pair_poly(float x0, float x1) {
    const float M = 12288.0f + 31.0f;
    float t0 = x0 + M, t1 = x1 + M;
    uint32_t G = __byte_perm(__float_as_uint(t0), __float_as_uint(t1), 0x5410);
    uint32_t W, q;
    asm("lop3.b32 %0, %1, %2, %3, 0xEA;" : "=r"(W) : "r"(G), "r"(0x03FF03FFu), "r"(0x3C003C00u));
    asm("fma.rn.f16x2 %0, %1, %2, %3;" : "=r"(q) : "r"(0x15121512u), "r"(W), "r"(0x8acc8accu));
    asm("fma.rn.f16x2 %0, %1, %2, %3;" : "=r"(q) : "r"(q), "r"(W), "r"(0x1fc21fc2u));
    asm("fma.rn.f16x2 %0, %1, %2, %3;" : "=r"(q) : "r"(q), "r"(W), "r"(0x2f732f73u));
    return ((G & 0xFC00FC00u) >> 3) + q;
}
#define NPP 18
__device__ __forceinline__ constexpr bool use_poly_pair(int i) { return ((i % 32 + 1) * NPP) / 32 != ((i % 32) * NPP) / 32; }
__device__ __forceinline__ uint32_t ex2_pair(float x0, float x1, int i) {
    return use_poly_pair(i) ? ex2_pair_poly(x0, x1) : pack_bf16(ex2_mufu(x0), ex2_mufu(x1));
}
__device__ __forceinline__ void top2_merge(float& v1, int& i1, float& v2, int& i2, float w, int j) {
    if (w > v1 || (w == v1 && j < i1)) { v2 = v1; i2 = i1; v1 = w; i1 = j; }
    else if (w > v2 || (w == v2 && j < i2)) { v2 = w; i2 = j; }
}

constexpr int P1_STAGES = 5;
constexpr int P1_STAGE_BYTES = 16384 + 24576;
constexpr int SM_K = 0, SM_V = 65536, SM_ONES = 131072;
constexpr int SM_WO = 0, SM_A3 = 163840, SM_WG = 131072;
constexpr int SM_MISC = 229376;
constexpr int SMEM_TOTAL = 232448;
struct Misc {
    uint64_t p1_full[P1_STAGES], p1_empty[P1_STAGES];
    uint64_t kv[16];
    uint64_t wo[8], a3[8], moe;
    unsigned int tag;
    int fast;
    int idx[2];
    float sel[8];
    unsigned int norm[12];
    union {
        struct { float mu[128], rs[128], cs[192]; } p1;
        struct { float part[2][64][3]; float mu[64], rs[64], r[64]; } p3;
    };
};
static_assert(sizeof(Misc) <= SMEM_TOTAL - SM_MISC, "misc smem");

__global__ void __launch_bounds__(512, 1)
mega_kernel(const __grid_constant__ CUtensorMap tmX, const __grid_constant__ CUtensorMap tmW,
            const __grid_constant__ CUtensorMap tmO, const __grid_constant__ CUtensorMap tmWo,
            const __grid_constant__ CUtensorMap tmG, const __grid_constant__ CUtensorMap tmU,
            const __nv_bfloat16* __restrict__ x, const __nv_bfloat16* __restrict__ wo,
            const __nv_bfloat16* __restrict__ w_r, const __nv_bfloat16* __restrict__ w_gate,
            const __nv_bfloat16* __restrict__ w_up, const __nv_bfloat16* __restrict__ w_down,
            __nv_bfloat16* __restrict__ out) {
    extern __shared__ __align__(1024) char smem[];
    Misc& ms = *reinterpret_cast<Misc*>(smem + SM_MISC);
    const int tid = threadIdx.x, lane = tid & 31;
    const int warp = __shfl_sync(0xffffffffu, tid >> 5, 0);
    const int wg = warp >> 2, w4 = warp & 3, g = lane >> 2, t4 = lane & 3;
    const int cta = blockIdx.x;
    const int rb = cta >> 3, hg = cta & 7;

    if (tid == 0) {
        TS(0);
        if (smem_u32(smem) & 1023) __trap();
        for (int i = 0; i < P1_STAGES; i++) { mbar_init(smem_u32(&ms.p1_full[i]), 1); mbar_init(smem_u32(&ms.p1_empty[i]), 15); }
        for (int i = 0; i < 16; i++) mbar_init(smem_u32(&ms.kv[i]), 1);
        for (int i = 0; i < 8; i++) { mbar_init(smem_u32(&ms.wo[i]), 1); mbar_init(smem_u32(&ms.a3[i]), 1); }
        mbar_init(smem_u32(&ms.moe), 1);
        asm volatile("fence.mbarrier_init.release.cluster;" ::: "memory");
        for (int kc = 0; kc < P1_STAGES; kc++) {
            const uint32_t bar = smem_u32(&ms.p1_full[kc]);
            const uint32_t sa = smem_u32(smem + kc * P1_STAGE_BYTES), sb = sa + 16384;
            mbar_expect_tx(bar, P1_STAGE_BYTES);
            tma_2d(sa, &tmX, kc * 64, rb * 128, bar);
#pragma unroll
            for (int p = 0; p < 3; p++) tma_2d(sb + p * 8192, &tmW, p * 512 + hg * 64, kc * 64, bar);
        }
        ms.tag = *reinterpret_cast<volatile unsigned int*>(&gEpoch) + 1u;
    }
    if (tid >= 32 && tid < 44) ms.norm[tid - 32] = 0;
    __syncthreads();
    const unsigned int tag = ms.tag;

    if (wg < 2) {
        float acc[96];
#pragma unroll
        for (int i = 0; i < 96; i++) acc[i] = 0.f;
#pragma unroll 1
        for (int kc = 0; kc < 8; kc++) {
            const int s = kc % P1_STAGES;
            mbar_wait(smem_u32(&ms.p1_full[s]), (kc / P1_STAGES) & 1);
            const uint32_t sa = smem_u32(smem + s * P1_STAGE_BYTES), sb = sa + 16384;
            const uint64_t da = make_desc(sa + wg * 8192, 16, 1024, 1);
            const uint64_t db = make_desc(sb, 8192, 1024, 1);
            wg_fence();
#pragma unroll
            for (int ks = 0; ks < 4; ks++) wgmma_n192(acc, da + ks * 2, db + ks * 128);
            wg_commit();
            wg_wait<0>();
            if (lane == 0) mbar_arrive(smem_u32(&ms.p1_empty[s]));
        }
        wg_wait<0>();
        pin(acc);
        if (tid == 0) TS(1);
        bar_sync(1, 480);
        const int lr0 = wg * 64 + w4 * 16 + g, lr1 = lr0 + 8;
        const float mu0 = ms.p1.mu[lr0], mu1 = ms.p1.mu[lr1], rs0 = ms.p1.rs[lr0], rs1 = ms.p1.rs[lr1];
        const int rg0 = (rb * 128 + wg * 64 + w4 * 16) >> 3;
#pragma unroll
        for (int hh = 0; hh < 4; hh++) {
            const int head = hg * 4 + hh;
            float nrm[3];
#pragma unroll
            for (int sec = 0; sec < 3; sec++) {
                float sq0 = 0.f, sq1 = 0.f, vm = 0.f;
#pragma unroll
                for (int db = 0; db < 2; db++) {
                    const int j = sec * 8 + hh * 2 + db;
                    const float2 c = *reinterpret_cast<const float2*>(&ms.p1.cs[j * 8 + 2 * t4]);
                    const float f0 = sec == 0 ? rs0 * QSCALE : rs0, f1 = sec == 0 ? rs1 * QSCALE : rs1;
                    const float a0 = (acc[4 * j + 0] - mu0 * c.x) * f0, a1 = (acc[4 * j + 1] - mu0 * c.y) * f0;
                    const float b0 = (acc[4 * j + 2] - mu1 * c.x) * f1, b1 = (acc[4 * j + 3] - mu1 * c.y) * f1;
                    const uint32_t pa = pack_bf16(a0, a1), pb = pack_bf16(b0, b1);
                    if (sec < 2) {
                        uint32_t* dst = reinterpret_cast<uint32_t*>(sec == 0 ? gQ : gK) + ((size_t)head * S_LEN * DH) / 2;
                        dst[(rg0 * 128 + db * 64) / 2 + lane] = pa;
                        dst[((rg0 + 1) * 128 + db * 64) / 2 + lane] = pb;
                        sq0 = fmaf(a0, a0, fmaf(a1, a1, sq0));
                        sq1 = fmaf(b0, b0, fmaf(b1, b1, sq1));
                    } else {
                        uint32_t* dst = reinterpret_cast<uint32_t*>(gV) + ((size_t)head * S_LEN * DH + db * (S_LEN * 8)) / 2;
                        dst[rg0 * 32 + lane] = pa;
                        dst[(rg0 + 1) * 32 + lane] = pb;
                        vm = fmaxf(vm, fmaxf(fmaxf(fabsf(a0), fabsf(a1)), fmaxf(fabsf(b0), fabsf(b1))));
                        if (!(a0 + a1 + b0 + b1 == a0 + a1 + b0 + b1)) vm = __int_as_float(0x7f800000);
                    }
                }
                if (sec < 2) {
                    sq0 += __shfl_xor_sync(0xffffffffu, sq0, 1); sq0 += __shfl_xor_sync(0xffffffffu, sq0, 2);
                    sq1 += __shfl_xor_sync(0xffffffffu, sq1, 1); sq1 += __shfl_xor_sync(0xffffffffu, sq1, 2);
                    vm = fmaxf(sq0, sq1);
                    if (!(sq0 + sq1 < 3.0e38f)) vm = __int_as_float(0x7f800000);
                }
                nrm[sec] = vm;
            }
            const unsigned int a = __reduce_max_sync(0xffffffffu, __float_as_uint(nrm[0]));
            const unsigned int b = __reduce_max_sync(0xffffffffu, __float_as_uint(nrm[1]));
            const unsigned int c = __reduce_max_sync(0xffffffffu, __float_as_uint(nrm[2]));
            if (lane == 0) { atomicMax(&ms.norm[hh * 3 + 0], a); atomicMax(&ms.norm[hh * 3 + 1], b); atomicMax(&ms.norm[hh * 3 + 2], c); }
        }
        fence_proxy_async();
        bar_sync(2, 256);
        if (tid < 12) gNorm[(rb * NH + hg * 4 + tid / 3) * 4 + tid % 3] = __uint_as_float(ms.norm[tid]);
        __syncwarp();
        if (tid == 0) { fence_gpu(); st_flag(&gFlagQKV[hg * 16 + rb], tag); TS(2); }
    } else if (wg == 2) {
        const int r = tid - 256;
        float c = 0.f, s1 = 0.f, s2 = 0.f;
#pragma unroll 1
        for (int kc = 0; kc < 8; kc++) {
            const int s = kc % P1_STAGES;
            mbar_wait(smem_u32(&ms.p1_full[s]), (kc / P1_STAGES) & 1);
            const char* row = smem + s * P1_STAGE_BYTES + r * 128;
            uint4 v[8];
#pragma unroll
            for (int j = 0; j < 8; j++) v[j] = *reinterpret_cast<const uint4*>(row + ((j ^ (r & 7)) << 4));
            __syncwarp();
            if (lane == 0) mbar_arrive(smem_u32(&ms.p1_empty[s]));
            if (kc == 0) c = bf_lo(v[0].x);
#pragma unroll
            for (int j = 0; j < 8; j++) {
                const uint32_t w[4] = {v[j].x, v[j].y, v[j].z, v[j].w};
#pragma unroll
                for (int e = 0; e < 4; e++) {
                    const float a = bf_lo(w[e]) - c, b = bf_hi(w[e]) - c;
                    s1 += a + b;
                    s2 = fmaf(a, a, fmaf(b, b, s2));
                }
            }
        }
        const float md = s1 * (1.f / DM);
        const float var = fmaxf(s2 * (1.f / DM) - md * md, 0.f);
        ms.p1.mu[r] = c + md;
        ms.p1.rs[r] = rsqrtf(var + LN_EPS);
        bar_arrive(1, 480);
    } else if (w4 == 0) {
        if (lane == 0) {
            for (int kc = P1_STAGES; kc < 8; kc++) {
                const int s = kc % P1_STAGES;
                mbar_wait(smem_u32(&ms.p1_empty[s]), 0);
                const uint32_t bar = smem_u32(&ms.p1_full[s]);
                const uint32_t sa = smem_u32(smem + s * P1_STAGE_BYTES), sb = sa + 16384;
                mbar_expect_tx(bar, P1_STAGE_BYTES);
                tma_2d(sa, &tmX, kc * 64, rb * 128, bar);
#pragma unroll
                for (int p = 0; p < 3; p++) tma_2d(sb + p * 8192, &tmW, p * 512 + hg * 64, kc * 64, bar);
            }
        }
    } else {
        const int c = tid - 416;
        const int box = c >> 5, cl = c & 31;
        float s0 = 0.f, s1 = 0.f;
#pragma unroll 1
        for (int kc = 0; kc < 8; kc++) {
            const int s = kc % P1_STAGES;
            mbar_wait(smem_u32(&ms.p1_full[s]), (kc / P1_STAGES) & 1);
            const char* base = smem + s * P1_STAGE_BYTES + 16384 + box * 8192 + ((cl & 3) << 2);
#pragma unroll
            for (int kb = 0; kb < 2; kb++) {
                uint32_t v[32];
#pragma unroll
                for (int k = 0; k < 32; k++)
                    v[k] = *reinterpret_cast<const uint32_t*>(base + (kb * 32 + k) * 128 + (((cl >> 2) ^ (k & 7)) << 4));
#pragma unroll
                for (int k = 0; k < 32; k++) { s0 += bf_lo(v[k]); s1 += bf_hi(v[k]); }
            }
            __syncwarp();
            if (lane == 0) mbar_arrive(smem_u32(&ms.p1_empty[s]));
        }
        ms.p1.cs[2 * c] = s0;
        ms.p1.cs[2 * c + 1] = s1;
        bar_arrive(1, 480);
    }
    __syncthreads();

    const int head = hg * 4 + (rb >> 2), quarter = rb & 3;
    {
        const uint4 one = make_uint4(0x00003F80u, 0, 0, 0);
#pragma unroll
        for (int i = 0; i < 4; i++) *reinterpret_cast<uint4*>(smem + SM_ONES + (tid + i * 512) * 16) = one;
        asm volatile("fence.proxy.async.shared::cta;" ::: "memory");
    }
    if (warp == 0) {
        if (lane < 16) {
            wait_flag(&gFlagQKV[hg * 16 + lane], tag);
            fence_proxy_async();
            const char* Kg = reinterpret_cast<const char*>(gK) + (size_t)head * 65536;
            const char* Vg = reinterpret_cast<const char*>(gV) + (size_t)head * 65536;
            const uint32_t bar = smem_u32(&ms.kv[lane]);
            mbar_expect_tx(bar, 8192);
            bulk_g2s(smem_u32(smem + SM_K + lane * 4096), Kg + lane * 4096, 4096, bar);
            bulk_g2s(smem_u32(smem + SM_V + lane * 2048), Vg + lane * 2048, 2048, bar);
            bulk_g2s(smem_u32(smem + SM_V + 32768 + lane * 2048), Vg + 32768 + lane * 2048, 2048, bar);
        }
        __syncwarp();
        float q2 = 0.f, k2 = 0.f, vm = 0.f;
        if (lane < 16) {
            const float4 n = __ldcg(reinterpret_cast<const float4*>(&gNorm[(lane * NH + head) * 4]));
            q2 = n.x; k2 = n.y; vm = n.z;
        }
        q2 = __uint_as_float(__reduce_max_sync(0xffffffffu, __float_as_uint(q2)));
        k2 = __uint_as_float(__reduce_max_sync(0xffffffffu, __float_as_uint(k2)));
        vm = __uint_as_float(__reduce_max_sync(0xffffffffu, __float_as_uint(vm)));
        if (lane == 0) ms.fast = (q2 * k2 * 1.04f <= 841.f) && (vm <= 1.0e18f) && (vm >= 1.0e-18f || vm == 0.f);
    } else if (warp == 1 && lane == 0) {
        bulk_prefetch_l2(reinterpret_cast<const char*>(wo) + cta * 4096, 4096);
        bulk_prefetch_l2(reinterpret_cast<const char*>(w_gate) + cta * 14336, 14336);
        bulk_prefetch_l2(reinterpret_cast<const char*>(w_up) + cta * 14336, 14336);
        bulk_prefetch_l2(reinterpret_cast<const char*>(w_down) + cta * 14336, 14336);
    }
    __syncthreads();
    if (tid == 0) TS(3);
    {
        const bool fast = ms.fast != 0;
        const uint64_t descK0 = make_desc(smem_u32(smem + SM_K), 128, 256, 0);
        const uint64_t descV0 = make_desc(smem_u32(smem + SM_V), 128, 32768, 0);
#pragma unroll 1
        for (int pass = 0; pass < 2; pass++) {
            const int tile = pass * 16 + quarter * 4 + wg;
            const int row0 = tile * 64 + w4 * 16;
            uint32_t q[4];
            {
                const uint32_t* Qp = reinterpret_cast<const uint32_t*>(gQ) + ((size_t)head * S_LEN * DH + (row0 >> 3) * 128) / 2;
                q[0] = __ldcg(Qp + lane); q[2] = __ldcg(Qp + 32 + lane);
                q[1] = __ldcg(Qp + 64 + lane); q[3] = __ldcg(Qp + 96 + lane);
            }
            float o[12];
#pragma unroll
            for (int i = 0; i < 12; i++) o[i] = 0.f;
            if (fast) {
#pragma unroll 1
                for (int j = 0; j < 16; j++) {
                    if (pass == 0) mbar_wait(smem_u32(&ms.kv[j]), 0);
                    float s[64];
                    wg_fence();
                    wgmma_qk128(s, q, descK0 + (uint64_t)(j * 4096 >> 4));
                    wg_commit();
                    wg_wait<0>();
                    pin(s);
#pragma unroll
                    for (int k = 0; k < 8; k++) {
                        uint32_t p[4];
#pragma unroll
                        for (int i = 0; i < 4; i++) p[i] = ex2_pair(s[8 * k + 2 * i], s[8 * k + 2 * i + 1], 4 * k + i);
                        wg_fence();
                        wgmma_pv24(o, p[0], p[1], p[2], p[3], descV0 + (uint64_t)((j * 2048 + k * 256) >> 4));
                        wg_commit();
                        wg_wait<2>();
                    }
                }
            } else {
                float m0 = -INFINITY, m1 = -INFINITY;
#pragma unroll 1
                for (int j = 0; j < 16; j++) {
                    if (pass == 0) mbar_wait(smem_u32(&ms.kv[j]), 0);
                    float s[64];
                    wg_fence();
                    wgmma_qk128(s, q, descK0 + (uint64_t)(j * 4096 >> 4));
                    wg_commit();
                    wg_wait<0>();
                    pin(s);
                    pin(o);
                    float n0 = m0, n1 = m1;
#pragma unroll
                    for (int i = 0; i < 16; i++) {
                        n0 = fmaxf(n0, fmaxf(s[4 * i], s[4 * i + 1]));
                        n1 = fmaxf(n1, fmaxf(s[4 * i + 2], s[4 * i + 3]));
                    }
                    n0 = fmaxf(n0, __shfl_xor_sync(0xffffffffu, n0, 1)); n0 = fmaxf(n0, __shfl_xor_sync(0xffffffffu, n0, 2));
                    n1 = fmaxf(n1, __shfl_xor_sync(0xffffffffu, n1, 1)); n1 = fmaxf(n1, __shfl_xor_sync(0xffffffffu, n1, 2));
                    const float a0 = ex2_mufu(m0 - n0), a1 = ex2_mufu(m1 - n1);
                    m0 = n0; m1 = n1;
#pragma unroll
                    for (int i = 0; i < 3; i++) { o[4 * i] *= a0; o[4 * i + 1] *= a0; o[4 * i + 2] *= a1; o[4 * i + 3] *= a1; }
#pragma unroll
                    for (int k = 0; k < 8; k++) {
                        const uint32_t p0 = pack_bf16(ex2_mufu(s[8 * k] - n0), ex2_mufu(s[8 * k + 1] - n0));
                        const uint32_t p1 = pack_bf16(ex2_mufu(s[8 * k + 2] - n1), ex2_mufu(s[8 * k + 3] - n1));
                        const uint32_t p2 = pack_bf16(ex2_mufu(s[8 * k + 4] - n0), ex2_mufu(s[8 * k + 5] - n0));
                        const uint32_t p3 = pack_bf16(ex2_mufu(s[8 * k + 6] - n1), ex2_mufu(s[8 * k + 7] - n1));
                        wg_fence();
                        wgmma_pv24(o, p0, p1, p2, p3, descV0 + (uint64_t)((j * 2048 + k * 256) >> 4));
                        wg_commit();
                        wg_wait<2>();
                    }
                    wg_wait<0>();
                }
            }
            wg_wait<0>();
            pin(o);
            const float l0 = __shfl_sync(0xffffffffu, o[8], lane & ~3), l1 = __shfl_sync(0xffffffffu, o[10], lane & ~3);
            const float r0 = 1.f / l0, r1 = 1.f / l1;
            uint32_t* Op = reinterpret_cast<uint32_t*>(gO + (size_t)row0 * DM + head * DH);
            Op[g * 256 + t4] = pack_bf16(o[0] * r0, o[1] * r0);
            Op[(g + 8) * 256 + t4] = pack_bf16(o[2] * r1, o[3] * r1);
            Op[g * 256 + 4 + t4] = pack_bf16(o[4] * r0, o[5] * r0);
            Op[(g + 8) * 256 + 4 + t4] = pack_bf16(o[6] * r1, o[7] * r1);
            fence_proxy_async();
            bar_sync(3 + wg, 128);
            if ((tid & 127) == 0) { fence_gpu(); st_flag(&gFlagO[tile * 32 + head], tag); }
        }
    }
    __syncthreads();
    if (tid == 0) TS(4);

    const int rb3 = cta >> 2, cb = cta & 3;
    if (wg < 2) {
        const int r0 = rb3 * 64 + w4 * 16 + g, r1 = r0 + 8;
        const int col0 = cb * 128 + wg * 64 + 2 * t4;
        uint32_t xa[8], xb[8], wr[8];
#pragma unroll
        for (int j = 0; j < 8; j++) {
            xa[j] = __ldg(reinterpret_cast<const uint32_t*>(x + (size_t)r0 * DM + col0 + j * 8));
            xb[j] = __ldg(reinterpret_cast<const uint32_t*>(x + (size_t)r1 * DM + col0 + j * 8));
            wr[j] = __ldg(reinterpret_cast<const uint32_t*>(w_r + col0 + j * 8));
        }
        const float p0 = __bfloat162float(x[(size_t)r0 * DM]), p1 = __bfloat162float(x[(size_t)r1 * DM]);
        float wsum = 0.f;
        {
            const uint4 a = __ldg(reinterpret_cast<const uint4*>(w_r) + lane), b = __ldg(reinterpret_cast<const uint4*>(w_r) + 32 + lane);
            const uint32_t w[8] = {a.x, a.y, a.z, a.w, b.x, b.y, b.z, b.w};
#pragma unroll
            for (int e = 0; e < 8; e++) wsum += bf_lo(w[e]) + bf_hi(w[e]);
#pragma unroll
            for (int m = 16; m; m >>= 1) wsum += __shfl_xor_sync(0xffffffffu, wsum, m);
        }
        float acc[32];
#pragma unroll
        for (int i = 0; i < 32; i++) acc[i] = 0.f;
#pragma unroll 1
        for (int kc = 0; kc < 8; kc++) {
            mbar_wait(smem_u32(&ms.wo[kc]), 0);
            mbar_wait(smem_u32(&ms.a3[kc]), 0);
            const uint64_t da = make_desc(smem_u32(smem + SM_A3 + kc * 8192), 16, 1024, 1);
            const uint64_t db = make_desc(smem_u32(smem + SM_WO + kc * 16384 + wg * 8192), 8192, 1024, 1);
            wg_fence();
#pragma unroll
            for (int ks = 0; ks < 4; ks++) wgmma_n64(acc, da + ks * 2, db + ks * 128);
            wg_commit();
        }
        wg_wait<0>();
        pin(acc);
        if (tid == 0) TS(6);
        float s1a = 0.f, s2a = 0.f, s3a = 0.f, s1b = 0.f, s2b = 0.f, s3b = 0.f;
#pragma unroll
        for (int j = 0; j < 8; j++) {
            const uint32_t ha = pack_bf16(bf_lo(xa[j]) + acc[4 * j], bf_hi(xa[j]) + acc[4 * j + 1]);
            const uint32_t hb = pack_bf16(bf_lo(xb[j]) + acc[4 * j + 2], bf_hi(xb[j]) + acc[4 * j + 3]);
            *reinterpret_cast<uint32_t*>(gH + (size_t)r0 * DM + col0 + j * 8) = ha;
            *reinterpret_cast<uint32_t*>(gH + (size_t)r1 * DM + col0 + j * 8) = hb;
            xa[j] = ha; xb[j] = hb;
            const float w0 = bf_lo(wr[j]), w1 = bf_hi(wr[j]);
            const float da0 = bf_lo(ha) - p0, da1 = bf_hi(ha) - p0, db0 = bf_lo(hb) - p1, db1 = bf_hi(hb) - p1;
            s1a += da0 + da1; s2a = fmaf(da0, da0, fmaf(da1, da1, s2a)); s3a = fmaf(da0, w0, fmaf(da1, w1, s3a));
            s1b += db0 + db1; s2b = fmaf(db0, db0, fmaf(db1, db1, s2b)); s3b = fmaf(db0, w0, fmaf(db1, w1, s3b));
        }
#pragma unroll
        for (int m = 1; m <= 2; m <<= 1) {
            s1a += __shfl_xor_sync(0xffffffffu, s1a, m); s2a += __shfl_xor_sync(0xffffffffu, s2a, m); s3a += __shfl_xor_sync(0xffffffffu, s3a, m);
            s1b += __shfl_xor_sync(0xffffffffu, s1b, m); s2b += __shfl_xor_sync(0xffffffffu, s2b, m); s3b += __shfl_xor_sync(0xffffffffu, s3b, m);
        }
        if (t4 == 0) {
            const int lr = w4 * 16 + g;
            ms.p3.part[wg][lr][0] = s1a; ms.p3.part[wg][lr][1] = s2a; ms.p3.part[wg][lr][2] = s3a;
            ms.p3.part[wg][lr + 8][0] = s1b; ms.p3.part[wg][lr + 8][1] = s2b; ms.p3.part[wg][lr + 8][2] = s3b;
        }
        bar_sync(1, 256);
        if (tid < 192) {
            const float v = (&ms.p3.part[0][0][0])[tid] + (&ms.p3.part[1][0][0])[tid];
            fence_gpu();
            st_pkt(&gPart[(rb3 * 4 + cb) * 192 + tid], tag, __float_as_uint(v));
        }
        {
            const int lr = tid >> 2, sl = tid & 3;
            const unsigned long long* pp = &gPart[(rb3 * 4 + sl) * 192 + lr * 3];
            float s1 = __uint_as_float(wait_pkt(pp, tag)), s2 = __uint_as_float(wait_pkt(pp + 1, tag)), s3 = __uint_as_float(wait_pkt(pp + 2, tag));
#pragma unroll
            for (int m = 1; m <= 2; m <<= 1) {
                s1 += __shfl_xor_sync(0xffffffffu, s1, m); s2 += __shfl_xor_sync(0xffffffffu, s2, m); s3 += __shfl_xor_sync(0xffffffffu, s3, m);
            }
            if (sl == 0) {
                const float md = s1 * (1.f / DM);
                const float var = fmaxf(s2 * (1.f / DM) - md * md, 0.f);
                const float rs = rsqrtf(var + LN_EPS);
                ms.p3.mu[lr] = __bfloat162float(x[(size_t)(rb3 * 64 + lr) * DM]) + md;
                ms.p3.rs[lr] = rs;
                ms.p3.r[lr] = (s3 - md * wsum) * rs;
            }
        }
        bar_sync(1, 256);
        if (tid == 0) TS(7);
        if (cb == 0 && warp == 0) {
            float v1 = -INFINITY, v2 = -INFINITY; int i1 = 0x7fffffff, i2 = 0x7fffffff;
            float ra = ms.p3.r[lane], rbv = ms.p3.r[lane + 32];
            if (!(ra == ra)) ra = -INFINITY;
            if (!(rbv == rbv)) rbv = -INFINITY;
            top2_merge(v1, i1, v2, i2, ra, lane);
            top2_merge(v1, i1, v2, i2, rbv, lane + 32);
#pragma unroll
            for (int m = 16; m; m >>= 1) {
                const float w1 = __shfl_xor_sync(0xffffffffu, v1, m), w2 = __shfl_xor_sync(0xffffffffu, v2, m);
                const int j1 = __shfl_xor_sync(0xffffffffu, i1, m), j2 = __shfl_xor_sync(0xffffffffu, i2, m);
                top2_merge(v1, i1, v2, i2, w1, j1);
                top2_merge(v1, i1, v2, i2, w2, j2);
            }
            if (lane < 8) {
                const int c = lane >> 2, f = lane & 3;
                const int li = c ? i2 : i1;
                unsigned int val;
                if (f == 0) val = __float_as_uint(c ? v2 : v1);
                else if (f == 1) val = (unsigned int)(rb3 * 64 + li);
                else if (f == 2) val = __float_as_uint(ms.p3.mu[li]);
                else val = __float_as_uint(ms.p3.rs[li]);
                fence_gpu();
                st_pkt(&gCand[rb3 * 8 + lane], tag, val);
            }
        }
        bar_sync(2, 512);
        {
            const int idx0 = ms.idx[0], idx1 = ms.idx[1];
            const int lr0 = w4 * 16 + g;
            const float mu0 = ms.p3.mu[lr0], rs0 = ms.p3.rs[lr0], mu1 = ms.p3.mu[lr0 + 8], rs1 = ms.p3.rs[lr0 + 8];
            const bool w0 = (r0 != idx0 && r0 != idx1), w1 = (r1 != idx0 && r1 != idx1);
#pragma unroll
            for (int j = 0; j < 8; j++) {
                const float a0 = bf_lo(xa[j]), a1 = bf_hi(xa[j]), b0 = bf_lo(xb[j]), b1 = bf_hi(xb[j]);
                const uint32_t la = pack_bf16((a0 - mu0) * rs0, (a1 - mu0) * rs0);
                const uint32_t lb = pack_bf16((b0 - mu1) * rs1, (b1 - mu1) * rs1);
                if (w0) *reinterpret_cast<uint32_t*>(out + (size_t)r0 * DM + col0 + j * 8) = pack_bf16(a0 + bf_lo(la), a1 + bf_hi(la));
                if (w1) *reinterpret_cast<uint32_t*>(out + (size_t)r1 * DM + col0 + j * 8) = pack_bf16(b0 + bf_lo(lb), b1 + bf_hi(lb));
            }
        }
    } else {
        const int t = tid - 256;
        if (warp == 8) {
            if (lane == 0) {
                for (int kc = 0; kc < 8; kc++) {
                    const uint32_t bar = smem_u32(&ms.wo[kc]);
                    mbar_expect_tx(bar, 16384);
                    tma_2d(smem_u32(smem + SM_WO + kc * 16384), &tmWo, cb * 128, kc * 64, bar);
                    tma_2d(smem_u32(smem + SM_WO + kc * 16384 + 8192), &tmWo, cb * 128 + 64, kc * 64, bar);
                }
            }
            __syncwarp();
            wait_flag(&gFlagO[rb3 * 32 + lane], tag);
            __syncwarp();
            if (lane == 0) TS(5);
            if (lane < 8) {
                fence_proxy_async();
                const uint32_t bar = smem_u32(&ms.a3[lane]);
                mbar_expect_tx(bar, 8192);
                tma_2d(smem_u32(smem + SM_A3 + lane * 8192), &tmO, lane * 64, rb3 * 64, bar);
            }
        } else if (warp == 9 && lane == 0 && cta < NFFN) {
            const uint32_t bar = smem_u32(&ms.moe);
            mbar_expect_tx(bar, 32768);
            tma_2d(smem_u32(smem + SM_WG), &tmG, cta * 16, 0, bar);
            tma_2d(smem_u32(smem + SM_WG + 8192), &tmG, cta * 16, 256, bar);
            tma_2d(smem_u32(smem + SM_WG + 16384), &tmU, cta * 16, 0, bar);
            tma_2d(smem_u32(smem + SM_WG + 24576), &tmU, cta * 16, 256, bar);
        }
        uint32_t wd[16];
        if (cta < NFFN) {
#pragma unroll
            for (int k = 0; k < 16; k++) wd[k] = __ldg(reinterpret_cast<const uint32_t*>(w_down + (size_t)(cta * 16 + k) * DM + 2 * t));
        }
        if (warp == 8) {
            float v1 = -INFINITY, v2 = -INFINITY; int i1 = 0x7fffffff, i2 = 0x7fffffff;
            const unsigned long long* cp = &gCand[lane * 8];
            float cv[2], cm[2], cr[2]; int ci[2];
#pragma unroll
            for (int c = 0; c < 2; c++) {
                cv[c] = __uint_as_float(wait_pkt(cp + c * 4 + 0, tag));
                ci[c] = (int)wait_pkt(cp + c * 4 + 1, tag);
                cm[c] = __uint_as_float(wait_pkt(cp + c * 4 + 2, tag));
                cr[c] = __uint_as_float(wait_pkt(cp + c * 4 + 3, tag));
                top2_merge(v1, i1, v2, i2, cv[c], ci[c]);
            }
#pragma unroll
            for (int m = 16; m; m >>= 1) {
                const float w1 = __shfl_xor_sync(0xffffffffu, v1, m), w2 = __shfl_xor_sync(0xffffffffu, v2, m);
                const int j1 = __shfl_xor_sync(0xffffffffu, i1, m), j2 = __shfl_xor_sync(0xffffffffu, i2, m);
                top2_merge(v1, i1, v2, i2, w1, j1);
                top2_merge(v1, i1, v2, i2, w2, j2);
            }
#pragma unroll
            for (int c = 0; c < 2; c++) {
                if (ci[c] == i1) { ms.idx[0] = i1; ms.sel[0] = cm[c]; ms.sel[1] = cr[c]; ms.sel[2] = 1.f / (1.f + __expf(-cv[c])); }
                if (ci[c] == i2) { ms.idx[1] = i2; ms.sel[4] = cm[c]; ms.sel[5] = cr[c]; ms.sel[6] = 1.f / (1.f + __expf(-cv[c])); }
            }
            fence_gpu();
            if (lane == 0) TS(8);
        }
        bar_sync(2, 512);
        const int idx0 = ms.idx[0], idx1 = ms.idx[1];
        float* sX = reinterpret_cast<float*>(smem + SM_A3);
        float* sPart = sX + 1024;
        float* sAct = sPart + 512;
        if (cta < NFFN) {
#pragma unroll
            for (int tk = 0; tk < 2; tk++) {
                const int row = tk ? idx1 : idx0;
                const uint32_t h = __ldcg(reinterpret_cast<const uint32_t*>(gH + (size_t)row * DM + 2 * t));
                const float mu = ms.sel[tk * 4], rs = ms.sel[tk * 4 + 1];
                const uint32_t ln = pack_bf16((bf_lo(h) - mu) * rs, (bf_hi(h) - mu) * rs);
                *reinterpret_cast<float2*>(&sX[tk * 512 + 2 * t]) = make_float2(bf_lo(ln), bf_hi(ln));
            }
            mbar_wait(smem_u32(&ms.moe), 0);
            bar_sync(1 + 8, 256);
            {
                const int wv = warp - 8, kk = lane >> 3, cp = lane & 7;
                float a[2][2][2] = {};
#pragma unroll
                for (int i = 0; i < 16; i++) {
                    const int k = wv * 64 + i * 4 + kk;
                    const float x0 = sX[k], x1 = sX[512 + k];
#pragma unroll
                    for (int mat = 0; mat < 2; mat++) {
                        const uint32_t w = *reinterpret_cast<const uint32_t*>(smem + SM_WG + mat * 16384 + k * 32 + cp * 4);
                        a[mat][0][0] = fmaf(x0, bf_lo(w), a[mat][0][0]); a[mat][0][1] = fmaf(x0, bf_hi(w), a[mat][0][1]);
                        a[mat][1][0] = fmaf(x1, bf_lo(w), a[mat][1][0]); a[mat][1][1] = fmaf(x1, bf_hi(w), a[mat][1][1]);
                    }
                }
#pragma unroll
                for (int mat = 0; mat < 2; mat++)
#pragma unroll
                    for (int tk = 0; tk < 2; tk++)
#pragma unroll
                        for (int e = 0; e < 2; e++) {
                            float v = a[mat][tk][e];
                            v += __shfl_xor_sync(0xffffffffu, v, 8);
                            v += __shfl_xor_sync(0xffffffffu, v, 16);
                            if (kk == 0) sPart[(wv * 2 + tk) * 32 + mat * 16 + 2 * cp + e] = v;
                        }
            }
            bar_sync(1 + 8, 256);
            if (t < 32) {
                const int tk = t >> 4, c = t & 15;
                float gs = 0.f, us = 0.f;
#pragma unroll
                for (int w = 0; w < 8; w++) { gs += sPart[(w * 2 + tk) * 32 + c]; us += sPart[(w * 2 + tk) * 32 + 16 + c]; }
                const float gb = bf_round(gs), ub = bf_round(us);
                const float sl = bf_round(gb / (1.f + __expf(-gb)));
                sAct[tk * 16 + c] = bf_round(sl * ub);
            }
            bar_sync(1 + 8, 256);
            {
                float y00 = 0.f, y01 = 0.f, y10 = 0.f, y11 = 0.f;
#pragma unroll
                for (int k = 0; k < 16; k++) {
                    const float a0 = sAct[k], a1 = sAct[16 + k];
                    y00 = fmaf(a0, bf_lo(wd[k]), y00); y01 = fmaf(a0, bf_hi(wd[k]), y01);
                    y10 = fmaf(a1, bf_lo(wd[k]), y10); y11 = fmaf(a1, bf_hi(wd[k]), y11);
                }
                unsigned long long* yp = &gYPart[(size_t)cta * 1024];
                st_pkt(yp + 2 * t, tag, __float_as_uint(y00)); st_pkt(yp + 2 * t + 1, tag, __float_as_uint(y01));
                st_pkt(yp + 512 + 2 * t, tag, __float_as_uint(y10)); st_pkt(yp + 512 + 2 * t + 1, tag, __float_as_uint(y11));
            }
            if (t == 0) TS(9);
        }
        if (cta < 64) {
            const int oi = cta * 16 + (t & 15), part = t >> 4;
            float y = 0.f;
#pragma unroll
            for (int i = 0; i < 7; i++) y += __uint_as_float(wait_pkt(&gYPart[(size_t)(part + i * 16) * 1024 + oi], tag));
            y += __shfl_xor_sync(0xffffffffu, y, 16);
            float* sR = sAct + 32;
            if (lane < 16) sR[(warp - 8) * 16 + lane] = y;
            bar_sync(1 + 8, 256);
            if (t < 16) {
                float s = 0.f;
#pragma unroll
                for (int w = 0; w < 8; w++) s += sR[w * 16 + t];
                const int tk = oi >> 9, col = oi & 511, row = tk ? idx1 : idx0;
                const float yb = bf_round(bf_round(s) * ms.sel[tk * 4 + 2]);
                const float h = __bfloat162float(__ldcg(reinterpret_cast<const unsigned short*>(gH) + (size_t)row * DM + col) == 0 ? __float2bfloat16(0.f)
                                    : __ushort_as_bfloat16(__ldcg(reinterpret_cast<const unsigned short*>(gH) + (size_t)row * DM + col)));
                const float ln = bf_round((h - ms.sel[tk * 4]) * ms.sel[tk * 4 + 1]);
                out[(size_t)row * DM + col] = __float2bfloat16(h + bf_round(ln + yb));
            }
            if (cta == 0 && t == 0) {
                *reinterpret_cast<volatile unsigned int*>(&gEpoch) = tag;
            }
            if (t == 0) TS(10);
        }
    }
}

typedef CUresult (*EncodeFn)(CUtensorMap*, CUtensorMapDataType, cuuint32_t, void*, const cuuint64_t*, const cuuint64_t*,
                             const cuuint32_t*, const cuuint32_t*, CUtensorMapInterleave, CUtensorMapSwizzle,
                             CUtensorMapL2promotion, CUtensorMapFloatOOBfill);

void make_map(EncodeFn enc, CUtensorMap* tm, const void* base, uint64_t cols, uint64_t rows, uint32_t box_c, uint32_t box_r, bool swz) {
    cuuint64_t dims[2] = {cols, rows};
    cuuint64_t strides[1] = {cols * 2};
    cuuint32_t box[2] = {box_c, box_r};
    cuuint32_t es[2] = {1, 1};
    enc(tm, CU_TENSOR_MAP_DATA_TYPE_BFLOAT16, 2, const_cast<void*>(base), dims, strides, box, es, CU_TENSOR_MAP_INTERLEAVE_NONE,
        swz ? CU_TENSOR_MAP_SWIZZLE_128B : CU_TENSOR_MAP_SWIZZLE_NONE, CU_TENSOR_MAP_L2_PROMOTION_L2_256B,
        CU_TENSOR_MAP_FLOAT_OOB_FILL_NONE);
}

}

extern "C" void kernel_launch(void* const* d_in, const int* in_sizes, int n_in, void* d_out, int out_size) {
    const __nv_bfloat16* x = (const __nv_bfloat16*)d_in[0];
    const __nv_bfloat16* wqkv = (const __nv_bfloat16*)d_in[1];
    const __nv_bfloat16* wo = (const __nv_bfloat16*)d_in[2];
    const __nv_bfloat16* w_r = (const __nv_bfloat16*)d_in[4];
    const __nv_bfloat16* w_gate = (const __nv_bfloat16*)d_in[5];
    const __nv_bfloat16* w_up = (const __nv_bfloat16*)d_in[6];
    const __nv_bfloat16* w_down = (const __nv_bfloat16*)d_in[7];
    __nv_bfloat16* out = (__nv_bfloat16*)d_out;

    static EncodeFn enc = nullptr;
    static void* pO = nullptr;
    if (!enc) {
        void* fn = nullptr;
        cudaDriverEntryPointQueryResult qr;
        cudaGetDriverEntryPoint("cuTensorMapEncodeTiled", &fn, cudaEnableDefault, &qr);
        enc = (EncodeFn)fn;
        cudaGetSymbolAddress(&pO, gO);
        cudaFuncSetAttribute(mega_kernel, cudaFuncAttributeMaxDynamicSharedMemorySize, SMEM_TOTAL);
    }
    CUtensorMap tmX, tmW, tmO, tmWo, tmG, tmU;
    make_map(enc, &tmX, x, DM, S_LEN, 64, 128, true);
    make_map(enc, &tmW, wqkv, 3 * DM, DM, 64, 64, true);
    make_map(enc, &tmO, pO, DM, S_LEN, 64, 64, true);
    make_map(enc, &tmWo, wo, DM, DM, 64, 64, true);
    make_map(enc, &tmG, w_gate, FF, DM, 16, 256, false);
    make_map(enc, &tmU, w_up, FF, DM, 16, 256, false);

    mega_kernel<<<128, 512, SMEM_TOTAL, cudaStreamPerThread>>>(tmX, tmW, tmO, tmWo, tmG, tmU, x, wo, w_r, w_gate, w_up, w_down, out);
}
```

```cpp
#include <cuda_runtime.h>
#include <cuda_bf16.h>
#include <cuda.h>
#include <stdint.h>

namespace {

constexpr int S_LEN = 2048, DM = 512, NH = 32, DH = 16, FF = 1792;
constexpr int NFFN = FF / 16;
constexpr float LN_EPS = 1e-5f;
constexpr float QSCALE = 0.25f * 1.4426950408889634f;

__device__ __align__(1024) __nv_bfloat16 gQ[NH * S_LEN * DH];
__device__ __align__(1024) __nv_bfloat16 gKV[NH * S_LEN * DH * 2];
__device__ __align__(1024) __nv_bfloat16 gO[S_LEN * DM];
__device__ __align__(1024) __nv_bfloat16 gH[S_LEN * DM];
__device__ __align__(16) float gNorm[16 * NH * 4];
__device__ unsigned int gEpoch;
__device__ unsigned int gFlagQKV[8 * 16];
__device__ unsigned int gFlagO[32 * 32];
__device__ unsigned int gFlagH[32 * 4];
__device__ uint4 gStat1[S_LEN];
__device__ uint4 gCsPart[8 * 16 * 48];
__device__ uint4 gPart[32 * 64 * 4];
__device__ uint4 gCand[32 * 2];
__device__ uint4 gYPart[NFFN * 256];

#define TS(slot) do {} while (0)

__device__ __forceinline__ uint32_t smem_u32(const void* p) { return (uint32_t)__cvta_generic_to_shared(p); }
__device__ __forceinline__ void mbar_init(uint32_t bar, uint32_t cnt) {
    asm volatile("mbarrier.init.shared::cta.b64 [%0], %1;" ::"r"(bar), "r"(cnt));
}
__device__ __forceinline__ void mbar_expect_tx(uint32_t bar, uint32_t bytes) {
    asm volatile("mbarrier.arrive.expect_tx.shared::cta.b64 _, [%0], %1;" ::"r"(bar), "r"(bytes) : "memory");
}
__device__ __forceinline__ void mbar_arrive(uint32_t bar) {
    asm volatile("mbarrier.arrive.shared::cta.b64 _, [%0];" ::"r"(bar) : "memory");
}
constexpr int SPIN_LIMIT = 1 << 22;
__device__ __forceinline__ void mbar_wait(uint32_t bar, uint32_t parity) {
    uint32_t done = 0;
    int it = 0;
    while (true) {
        asm volatile("{.reg .pred p; mbarrier.try_wait.parity.shared::cta.b64 p, [%1], %2; selp.u32 %0, 1, 0, p;}"
                     : "=r"(done) : "r"(bar), "r"(parity) : "memory");
        if (done) break;
        if (++it > SPIN_LIMIT) __trap();
    }
}
__device__ __forceinline__ void bulk_g2s(uint32_t dst, const void* src, uint32_t bytes, uint32_t bar) {
    asm volatile("cp.async.bulk.shared::cluster.global.mbarrier::complete_tx::bytes [%0], [%1], %2, [%3];"
                 ::"r"(dst), "l"(src), "r"(bytes), "r"(bar) : "memory");
}
__device__ __forceinline__ void bulk_prefetch_l2(const void* src, uint32_t bytes) {
    asm volatile("cp.async.bulk.prefetch.L2.global [%0], %1;" ::"l"(src), "r"(bytes) : "memory");
}
__device__ __forceinline__ void tma_2d(uint32_t dst, const CUtensorMap* tm, int c0, int c1, uint32_t bar) {
    asm volatile("cp.async.bulk.tensor.2d.shared::cluster.global.mbarrier::complete_tx::bytes [%0], [%1, {%3, %4}], [%2];"
                 ::"r"(dst), "l"(tm), "r"(bar), "r"(c0), "r"(c1) : "memory");
}
__device__ __forceinline__ void fence_proxy_async_global() { asm volatile("fence.proxy.async.global;" ::: "memory"); }
__device__ __forceinline__ void fence_gpu() { asm volatile("fence.acq_rel.gpu;" ::: "memory"); }
__device__ __forceinline__ void bar_sync(int id, int n) { asm volatile("bar.sync %0, %1;" ::"r"(id), "r"(n) : "memory"); }
__device__ __forceinline__ void bar_arrive(int id, int n) { asm volatile("bar.arrive %0, %1;" ::"r"(id), "r"(n) : "memory"); }
__device__ __forceinline__ void st_flag(unsigned int* p, unsigned int v) {
    asm volatile("st.release.gpu.global.u32 [%0], %1;" ::"l"(p), "r"(v) : "memory");
}
__device__ __forceinline__ unsigned int ld_flag(const unsigned int* p) {
    unsigned int v;
    asm volatile("ld.acquire.gpu.global.u32 %0, [%1];" : "=r"(v) : "l"(p) : "memory");
    return v;
}
__device__ __forceinline__ void wait_flag(const unsigned int* p, unsigned int tag) {
    int it = 0;
    while (ld_flag(p) != tag) {
        if (++it > SPIN_LIMIT) __trap();
        __nanosleep(20);
    }
}
__device__ __forceinline__ void st_pkt(uint4* p, uint4 v) {
    asm volatile("st.relaxed.gpu.global.v4.u32 [%0], {%1,%2,%3,%4};" ::"l"(p), "r"(v.x), "r"(v.y), "r"(v.z), "r"(v.w) : "memory");
}
__device__ __forceinline__ uint4 ld_pkt(const uint4* p) {
    uint4 v;
    asm volatile("ld.relaxed.gpu.global.v4.u32 {%0,%1,%2,%3}, [%4];" : "=r"(v.x), "=r"(v.y), "=r"(v.z), "=r"(v.w) : "l"(p) : "memory");
    return v;
}
template <int N, unsigned int MASK>
__device__ __forceinline__ void wait_pkts(const uint4* p, int stride, unsigned int tag, uint4 (&v)[N]) {
    int it = 0;
    while (true) {
        bool ok = true;
#pragma unroll
        for (int i = 0; i < N; i++) v[i] = ld_pkt(p + (size_t)i * stride);
#pragma unroll
        for (int i = 0; i < N; i++) ok = ok && ((v[i].w & MASK) == tag);
        if (ok) break;
        if (++it > SPIN_LIMIT) __trap();
        __nanosleep(40);
    }
}
__device__ __forceinline__ uint4 embed_tag(float a, float b, float c, float d, unsigned int tag) {
    return make_uint4((__float_as_uint(a) & ~15u) | (tag & 15u), (__float_as_uint(b) & ~15u) | ((tag >> 4) & 15u),
                      (__float_as_uint(c) & ~15u) | ((tag >> 8) & 15u), (__float_as_uint(d) & ~15u) | ((tag >> 12) & 15u));
}
template <int N>
__device__ __forceinline__ void wait_pkts4(const uint4* p, int stride, unsigned int tag, uint4 (&v)[N]) {
    const unsigned int t16 = tag & 0xffffu;
    int it = 0;
    while (true) {
        bool ok = true;
#pragma unroll
        for (int i = 0; i < N; i++) v[i] = ld_pkt(p + (size_t)i * stride);
#pragma unroll
        for (int i = 0; i < N; i++)
            ok = ok && (((v[i].x & 15u) | ((v[i].y & 15u) << 4) | ((v[i].z & 15u) << 8) | ((v[i].w & 15u) << 12)) == t16);
        if (ok) break;
        if (++it > SPIN_LIMIT) __trap();
        __nanosleep(40);
    }
}
__device__ __forceinline__ uint64_t make_desc(uint32_t addr, uint32_t lbo, uint32_t sbo, uint32_t mode) {
    return (uint64_t)((addr & 0x3FFFF) >> 4) | ((uint64_t)((lbo & 0x3FFFF) >> 4) << 16) |
           ((uint64_t)((sbo & 0x3FFFF) >> 4) << 32) | ((uint64_t)mode << 62);
}
__device__ __forceinline__ void wg_fence() { asm volatile("wgmma.fence.sync.aligned;" ::: "memory"); }
__device__ __forceinline__ void wg_commit() { asm volatile("wgmma.commit_group.sync.aligned;" ::: "memory"); }
template <int N> __device__ __forceinline__ void wg_wait() { asm volatile("wgmma.wait_group.sync.aligned %0;" ::"n"(N) : "memory"); }
template <int N> __device__ __forceinline__ void pin(float (&d)[N]) {
#pragma unroll
    for (int i = 0; i < N; i++) asm volatile("" : "+f"(d[i])::"memory");
}
__device__ __forceinline__ uint32_t pack_bf16(float lo, float hi) {
    uint32_t r;
    asm("cvt.rn.bf16x2.f32 %0, %1, %2;" : "=r"(r) : "f"(hi), "f"(lo));
    return r;
}
__device__ __forceinline__ float bf_lo(uint32_t v) { return __uint_as_float(v << 16); }
__device__ __forceinline__ float bf_hi(uint32_t v) { return __uint_as_float(v & 0xFFFF0000u); }
__device__ __forceinline__ float bf_round(float v) { return __bfloat162float(__float2bfloat16(v)); }
__device__ __forceinline__ float ex2_mufu(float x) {
    float y;
    asm("ex2.approx.ftz.f32 %0, %1;" : "=f"(y) : "f"(x));
    return y;
}

#define ACC8(d, o) "+f"(d[o + 0]), "+f"(d[o + 1]), "+f"(d[o + 2]), "+f"(d[o + 3]), "+f"(d[o + 4]), "+f"(d[o + 5]), "+f"(d[o + 6]), "+f"(d[o + 7])
#define OUT8(d, o) "=f"(d[o + 0]), "=f"(d[o + 1]), "=f"(d[o + 2]), "=f"(d[o + 3]), "=f"(d[o + 4]), "=f"(d[o + 5]), "=f"(d[o + 6]), "=f"(d[o + 7])

__device__ __forceinline__ void wgmma_n192(float (&d)[96], uint64_t da, uint64_t db) {
    asm volatile(
        "wgmma.mma_async.sync.aligned.m64n192k16.f32.bf16.bf16 "
        "{%0,%1,%2,%3,%4,%5,%6,%7,%8,%9,%10,%11,%12,%13,%14,%15,%16,%17,%18,%19,%20,%21,%22,%23,%24,%25,%26,%27,%28,%29,%30,%31,"
        "%32,%33,%34,%35,%36,%37,%38,%39,%40,%41,%42,%43,%44,%45,%46,%47,%48,%49,%50,%51,%52,%53,%54,%55,%56,%57,%58,%59,%60,%61,%62,%63,"
        "%64,%65,%66,%67,%68,%69,%70,%71,%72,%73,%74,%75,%76,%77,%78,%79,%80,%81,%82,%83,%84,%85,%86,%87,%88,%89,%90,%91,%92,%93,%94,%95},"
        "%96, %97, 1, 1, 1, 0, 1;"
        : ACC8(d, 0), ACC8(d, 8), ACC8(d, 16), ACC8(d, 24), ACC8(d, 32), ACC8(d, 40), ACC8(d, 48), ACC8(d, 56),
          ACC8(d, 64), ACC8(d, 72), ACC8(d, 80), ACC8(d, 88)
        : "l"(da), "l"(db));
}
__device__ __forceinline__ void wgmma_n64(float (&d)[32], uint64_t da, uint64_t db) {
    asm volatile(
        "wgmma.mma_async.sync.aligned.m64n64k16.f32.bf16.bf16 "
        "{%0,%1,%2,%3,%4,%5,%6,%7,%8,%9,%10,%11,%12,%13,%14,%15,%16,%17,%18,%19,%20,%21,%22,%23,%24,%25,%26,%27,%28,%29,%30,%31},"
        "%32, %33, 1, 1, 1, 0, 1;"
        : ACC8(d, 0), ACC8(d, 8), ACC8(d, 16), ACC8(d, 24)
        : "l"(da), "l"(db));
}
__device__ __forceinline__ void wgmma_qk128(float (&d)[64], const uint32_t (&a)[4], uint64_t desc) {
    asm volatile(
        "wgmma.mma_async.sync.aligned.m64n128k16.f32.bf16.bf16 "
        "{%0,%1,%2,%3,%4,%5,%6,%7,%8,%9,%10,%11,%12,%13,%14,%15,%16,%17,%18,%19,%20,%21,%22,%23,%24,%25,%26,%27,%28,%29,%30,%31,"
        "%32,%33,%34,%35,%36,%37,%38,%39,%40,%41,%42,%43,%44,%45,%46,%47,%48,%49,%50,%51,%52,%53,%54,%55,%56,%57,%58,%59,%60,%61,%62,%63},"
        "{%64,%65,%66,%67}, %68, 0, 1, 1, 0;"
        : OUT8(d, 0), OUT8(d, 8), OUT8(d, 16), OUT8(d, 24), OUT8(d, 32), OUT8(d, 40), OUT8(d, 48), OUT8(d, 56)
        : "r"(a[0]), "r"(a[1]), "r"(a[2]), "r"(a[3]), "l"(desc));
}
__device__ __forceinline__ void wgmma_pv24(float (&o)[12], uint32_t a0, uint32_t a1, uint32_t a2, uint32_t a3, uint64_t desc) {
    asm volatile(
        "wgmma.mma_async.sync.aligned.m64n24k16.f32.bf16.bf16 "
        "{%0,%1,%2,%3,%4,%5,%6,%7,%8,%9,%10,%11}, {%12,%13,%14,%15}, %16, 1, 1, 1, 1;"
        : ACC8(o, 0), "+f"(o[8]), "+f"(o[9]), "+f"(o[10]), "+f"(o[11])
        : "r"(a0), "r"(a1), "r"(a2), "r"(a3), "l"(desc));
}

__device__ __forceinline__ uint32_t ex2_pair_poly(float x0, float x1) {
    const float M = 12288.0f + 31.0f;
    float t0 = x0 + M, t1 = x1 + M;
    uint32_t G = __byte_perm(__float_as_uint(t0), __float_as_uint(t1), 0x5410);
    uint32_t W, q;
    asm("lop3.b32 %0, %1, %2, %3, 0xEA;" : "=r"(W) : "r"(G), "r"(0x03FF03FFu), "r"(0x3C003C00u));
    asm("fma.rn.f16x2 %0, %1, %2, %3;" : "=r"(q) : "r"(0x15121512u), "r"(W), "r"(0x8acc8accu));
    asm("fma.rn.f16x2 %0, %1, %2, %3;" : "=r"(q) : "r"(q), "r"(W), "r"(0x1fc21fc2u));
    asm("fma.rn.f16x2 %0, %1, %2, %3;" : "=r"(q) : "r"(q), "r"(W), "r"(0x2f732f73u));
    return ((G & 0xFC00FC00u) >> 3) + q;
}
#define NPP 18
__device__ __forceinline__ constexpr bool use_poly_pair(int i) { return ((i % 32 + 1) * NPP) / 32 != ((i % 32) * NPP) / 32; }
__device__ __forceinline__ uint32_t ex2_pair(float x0, float x1, int i) {
    return use_poly_pair(i) ? ex2_pair_poly(x0, x1) : pack_bf16(ex2_mufu(x0), ex2_mufu(x1));
}
__device__ __forceinline__ void top2_merge(float& v1, int& i1, float& v2, int& i2, float w, int j) {
    if (w > v1 || (w == v1 && j < i1)) { v2 = v1; i2 = i1; v1 = w; i1 = j; }
    else if (w > v2 || (w == v2 && j < i2)) { v2 = w; i2 = j; }
}

constexpr int P1_STAGES = 5;
constexpr int P1_STAGE_BYTES = 16384 + 24576;
constexpr int KV_CHUNK = 10240;
constexpr int SM_WO = 0, SM_A3 = 163840, SM_WG = 131072;
constexpr int SM_MISC = 229376;
constexpr int SMEM_TOTAL = 232448;
struct Misc {
    uint64_t p1_full[P1_STAGES], p1_empty[P1_STAGES];
    uint64_t kv[16];
    uint64_t wo[8], a3[8], moe;
    unsigned int tag;
    int fast;
    int idx[2];
    float sel[8];
    unsigned int norm[12];
    float4 nrm[16];
    union {
        struct { float mu[128], rs[128], cs[192]; } p1;
        struct { float part[2][64][3]; float mu[64], rs[64], r[64]; } p3;
    };
};
static_assert(sizeof(Misc) <= SMEM_TOTAL - SM_MISC, "misc smem");

__global__ void __launch_bounds__(512, 1)
mega_kernel(const __grid_constant__ CUtensorMap tmX, const __grid_constant__ CUtensorMap tmW,
            const __grid_constant__ CUtensorMap tmO, const __grid_constant__ CUtensorMap tmWo,
            const __grid_constant__ CUtensorMap tmG, const __grid_constant__ CUtensorMap tmU,
            const __nv_bfloat16* __restrict__ x, const __nv_bfloat16* __restrict__ wqkv, const __nv_bfloat16* __restrict__ wo,
            const __nv_bfloat16* __restrict__ w_r, const __nv_bfloat16* __restrict__ w_gate,
            const __nv_bfloat16* __restrict__ w_up, const __nv_bfloat16* __restrict__ w_down,
            __nv_bfloat16* __restrict__ out) {
    extern __shared__ __align__(1024) char smem[];
    Misc& ms = *reinterpret_cast<Misc*>(smem + SM_MISC);
    const int tid = threadIdx.x, lane = tid & 31;
    const int warp = __shfl_sync(0xffffffffu, tid >> 5, 0);
    const int wg = warp >> 2, w4 = warp & 3, g = lane >> 2, t4 = lane & 3;
    const int cta = blockIdx.x;
    const int rb = cta >> 3, hg = cta & 7;

    if (tid == 0) {
        TS(0);
        if (smem_u32(smem) & 1023) __trap();
        for (int i = 0; i < P1_STAGES; i++) { mbar_init(smem_u32(&ms.p1_full[i]), 1); mbar_init(smem_u32(&ms.p1_empty[i]), 8); }
        asm volatile("fence.mbarrier_init.release.cluster;" ::: "memory");
    } else if (tid == 32) {
        for (int i = 0; i < 16; i++) mbar_init(smem_u32(&ms.kv[i]), 1);
        for (int i = 0; i < 8; i++) { mbar_init(smem_u32(&ms.wo[i]), 1); mbar_init(smem_u32(&ms.a3[i]), 1); }
        mbar_init(smem_u32(&ms.moe), 1);
        asm volatile("fence.mbarrier_init.release.cluster;" ::: "memory");
    }
    if (tid >= 64 && tid < 76) ms.norm[tid - 64] = 0;
    const unsigned int tag = *reinterpret_cast<volatile unsigned int*>(&gEpoch) + 1u;
    __syncthreads();
    if (warp < P1_STAGES && lane == 0) {
        const int kc = warp;
        const uint32_t bar = smem_u32(&ms.p1_full[kc]);
        const uint32_t sa = smem_u32(smem + kc * P1_STAGE_BYTES), sb = sa + 16384;
        mbar_expect_tx(bar, P1_STAGE_BYTES);
        tma_2d(sa, &tmX, kc * 64, rb * 128, bar);
#pragma unroll
        for (int p = 0; p < 3; p++) tma_2d(sb + p * 8192, &tmW, p * 512 + hg * 64, kc * 64, bar);
    }
    __syncwarp();

    if (wg < 2) {
        float acc[96];
#pragma unroll
        for (int i = 0; i < 96; i++) acc[i] = 0.f;
#pragma unroll 1
        for (int kc = 0; kc < 8; kc++) {
            const int s = kc % P1_STAGES;
            mbar_wait(smem_u32(&ms.p1_full[s]), (kc / P1_STAGES) & 1);
            if (tid == 0) TS(24 + kc);
            const uint32_t sa = smem_u32(smem + s * P1_STAGE_BYTES), sb = sa + 16384;
            const uint64_t da = make_desc(sa + wg * 8192, 16, 1024, 1);
            const uint64_t db = make_desc(sb, 8192, 1024, 1);
            wg_fence();
#pragma unroll
            for (int ks = 0; ks < 4; ks++) wgmma_n192(acc, da + ks * 2, db + ks * 128);
            wg_commit();
            wg_wait<0>();
            if (lane == 0) mbar_arrive(smem_u32(&ms.p1_empty[s]));
        }
        wg_wait<0>();
        pin(acc);
        if (tid == 0) TS(1);
        bar_sync(1, 480);
        if (tid == 0) TS(16);
        const int lr0 = wg * 64 + w4 * 16 + g, lr1 = lr0 + 8;
        const float mu0 = ms.p1.mu[lr0], mu1 = ms.p1.mu[lr1], rs0 = ms.p1.rs[lr0], rs1 = ms.p1.rs[lr1];
        const int lg0 = wg * 8 + w4 * 2;
        const int rg0 = rb * 16 + lg0;
#pragma unroll
        for (int hh = 0; hh < 4; hh++) {
            const int head = hg * 4 + hh;
            float nrm[3];
#pragma unroll
            for (int sec = 0; sec < 3; sec++) {
                float sq0 = 0.f, sq1 = 0.f, vm = 0.f;
#pragma unroll
                for (int db = 0; db < 2; db++) {
                    const int j = sec * 8 + hh * 2 + db;
                    const float2 c = *reinterpret_cast<const float2*>(&ms.p1.cs[j * 8 + 2 * t4]);
                    const float f0 = sec == 0 ? rs0 * QSCALE : rs0, f1 = sec == 0 ? rs1 * QSCALE : rs1;
                    const float a0 = (acc[4 * j + 0] - mu0 * c.x) * f0, a1 = (acc[4 * j + 1] - mu0 * c.y) * f0;
                    const float b0 = (acc[4 * j + 2] - mu1 * c.x) * f1, b1 = (acc[4 * j + 3] - mu1 * c.y) * f1;
                    const uint32_t pa = pack_bf16(a0, a1), pb = pack_bf16(b0, b1);
                    if (sec < 2) {
                        uint32_t* dst = sec == 0 ? reinterpret_cast<uint32_t*>(gQ) + ((size_t)head * S_LEN * DH + rg0 * 128) / 2
                                                 : reinterpret_cast<uint32_t*>(gKV) + (size_t)(head * 16 + rb) * 2048 + lg0 * 64;
                        dst[db * 32 + lane] = pa;
                        dst[64 + db * 32 + lane] = pb;
                        sq0 = fmaf(a0, a0, fmaf(a1, a1, sq0));
                        sq1 = fmaf(b0, b0, fmaf(b1, b1, sq1));
                    } else {
                        uint32_t* dst = reinterpret_cast<uint32_t*>(gKV) + (size_t)(head * 16 + rb) * 2048 + 1024 + db * 512 + lg0 * 32;
                        dst[lane] = pa;
                        dst[32 + lane] = pb;
                        vm = fmaxf(vm, fmaxf(fmaxf(fabsf(a0), fabsf(a1)), fmaxf(fabsf(b0), fabsf(b1))));
                        if (!(a0 + a1 + b0 + b1 == a0 + a1 + b0 + b1)) vm = __int_as_float(0x7f800000);
                    }
                }
                if (sec < 2) {
                    sq0 += __shfl_xor_sync(0xffffffffu, sq0, 1); sq0 += __shfl_xor_sync(0xffffffffu, sq0, 2);
                    sq1 += __shfl_xor_sync(0xffffffffu, sq1, 1); sq1 += __shfl_xor_sync(0xffffffffu, sq1, 2);
                    vm = fmaxf(sq0, sq1);
                    if (!(sq0 + sq1 < 3.0e38f)) vm = __int_as_float(0x7f800000);
                }
                nrm[sec] = vm;
            }
            const unsigned int a = __reduce_max_sync(0xffffffffu, __float_as_uint(nrm[0]));
            const unsigned int b = __reduce_max_sync(0xffffffffu, __float_as_uint(nrm[1]));
            const unsigned int c = __reduce_max_sync(0xffffffffu, __float_as_uint(nrm[2]));
            if (lane == 0) { atomicMax(&ms.norm[hh * 3 + 0], a); atomicMax(&ms.norm[hh * 3 + 1], b); atomicMax(&ms.norm[hh * 3 + 2], c); }
        }
        if (tid == 0) TS(17);
        bar_sync(2, 256);
        if (tid == 0) TS(18);
        if (tid < 12) gNorm[(rb * NH + hg * 4 + tid / 3) * 4 + tid % 3] = __uint_as_float(ms.norm[tid]);
        __syncwarp();
        if (tid == 0) { st_flag(&gFlagQKV[hg * 16 + rb], tag); TS(2); }
    } else if (wg == 2) {
        const int t = tid - 256;
        {
            const int row = rb * 128 + hg * 16 + (t >> 3), j = t & 7;
            const uint4* xp = reinterpret_cast<const uint4*>(x + (size_t)row * DM);
            uint4 v[8];
#pragma unroll
            for (int i = 0; i < 8; i++) v[i] = __ldg(xp + i * 8 + j);
            float s1 = 0.f;
#pragma unroll
            for (int i = 0; i < 8; i++) {
                const uint32_t w[4] = {v[i].x, v[i].y, v[i].z, v[i].w};
#pragma unroll
                for (int e = 0; e < 4; e++) s1 += bf_lo(w[e]) + bf_hi(w[e]);
            }
            s1 += __shfl_xor_sync(0xffffffffu, s1, 1); s1 += __shfl_xor_sync(0xffffffffu, s1, 2); s1 += __shfl_xor_sync(0xffffffffu, s1, 4);
            const float mu = s1 * (1.f / DM);
            float s2 = 0.f;
#pragma unroll
            for (int i = 0; i < 8; i++) {
                const uint32_t w[4] = {v[i].x, v[i].y, v[i].z, v[i].w};
#pragma unroll
                for (int e = 0; e < 4; e++) {
                    const float a = bf_lo(w[e]) - mu, b = bf_hi(w[e]) - mu;
                    s2 = fmaf(a, a, fmaf(b, b, s2));
                }
            }
            s2 += __shfl_xor_sync(0xffffffffu, s2, 1); s2 += __shfl_xor_sync(0xffffffffu, s2, 2); s2 += __shfl_xor_sync(0xffffffffu, s2, 4);
            if (j == 0) st_pkt(&gStat1[row], make_uint4(__float_as_uint(mu), __float_as_uint(rsqrtf(s2 * (1.f / DM) + LN_EPS)), 0u, tag));
        }
        uint4 st[1];
        wait_pkts<1, 0xffffffffu>(&gStat1[rb * 128 + t], 0, tag, st);
        ms.p1.mu[t] = __uint_as_float(st[0].x);
        ms.p1.rs[t] = __uint_as_float(st[0].y);
        bar_arrive(1, 480);
    } else if (w4 == 0) {
        if (lane == 0) {
            for (int kc = P1_STAGES; kc < 8; kc++) {
                const int s = kc % P1_STAGES;
                mbar_wait(smem_u32(&ms.p1_empty[s]), 0);
                const uint32_t bar = smem_u32(&ms.p1_full[s]);
                const uint32_t sa = smem_u32(smem + s * P1_STAGE_BYTES), sb = sa + 16384;
                mbar_expect_tx(bar, P1_STAGE_BYTES);
                tma_2d(sa, &tmX, kc * 64, rb * 128, bar);
#pragma unroll
                for (int p = 0; p < 3; p++) tma_2d(sb + p * 8192, &tmW, p * 512 + hg * 64, kc * 64, bar);
            }
            bulk_prefetch_l2(reinterpret_cast<const char*>(wo) + cta * 4096, 4096);
            bulk_prefetch_l2(reinterpret_cast<const char*>(w_gate) + cta * 14336, 14336);
            bulk_prefetch_l2(reinterpret_cast<const char*>(w_up) + cta * 14336, 14336);
            bulk_prefetch_l2(reinterpret_cast<const char*>(w_down) + cta * 14336, 14336);
        }
    } else {
        const int t = tid - 416;
        const int c16 = t >> 2, rs = t & 3;
        const __nv_bfloat16* wp = wqkv + (size_t)(rb * 32 + rs) * (3 * DM) + (c16 >> 3) * 512 + hg * 64 + (c16 & 7) * 8;
        uint4 v[8];
#pragma unroll
        for (int i = 0; i < 8; i++) v[i] = __ldg(reinterpret_cast<const uint4*>(wp + (size_t)i * 4 * (3 * DM)));
        float a[8] = {};
#pragma unroll
        for (int i = 0; i < 8; i++) {
            a[0] += bf_lo(v[i].x); a[1] += bf_hi(v[i].x); a[2] += bf_lo(v[i].y); a[3] += bf_hi(v[i].y);
            a[4] += bf_lo(v[i].z); a[5] += bf_hi(v[i].z); a[6] += bf_lo(v[i].w); a[7] += bf_hi(v[i].w);
        }
#pragma unroll
        for (int e = 0; e < 8; e++) { a[e] += __shfl_xor_sync(0xffffffffu, a[e], 1); a[e] += __shfl_xor_sync(0xffffffffu, a[e], 2); }
        if (rs < 2) {
            const int pk = c16 * 2 + rs;
            st_pkt(&gCsPart[(hg * 16 + rb) * 48 + pk], embed_tag(rs ? a[4] : a[0], rs ? a[5] : a[1], rs ? a[6] : a[2], rs ? a[7] : a[3], tag));
            uint4 p[16];
            wait_pkts4<16>(&gCsPart[hg * 16 * 48 + pk], 48, tag, p);
            float s0 = 0.f, s1 = 0.f, s2 = 0.f, s3 = 0.f;
#pragma unroll
            for (int i = 0; i < 16; i++) {
                s0 += __uint_as_float(p[i].x); s1 += __uint_as_float(p[i].y); s2 += __uint_as_float(p[i].z); s3 += __uint_as_float(p[i].w);
            }
            *reinterpret_cast<float4*>(&ms.p1.cs[pk * 4]) = make_float4(s0, s1, s2, s3);
        }
        __syncwarp();
        bar_arrive(1, 480);
    }
    __syncthreads();
    if (tid == 0) TS(20);

    const int head = hg * 4 + (rb >> 2), quarter = rb & 3;
    {
        const uint4 one = make_uint4(0x00003F80u, 0, 0, 0);
#pragma unroll
        for (int i = 0; i < 4; i++) {
            const int e = tid + i * 512;
            *reinterpret_cast<uint4*>(smem + (e >> 7) * KV_CHUNK + 8192 + (e & 127) * 16) = one;
        }
        asm volatile("fence.proxy.async.shared::cta;" ::: "memory");
    }
    if (lane == 0) {
        wait_flag(&gFlagQKV[hg * 16 + warp], tag);
        fence_proxy_async_global();
        const uint32_t bar = smem_u32(&ms.kv[warp]);
        mbar_expect_tx(bar, 8192);
        bulk_g2s(smem_u32(smem + warp * KV_CHUNK), reinterpret_cast<const char*>(gKV) + (size_t)(head * 16 + warp) * 8192, 8192, bar);
        ms.nrm[warp] = __ldcg(reinterpret_cast<const float4*>(&gNorm[(warp * NH + head) * 4]));
    }
    __syncthreads();
    if (warp == 0) {
        const float4 n = ms.nrm[lane & 15];
        const float q2 = __uint_as_float(__reduce_max_sync(0xffffffffu, __float_as_uint(n.x)));
        const float k2 = __uint_as_float(__reduce_max_sync(0xffffffffu, __float_as_uint(n.y)));
        const float vm = __uint_as_float(__reduce_max_sync(0xffffffffu, __float_as_uint(n.z)));
        if (lane == 0) ms.fast = (q2 * k2 * 1.04f <= 841.f) && (vm <= 1.0e18f) && (vm >= 1.0e-18f || vm == 0.f);
    }
    __syncthreads();
    if (tid == 0) TS(3);
    {
        const bool fast = ms.fast != 0;
        const uint64_t descK0 = make_desc(smem_u32(smem), 128, 256, 0);
        const uint64_t descV0 = make_desc(smem_u32(smem + 4096), 128, 2048, 0);
#pragma unroll 1
        for (int pass = 0; pass < 2; pass++) {
            const int tile = pass * 16 + quarter * 4 + wg;
            const int row0 = tile * 64 + w4 * 16;
            uint32_t q[4];
            {
                const uint32_t* Qp = reinterpret_cast<const uint32_t*>(gQ) + ((size_t)head * S_LEN * DH + (row0 >> 3) * 128) / 2;
                q[0] = __ldcg(Qp + lane); q[2] = __ldcg(Qp + 32 + lane);
                q[1] = __ldcg(Qp + 64 + lane); q[3] = __ldcg(Qp + 96 + lane);
            }
            float o[12];
#pragma unroll
            for (int i = 0; i < 12; i++) o[i] = 0.f;
            if (fast) {
#pragma unroll 1
                for (int j = 0; j < 16; j++) {
                    if (pass == 0) mbar_wait(smem_u32(&ms.kv[j]), 0);
                    float s[64];
                    wg_fence();
                    wgmma_qk128(s, q, descK0 + (uint64_t)(j * (KV_CHUNK >> 4)));
                    wg_commit();
                    wg_wait<0>();
                    pin(s);
#pragma unroll
                    for (int k = 0; k < 8; k++) {
                        uint32_t p[4];
#pragma unroll
                        for (int i = 0; i < 4; i++) p[i] = ex2_pair(s[8 * k + 2 * i], s[8 * k + 2 * i + 1], 4 * k + i);
                        wg_fence();
                        wgmma_pv24(o, p[0], p[1], p[2], p[3], descV0 + (uint64_t)(j * (KV_CHUNK >> 4) + k * 16));
                        wg_commit();
                        wg_wait<2>();
                    }
                }
            } else {
                float m0 = -INFINITY, m1 = -INFINITY;
#pragma unroll 1
                for (int j = 0; j < 16; j++) {
                    if (pass == 0) mbar_wait(smem_u32(&ms.kv[j]), 0);
                    float s[64];
                    wg_fence();
                    wgmma_qk128(s, q, descK0 + (uint64_t)(j * (KV_CHUNK >> 4)));
                    wg_commit();
                    wg_wait<0>();
                    pin(s);
                    pin(o);
                    float n0 = m0, n1 = m1;
#pragma unroll
                    for (int i = 0; i < 16; i++) {
                        n0 = fmaxf(n0, fmaxf(s[4 * i], s[4 * i + 1]));
                        n1 = fmaxf(n1, fmaxf(s[4 * i + 2], s[4 * i + 3]));
                    }
                    n0 = fmaxf(n0, __shfl_xor_sync(0xffffffffu, n0, 1)); n0 = fmaxf(n0, __shfl_xor_sync(0xffffffffu, n0, 2));
                    n1 = fmaxf(n1, __shfl_xor_sync(0xffffffffu, n1, 1)); n1 = fmaxf(n1, __shfl_xor_sync(0xffffffffu, n1, 2));
                    const float a0 = ex2_mufu(m0 - n0), a1 = ex2_mufu(m1 - n1);
                    m0 = n0; m1 = n1;
#pragma unroll
                    for (int i = 0; i < 3; i++) { o[4 * i] *= a0; o[4 * i + 1] *= a0; o[4 * i + 2] *= a1; o[4 * i + 3] *= a1; }
#pragma unroll
                    for (int k = 0; k < 8; k++) {
                        const uint32_t p0 = pack_bf16(ex2_mufu(s[8 * k] - n0), ex2_mufu(s[8 * k + 1] - n0));
                        const uint32_t p1 = pack_bf16(ex2_mufu(s[8 * k + 2] - n1), ex2_mufu(s[8 * k + 3] - n1));
                        const uint32_t p2 = pack_bf16(ex2_mufu(s[8 * k + 4] - n0), ex2_mufu(s[8 * k + 5] - n0));
                        const uint32_t p3 = pack_bf16(ex2_mufu(s[8 * k + 6] - n1), ex2_mufu(s[8 * k + 7] - n1));
                        wg_fence();
                        wgmma_pv24(o, p0, p1, p2, p3, descV0 + (uint64_t)(j * (KV_CHUNK >> 4) + k * 16));
                        wg_commit();
                        wg_wait<2>();
                    }
                    wg_wait<0>();
                }
            }
            wg_wait<0>();
            pin(o);
            const float l0 = __shfl_sync(0xffffffffu, o[8], lane & ~3), l1 = __shfl_sync(0xffffffffu, o[10], lane & ~3);
            const float r0 = 1.f / l0, r1 = 1.f / l1;
            uint32_t* Op = reinterpret_cast<uint32_t*>(gO + (size_t)row0 * DM + head * DH);
            Op[g * 256 + t4] = pack_bf16(o[0] * r0, o[1] * r0);
            Op[(g + 8) * 256 + t4] = pack_bf16(o[2] * r1, o[3] * r1);
            Op[g * 256 + 4 + t4] = pack_bf16(o[4] * r0, o[5] * r0);
            Op[(g + 8) * 256 + 4 + t4] = pack_bf16(o[6] * r1, o[7] * r1);
            bar_sync(3 + wg, 128);
            if ((tid & 127) == 0) st_flag(&gFlagO[tile * 32 + head], tag);
        }
    }
    __syncthreads();
    if (tid == 0) TS(4);

    const int rb3 = cta >> 2, cb = cta & 3;
    if (wg < 2) {
        const int r0 = rb3 * 64 + w4 * 16 + g, r1 = r0 + 8;
        const int col0 = cb * 128 + wg * 64 + 2 * t4;
        uint32_t xa[8], xb[8], wr[8];
#pragma unroll
        for (int j = 0; j < 8; j++) {
            xa[j] = __ldg(reinterpret_cast<const uint32_t*>(x + (size_t)r0 * DM + col0 + j * 8));
            xb[j] = __ldg(reinterpret_cast<const uint32_t*>(x + (size_t)r1 * DM + col0 + j * 8));
            wr[j] = __ldg(reinterpret_cast<const uint32_t*>(w_r + col0 + j * 8));
        }
        const float p0 = __bfloat162float(x[(size_t)r0 * DM]), p1 = __bfloat162float(x[(size_t)r1 * DM]);
        const float pivot = __bfloat162float(x[(size_t)(rb3 * 64 + (tid >> 2)) * DM]);
        float wsum = 0.f;
        {
            const uint4 a = __ldg(reinterpret_cast<const uint4*>(w_r) + lane), b = __ldg(reinterpret_cast<const uint4*>(w_r) + 32 + lane);
            const uint32_t w[8] = {a.x, a.y, a.z, a.w, b.x, b.y, b.z, b.w};
#pragma unroll
            for (int e = 0; e < 8; e++) wsum += bf_lo(w[e]) + bf_hi(w[e]);
#pragma unroll
            for (int m = 16; m; m >>= 1) wsum += __shfl_xor_sync(0xffffffffu, wsum, m);
        }
        float acc[32];
#pragma unroll
        for (int i = 0; i < 32; i++) acc[i] = 0.f;
#pragma unroll 1
        for (int kc = 0; kc < 8; kc++) {
            mbar_wait(smem_u32(&ms.wo[kc]), 0);
            mbar_wait(smem_u32(&ms.a3[kc]), 0);
            const uint64_t da = make_desc(smem_u32(smem + SM_A3 + kc * 8192), 16, 1024, 1);
            const uint64_t db = make_desc(smem_u32(smem + SM_WO + kc * 16384 + wg * 8192), 8192, 1024, 1);
            wg_fence();
#pragma unroll
            for (int ks = 0; ks < 4; ks++) wgmma_n64(acc, da + ks * 2, db + ks * 128);
            wg_commit();
        }
        wg_wait<0>();
        pin(acc);
        if (tid == 0) TS(6);
        float s1a = 0.f, s2a = 0.f, s3a = 0.f, s1b = 0.f, s2b = 0.f, s3b = 0.f;
#pragma unroll
        for (int j = 0; j < 8; j++) {
            const uint32_t ha = pack_bf16(bf_lo(xa[j]) + acc[4 * j], bf_hi(xa[j]) + acc[4 * j + 1]);
            const uint32_t hb = pack_bf16(bf_lo(xb[j]) + acc[4 * j + 2], bf_hi(xb[j]) + acc[4 * j + 3]);
            *reinterpret_cast<uint32_t*>(gH + (size_t)r0 * DM + col0 + j * 8) = ha;
            *reinterpret_cast<uint32_t*>(gH + (size_t)r1 * DM + col0 + j * 8) = hb;
            xa[j] = ha; xb[j] = hb;
            const float w0 = bf_lo(wr[j]), w1 = bf_hi(wr[j]);
            const float da0 = bf_lo(ha) - p0, da1 = bf_hi(ha) - p0, db0 = bf_lo(hb) - p1, db1 = bf_hi(hb) - p1;
            s1a += da0 + da1; s2a = fmaf(da0, da0, fmaf(da1, da1, s2a)); s3a = fmaf(da0, w0, fmaf(da1, w1, s3a));
            s1b += db0 + db1; s2b = fmaf(db0, db0, fmaf(db1, db1, s2b)); s3b = fmaf(db0, w0, fmaf(db1, w1, s3b));
        }
#pragma unroll
        for (int m = 1; m <= 2; m <<= 1) {
            s1a += __shfl_xor_sync(0xffffffffu, s1a, m); s2a += __shfl_xor_sync(0xffffffffu, s2a, m); s3a += __shfl_xor_sync(0xffffffffu, s3a, m);
            s1b += __shfl_xor_sync(0xffffffffu, s1b, m); s2b += __shfl_xor_sync(0xffffffffu, s2b, m); s3b += __shfl_xor_sync(0xffffffffu, s3b, m);
        }
        if (t4 == 0) {
            const int lr = w4 * 16 + g;
            ms.p3.part[wg][lr][0] = s1a; ms.p3.part[wg][lr][1] = s2a; ms.p3.part[wg][lr][2] = s3a;
            ms.p3.part[wg][lr + 8][0] = s1b; ms.p3.part[wg][lr + 8][1] = s2b; ms.p3.part[wg][lr + 8][2] = s3b;
        }
        if (tid == 0) TS(11);
        bar_sync(1, 256);
        if (tid == 0) TS(12);
        if (tid < 64) {
            st_pkt(&gPart[(rb3 * 64 + tid) * 4 + cb],
                   make_uint4(__float_as_uint(ms.p3.part[0][tid][0] + ms.p3.part[1][tid][0]), __float_as_uint(ms.p3.part[0][tid][1] + ms.p3.part[1][tid][1]),
                              __float_as_uint(ms.p3.part[0][tid][2] + ms.p3.part[1][tid][2]), tag));
        } else if (tid == 224) {
            st_flag(&gFlagH[rb3 * 4 + cb], tag);
            TS(13);
        }
        {
            const int lr = tid >> 2, sl = tid & 3;
            uint4 pv[1];
            wait_pkts<1, 0xffffffffu>(&gPart[rb3 * 256 + tid], 0, tag, pv);
            float s1 = __uint_as_float(pv[0].x), s2 = __uint_as_float(pv[0].y), s3 = __uint_as_float(pv[0].z);
            if (tid == 0) TS(14);
#pragma unroll
            for (int m = 1; m <= 2; m <<= 1) {
                s1 += __shfl_xor_sync(0xffffffffu, s1, m); s2 += __shfl_xor_sync(0xffffffffu, s2, m); s3 += __shfl_xor_sync(0xffffffffu, s3, m);
            }
            if (sl == 0) {
                const float md = s1 * (1.f / DM);
                const float var = fmaxf(s2 * (1.f / DM) - md * md, 0.f);
                const float rs = rsqrtf(var + LN_EPS);
                ms.p3.mu[lr] = pivot + md;
                ms.p3.rs[lr] = rs;
                ms.p3.r[lr] = (s3 - md * wsum) * rs;
            }
        }
        bar_sync(1, 256);
        if (tid == 0) TS(7);
        if (cb == 0 && warp == 0) {
            float v1 = -INFINITY, v2 = -INFINITY; int i1 = 0x7fffffff, i2 = 0x7fffffff;
            float ra = ms.p3.r[lane], rbv = ms.p3.r[lane + 32];
            if (!(ra == ra)) ra = -INFINITY;
            if (!(rbv == rbv)) rbv = -INFINITY;
            top2_merge(v1, i1, v2, i2, ra, lane);
            top2_merge(v1, i1, v2, i2, rbv, lane + 32);
#pragma unroll
            for (int m = 16; m; m >>= 1) {
                const float w1 = __shfl_xor_sync(0xffffffffu, v1, m), w2 = __shfl_xor_sync(0xffffffffu, v2, m);
                const int j1 = __shfl_xor_sync(0xffffffffu, i1, m), j2 = __shfl_xor_sync(0xffffffffu, i2, m);
                top2_merge(v1, i1, v2, i2, w1, j1);
                top2_merge(v1, i1, v2, i2, w2, j2);
            }
            if (lane < 4) wait_flag(&gFlagH[rb3 * 4 + lane], tag);
            __syncwarp();
            if (lane < 2) {
                const int li = lane ? i2 : i1;
                st_pkt(&gCand[rb3 * 2 + lane], make_uint4(__float_as_uint(lane ? v2 : v1), __float_as_uint(ms.p3.mu[li]), __float_as_uint(ms.p3.rs[li]),
                                                          (tag << 11) | (unsigned int)(rb3 * 64 + li)));
                if (lane == 0) TS(15);
            }
        }
        bar_sync(2, 512);
        {
            const int idx0 = ms.idx[0], idx1 = ms.idx[1];
            const int lr0 = w4 * 16 + g;
            const float mu0 = ms.p3.mu[lr0], rs0 = ms.p3.rs[lr0], mu1 = ms.p3.mu[lr0 + 8], rs1 = ms.p3.rs[lr0 + 8];
            const bool w0 = (r0 != idx0 && r0 != idx1), w1 = (r1 != idx0 && r1 != idx1);
#pragma unroll
            for (int j = 0; j < 8; j++) {
                const float a0 = bf_lo(xa[j]), a1 = bf_hi(xa[j]), b0 = bf_lo(xb[j]), b1 = bf_hi(xb[j]);
                const uint32_t la = pack_bf16((a0 - mu0) * rs0, (a1 - mu0) * rs0);
                const uint32_t lb = pack_bf16((b0 - mu1) * rs1, (b1 - mu1) * rs1);
                if (w0) *reinterpret_cast<uint32_t*>(out + (size_t)r0 * DM + col0 + j * 8) = pack_bf16(a0 + bf_lo(la), a1 + bf_hi(la));
                if (w1) *reinterpret_cast<uint32_t*>(out + (size_t)r1 * DM + col0 + j * 8) = pack_bf16(b0 + bf_lo(lb), b1 + bf_hi(lb));
            }
        }
    } else {
        const int t = tid - 256;
        if (warp == 8) {
            if (lane == 0) {
                for (int kc = 0; kc < 8; kc++) {
                    const uint32_t bar = smem_u32(&ms.wo[kc]);
                    mbar_expect_tx(bar, 16384);
                    tma_2d(smem_u32(smem + SM_WO + kc * 16384), &tmWo, cb * 128, kc * 64, bar);
                    tma_2d(smem_u32(smem + SM_WO + kc * 16384 + 8192), &tmWo, cb * 128 + 64, kc * 64, bar);
                }
            }
            __syncwarp();
            wait_flag(&gFlagO[rb3 * 32 + lane], tag);
            __syncwarp();
            if (lane == 0) TS(5);
            if (lane < 8) {
                fence_proxy_async_global();
                const uint32_t bar = smem_u32(&ms.a3[lane]);
                mbar_expect_tx(bar, 8192);
                tma_2d(smem_u32(smem + SM_A3 + lane * 8192), &tmO, lane * 64, rb3 * 64, bar);
            }
        } else if (warp == 9 && lane == 0 && cta < NFFN) {
            const uint32_t bar = smem_u32(&ms.moe);
            mbar_expect_tx(bar, 32768);
            tma_2d(smem_u32(smem + SM_WG), &tmG, cta * 16, 0, bar);
            tma_2d(smem_u32(smem + SM_WG + 8192), &tmG, cta * 16, 256, bar);
            tma_2d(smem_u32(smem + SM_WG + 16384), &tmU, cta * 16, 0, bar);
            tma_2d(smem_u32(smem + SM_WG + 24576), &tmU, cta * 16, 256, bar);
        }
        uint32_t wd[16];
        if (cta < NFFN) {
#pragma unroll
            for (int k = 0; k < 16; k++) wd[k] = __ldg(reinterpret_cast<const uint32_t*>(w_down + (size_t)(cta * 16 + k) * DM + 2 * t));
        }
        if (warp == 8) {
            float v1 = -INFINITY, v2 = -INFINITY; int i1 = 0x7fffffff, i2 = 0x7fffffff;
            float cv[2], cm[2], cr[2]; int ci[2];
            uint4 cvl[2];
            wait_pkts<2, 0xfffff800u>(&gCand[lane * 2], 1, tag << 11, cvl);
            asm volatile("fence.acquire.gpu;" ::: "memory");
#pragma unroll
            for (int c = 0; c < 2; c++) {
                cv[c] = __uint_as_float(cvl[c].x); ci[c] = (int)(cvl[c].w & 0x7ffu);
                cm[c] = __uint_as_float(cvl[c].y); cr[c] = __uint_as_float(cvl[c].z);
                top2_merge(v1, i1, v2, i2, cv[c], ci[c]);
            }
#pragma unroll
            for (int m = 16; m; m >>= 1) {
                const float w1 = __shfl_xor_sync(0xffffffffu, v1, m), w2 = __shfl_xor_sync(0xffffffffu, v2, m);
                const int j1 = __shfl_xor_sync(0xffffffffu, i1, m), j2 = __shfl_xor_sync(0xffffffffu, i2, m);
                top2_merge(v1, i1, v2, i2, w1, j1);
                top2_merge(v1, i1, v2, i2, w2, j2);
            }
#pragma unroll
            for (int c = 0; c < 2; c++) {
                if (ci[c] == i1) { ms.idx[0] = i1; ms.sel[0] = cm[c]; ms.sel[1] = cr[c]; ms.sel[2] = 1.f / (1.f + __expf(-cv[c])); }
                if (ci[c] == i2) { ms.idx[1] = i2; ms.sel[4] = cm[c]; ms.sel[5] = cr[c]; ms.sel[6] = 1.f / (1.f + __expf(-cv[c])); }
            }
            if (lane == 0) TS(8);
        }
        bar_sync(2, 512);
        const int idx0 = ms.idx[0], idx1 = ms.idx[1];
        float* sX = reinterpret_cast<float*>(smem + SM_A3);
        float* sPart = sX + 1024;
        float* sAct = sPart + 512;
        if (cta < NFFN) {
#pragma unroll
            for (int tk = 0; tk < 2; tk++) {
                const int row = tk ? idx1 : idx0;
                const uint32_t h = __ldcg(reinterpret_cast<const uint32_t*>(gH + (size_t)row * DM + 2 * t));
                const float mu = ms.sel[tk * 4], rs = ms.sel[tk * 4 + 1];
                const uint32_t ln = pack_bf16((bf_lo(h) - mu) * rs, (bf_hi(h) - mu) * rs);
                *reinterpret_cast<float2*>(&sX[tk * 512 + 2 * t]) = make_float2(bf_lo(ln), bf_hi(ln));
            }
            mbar_wait(smem_u32(&ms.moe), 0);
            bar_sync(1 + 8, 256);
            {
                const int wv = warp - 8, kk = lane >> 3, cp = lane & 7;
                float a[2][2][2] = {};
#pragma unroll
                for (int i = 0; i < 16; i++) {
                    const int k = wv * 64 + i * 4 + kk;
                    const float x0 = sX[k], x1 = sX[512 + k];
#pragma unroll
                    for (int mat = 0; mat < 2; mat++) {
                        const uint32_t w = *reinterpret_cast<const uint32_t*>(smem + SM_WG + mat * 16384 + k * 32 + cp * 4);
                        a[mat][0][0] = fmaf(x0, bf_lo(w), a[mat][0][0]); a[mat][0][1] = fmaf(x0, bf_hi(w), a[mat][0][1]);
                        a[mat][1][0] = fmaf(x1, bf_lo(w), a[mat][1][0]); a[mat][1][1] = fmaf(x1, bf_hi(w), a[mat][1][1]);
                    }
                }
#pragma unroll
                for (int mat = 0; mat < 2; mat++)
#pragma unroll
                    for (int tk = 0; tk < 2; tk++)
#pragma unroll
                        for (int e = 0; e < 2; e++) {
                            float v = a[mat][tk][e];
                            v += __shfl_xor_sync(0xffffffffu, v, 8);
                            v += __shfl_xor_sync(0xffffffffu, v, 16);
                            if (kk == 0) sPart[(wv * 2 + tk) * 32 + mat * 16 + 2 * cp + e] = v;
                        }
            }
            bar_sync(1 + 8, 256);
            if (t < 32) {
                const int tk = t >> 4, c = t & 15;
                float gs = 0.f, us = 0.f;
#pragma unroll
                for (int w = 0; w < 8; w++) { gs += sPart[(w * 2 + tk) * 32 + c]; us += sPart[(w * 2 + tk) * 32 + 16 + c]; }
                const float gb = bf_round(gs), ub = bf_round(us);
                const float sl = bf_round(gb / (1.f + __expf(-gb)));
                sAct[tk * 16 + c] = bf_round(sl * ub);
            }
            bar_sync(1 + 8, 256);
            {
                float y00 = 0.f, y01 = 0.f, y10 = 0.f, y11 = 0.f;
#pragma unroll
                for (int k = 0; k < 16; k++) {
                    const float a0 = sAct[k], a1 = sAct[16 + k];
                    y00 = fmaf(a0, bf_lo(wd[k]), y00); y01 = fmaf(a0, bf_hi(wd[k]), y01);
                    y10 = fmaf(a1, bf_lo(wd[k]), y10); y11 = fmaf(a1, bf_hi(wd[k]), y11);
                }
                st_pkt(&gYPart[cta * 256 + t], embed_tag(y00, y01, y10, y11, tag));
            }
            if (t == 0) TS(9);
        }
        if (cta < 64) {
            const int pc = t & 3, part = t >> 2;
            const int opc = (t >> 2) & 3, oe = t & 3, otk = oe >> 1, ocol = (cta * 4 + opc) * 2 + (oe & 1);
            const float hsel = __uint_as_float((uint32_t)__ldcg(reinterpret_cast<const unsigned short*>(gH) + (size_t)(otk ? idx1 : idx0) * DM + ocol) << 16);
            float y[4] = {0.f, 0.f, 0.f, 0.f};
            if (part < 56) {
                uint4 yv[2];
                wait_pkts4<2>(&gYPart[part * 256 + cta * 4 + pc], 56 * 256, tag, yv);
                y[0] = __uint_as_float(yv[0].x) + __uint_as_float(yv[1].x); y[1] = __uint_as_float(yv[0].y) + __uint_as_float(yv[1].y);
                y[2] = __uint_as_float(yv[0].z) + __uint_as_float(yv[1].z); y[3] = __uint_as_float(yv[0].w) + __uint_as_float(yv[1].w);
            }
            __syncwarp();
#pragma unroll
            for (int e = 0; e < 4; e++) {
                y[e] += __shfl_xor_sync(0xffffffffu, y[e], 4); y[e] += __shfl_xor_sync(0xffffffffu, y[e], 8); y[e] += __shfl_xor_sync(0xffffffffu, y[e], 16);
            }
            float* sR = sAct + 32;
            if (lane < 4) *reinterpret_cast<float4*>(&sR[(warp - 8) * 16 + lane * 4]) = make_float4(y[0], y[1], y[2], y[3]);
            bar_sync(1 + 8, 256);
            if (t < 16) {
                float s = 0.f;
#pragma unroll
                for (int w = 0; w < 8; w++) s += sR[w * 16 + t];
                const float yb = bf_round(bf_round(s) * ms.sel[otk * 4 + 2]);
                const float ln = bf_round((hsel - ms.sel[otk * 4]) * ms.sel[otk * 4 + 1]);
                out[(size_t)(otk ? idx1 : idx0) * DM + ocol] = __float2bfloat16(hsel + bf_round(ln + yb));
            }
            if (cta == 0 && t == 0) {
                *reinterpret_cast<volatile unsigned int*>(&gEpoch) = tag;
            }
            if (t == 0) TS(10);
        }
    }
}

typedef CUresult (*EncodeFn)(CUtensorMap*, CUtensorMapDataType, cuuint32_t, void*, const cuuint64_t*, const cuuint64_t*,
                             const cuuint32_t*, const cuuint32_t*, CUtensorMapInterleave, CUtensorMapSwizzle,
                             CUtensorMapL2promotion, CUtensorMapFloatOOBfill);

void make_map(EncodeFn enc, CUtensorMap* tm, const void* base, uint64_t cols, uint64_t rows, uint32_t box_c, uint32_t box_r, bool swz) {
    cuuint64_t dims[2] = {cols, rows};
    cuuint64_t strides[1] = {cols * 2};
    cuuint32_t box[2] = {box_c, box_r};
    cuuint32_t es[2] = {1, 1};
    enc(tm, CU_TENSOR_MAP_DATA_TYPE_BFLOAT16, 2, const_cast<void*>(base), dims, strides, box, es, CU_TENSOR_MAP_INTERLEAVE_NONE,
        swz ? CU_TENSOR_MAP_SWIZZLE_128B : CU_TENSOR_MAP_SWIZZLE_NONE, CU_TENSOR_MAP_L2_PROMOTION_L2_256B,
        CU_TENSOR_MAP_FLOAT_OOB_FILL_NONE);
}

}

extern "C" void kernel_launch(void* const* d_in, const int* in_sizes, int n_in, void* d_out, int out_size) {
    const __nv_bfloat16* x = (const __nv_bfloat16*)d_in[0];
    const __nv_bfloat16* wqkv = (const __nv_bfloat16*)d_in[1];
    const __nv_bfloat16* wo = (const __nv_bfloat16*)d_in[2];
    const __nv_bfloat16* w_r = (const __nv_bfloat16*)d_in[4];
    const __nv_bfloat16* w_gate = (const __nv_bfloat16*)d_in[5];
    const __nv_bfloat16* w_up = (const __nv_bfloat16*)d_in[6];
    const __nv_bfloat16* w_down = (const __nv_bfloat16*)d_in[7];
    __nv_bfloat16* out = (__nv_bfloat16*)d_out;

    static EncodeFn enc = nullptr;
    static void* pO = nullptr;
    if (!enc) {
        void* fn = nullptr;
        cudaDriverEntryPointQueryResult qr;
        cudaGetDriverEntryPoint("cuTensorMapEncodeTiled", &fn, cudaEnableDefault, &qr);
        enc = (EncodeFn)fn;
        cudaGetSymbolAddress(&pO, gO);
        cudaFuncSetAttribute(mega_kernel, cudaFuncAttributeMaxDynamicSharedMemorySize, SMEM_TOTAL);
    }
    CUtensorMap tmX, tmW, tmO, tmWo, tmG, tmU;
    make_map(enc, &tmX, x, DM, S_LEN, 64, 128, true);
    make_map(enc, &tmW, wqkv, 3 * DM, DM, 64, 64, true);
    make_map(enc, &tmO, pO, DM, S_LEN, 64, 64, true);
    make_map(enc, &tmWo, wo, DM, DM, 64, 64, true);
    make_map(enc, &tmG, w_gate, FF, DM, 16, 256, false);
    make_map(enc, &tmU, w_up, FF, DM, 16, 256, false);

    mega_kernel<<<128, 512, SMEM_TOTAL, cudaStreamPerThread>>>(tmX, tmW, tmO, tmWo, tmG, tmU, x, wqkv, wo, w_r, w_gate, w_up, w_down, out);
}
```

```cpp
#include <cuda_runtime.h>
#include <cuda_bf16.h>
#include <cuda.h>
#include <stdint.h>

namespace {

constexpr int S_LEN = 2048, DM = 512, NH = 32, DH = 16, FF = 1792;
constexpr int NFFN = FF / 16;
constexpr float LN_EPS = 1e-5f;
constexpr float QSCALE = 0.25f * 1.4426950408889634f;

__device__ __align__(1024) __nv_bfloat16 gQ[NH * S_LEN * DH];
__device__ __align__(1024) __nv_bfloat16 gKV[NH * S_LEN * DH * 2];
__device__ __align__(1024) __nv_bfloat16 gO[S_LEN * DM];
__device__ __align__(16) float gNorm[16 * NH * 4];
__device__ unsigned int gEpoch;
__device__ unsigned int gFlagQKV[8 * 16];
__device__ unsigned int gFlagO[32 * 32];
__device__ uint4 gStat1[S_LEN];
__device__ uint4 gCsPart[8 * 16 * 48];
__device__ uint4 gPart[32 * 64 * 4];
__device__ uint4 gCand[128 * 64];
__device__ uint4 gCandRow[64 * 128];
__device__ uint4 gYPart[NFFN * 256];

#define TS(slot) do {} while (0)

__device__ __forceinline__ uint32_t smem_u32(const void* p) { return (uint32_t)__cvta_generic_to_shared(p); }
__device__ __forceinline__ void mbar_init(uint32_t bar, uint32_t cnt) {
    asm volatile("mbarrier.init.shared::cta.b64 [%0], %1;" ::"r"(bar), "r"(cnt));
}
__device__ __forceinline__ void mbar_expect_tx(uint32_t bar, uint32_t bytes) {
    asm volatile("mbarrier.arrive.expect_tx.shared::cta.b64 _, [%0], %1;" ::"r"(bar), "r"(bytes) : "memory");
}
__device__ __forceinline__ void mbar_arrive(uint32_t bar) {
    asm volatile("mbarrier.arrive.shared::cta.b64 _, [%0];" ::"r"(bar) : "memory");
}
constexpr int SPIN_LIMIT = 1 << 22;
#define BACKOFF() __nanosleep(100)
__device__ __forceinline__ void mbar_wait(uint32_t bar, uint32_t parity) {
    uint32_t done = 0;
    int it = 0;
    while (true) {
        asm volatile("{.reg .pred p; mbarrier.try_wait.parity.shared::cta.b64 p, [%1], %2; selp.u32 %0, 1, 0, p;}"
                     : "=r"(done) : "r"(bar), "r"(parity) : "memory");
        if (done) break;
        if (++it > SPIN_LIMIT) __trap();
    }
}
__device__ __forceinline__ void bulk_g2s(uint32_t dst, const void* src, uint32_t bytes, uint32_t bar) {
    asm volatile("cp.async.bulk.shared::cluster.global.mbarrier::complete_tx::bytes [%0], [%1], %2, [%3];"
                 ::"r"(dst), "l"(src), "r"(bytes), "r"(bar) : "memory");
}
__device__ __forceinline__ void bulk_prefetch_l2(const void* src, uint32_t bytes) {
    asm volatile("cp.async.bulk.prefetch.L2.global [%0], %1;" ::"l"(src), "r"(bytes) : "memory");
}
__device__ __forceinline__ void tma_2d(uint32_t dst, const CUtensorMap* tm, int c0, int c1, uint32_t bar) {
    asm volatile("cp.async.bulk.tensor.2d.shared::cluster.global.mbarrier::complete_tx::bytes [%0], [%1, {%3, %4}], [%2];"
                 ::"r"(dst), "l"(tm), "r"(bar), "r"(c0), "r"(c1) : "memory");
}
__device__ __forceinline__ void fence_proxy_async_global() { asm volatile("fence.proxy.async.global;" ::: "memory"); }
__device__ __forceinline__ void fence_gpu() { asm volatile("fence.acq_rel.gpu;" ::: "memory"); }
__device__ __forceinline__ void bar_sync(int id, int n) { asm volatile("bar.sync %0, %1;" ::"r"(id), "r"(n) : "memory"); }
__device__ __forceinline__ void bar_arrive(int id, int n) { asm volatile("bar.arrive %0, %1;" ::"r"(id), "r"(n) : "memory"); }
__device__ __forceinline__ void st_flag(unsigned int* p, unsigned int v) {
    asm volatile("st.release.gpu.global.u32 [%0], %1;" ::"l"(p), "r"(v) : "memory");
}
__device__ __forceinline__ unsigned int ld_flag(const unsigned int* p) {
    unsigned int v;
    asm volatile("ld.relaxed.gpu.global.u32 %0, [%1];" : "=r"(v) : "l"(p) : "memory");
    return v;
}
__device__ __forceinline__ void wait_flag(const unsigned int* p, unsigned int tag) {
    int it = 0;
    while (ld_flag(p) != tag) {
        if (++it > SPIN_LIMIT) __trap();
        BACKOFF();
    }
}
__device__ __forceinline__ void st_pkt(uint4* p, uint4 v) {
    asm volatile("st.relaxed.gpu.global.v4.u32 [%0], {%1,%2,%3,%4};" ::"l"(p), "r"(v.x), "r"(v.y), "r"(v.z), "r"(v.w) : "memory");
}
__device__ __forceinline__ uint4 ld_pkt(const uint4* p) {
    uint4 v;
    asm volatile("ld.relaxed.gpu.global.v4.u32 {%0,%1,%2,%3}, [%4];" : "=r"(v.x), "=r"(v.y), "=r"(v.z), "=r"(v.w) : "l"(p) : "memory");
    return v;
}
template <int N, unsigned int MASK>
__device__ __forceinline__ void wait_pkts(const uint4* p, int stride, unsigned int tag, uint4 (&v)[N]) {
    int it = 0;
    while (true) {
        bool ok = true;
#pragma unroll
        for (int i = 0; i < N; i++) v[i] = ld_pkt(p + (size_t)i * stride);
#pragma unroll
        for (int i = 0; i < N; i++) ok = ok && ((v[i].w & MASK) == tag);
        if (ok) break;
        if (++it > SPIN_LIMIT) __trap();
        BACKOFF();
    }
}
__device__ __forceinline__ uint4 embed_tag(float a, float b, float c, float d, unsigned int tag) {
    return make_uint4((__float_as_uint(a) & ~15u) | (tag & 15u), (__float_as_uint(b) & ~15u) | ((tag >> 4) & 15u),
                      (__float_as_uint(c) & ~15u) | ((tag >> 8) & 15u), (__float_as_uint(d) & ~15u) | ((tag >> 12) & 15u));
}
template <int N>
__device__ __forceinline__ void wait_pkts4(const uint4* p, int stride, unsigned int tag, uint4 (&v)[N]) {
    const unsigned int t16 = tag & 0xffffu;
    int it = 0;
    while (true) {
        bool ok = true;
#pragma unroll
        for (int i = 0; i < N; i++) v[i] = ld_pkt(p + (size_t)i * stride);
#pragma unroll
        for (int i = 0; i < N; i++)
            ok = ok && (((v[i].x & 15u) | ((v[i].y & 15u) << 4) | ((v[i].z & 15u) << 8) | ((v[i].w & 15u) << 12)) == t16);
        if (ok) break;
        if (++it > SPIN_LIMIT) __trap();
        BACKOFF();
    }
}
__device__ __forceinline__ uint64_t make_desc(uint32_t addr, uint32_t lbo, uint32_t sbo, uint32_t mode) {
    return (uint64_t)((addr & 0x3FFFF) >> 4) | ((uint64_t)((lbo & 0x3FFFF) >> 4) << 16) |
           ((uint64_t)((sbo & 0x3FFFF) >> 4) << 32) | ((uint64_t)mode << 62);
}
__device__ __forceinline__ void wg_fence() { asm volatile("wgmma.fence.sync.aligned;" ::: "memory"); }
__device__ __forceinline__ void wg_commit() { asm volatile("wgmma.commit_group.sync.aligned;" ::: "memory"); }
template <int N> __device__ __forceinline__ void wg_wait() { asm volatile("wgmma.wait_group.sync.aligned %0;" ::"n"(N) : "memory"); }
template <int N> __device__ __forceinline__ void pin(float (&d)[N]) {
#pragma unroll
    for (int i = 0; i < N; i++) asm volatile("" : "+f"(d[i])::"memory");
}
__device__ __forceinline__ uint32_t pack_bf16(float lo, float hi) {
    uint32_t r;
    asm("cvt.rn.bf16x2.f32 %0, %1, %2;" : "=r"(r) : "f"(hi), "f"(lo));
    return r;
}
__device__ __forceinline__ float bf_lo(uint32_t v) { return __uint_as_float(v << 16); }
__device__ __forceinline__ float bf_hi(uint32_t v) { return __uint_as_float(v & 0xFFFF0000u); }
__device__ __forceinline__ float bf_round(float v) { return __bfloat162float(__float2bfloat16(v)); }
__device__ __forceinline__ float ex2_mufu(float x) {
    float y;
    asm("ex2.approx.ftz.f32 %0, %1;" : "=f"(y) : "f"(x));
    return y;
}

#define ACC8(d, o) "+f"(d[o + 0]), "+f"(d[o + 1]), "+f"(d[o + 2]), "+f"(d[o + 3]), "+f"(d[o + 4]), "+f"(d[o + 5]), "+f"(d[o + 6]), "+f"(d[o + 7])
#define OUT8(d, o) "=f"(d[o + 0]), "=f"(d[o + 1]), "=f"(d[o + 2]), "=f"(d[o + 3]), "=f"(d[o + 4]), "=f"(d[o + 5]), "=f"(d[o + 6]), "=f"(d[o + 7])

__device__ __forceinline__ void wgmma_n192(float (&d)[96], uint64_t da, uint64_t db) {
    asm volatile(
        "wgmma.mma_async.sync.aligned.m64n192k16.f32.bf16.bf16 "
        "{%0,%1,%2,%3,%4,%5,%6,%7,%8,%9,%10,%11,%12,%13,%14,%15,%16,%17,%18,%19,%20,%21,%22,%23,%24,%25,%26,%27,%28,%29,%30,%31,"
        "%32,%33,%34,%35,%36,%37,%38,%39,%40,%41,%42,%43,%44,%45,%46,%47,%48,%49,%50,%51,%52,%53,%54,%55,%56,%57,%58,%59,%60,%61,%62,%63,"
        "%64,%65,%66,%67,%68,%69,%70,%71,%72,%73,%74,%75,%76,%77,%78,%79,%80,%81,%82,%83,%84,%85,%86,%87,%88,%89,%90,%91,%92,%93,%94,%95},"
        "%96, %97, 1, 1, 1, 0, 1;"
        : ACC8(d, 0), ACC8(d, 8), ACC8(d, 16), ACC8(d, 24), ACC8(d, 32), ACC8(d, 40), ACC8(d, 48), ACC8(d, 56),
          ACC8(d, 64), ACC8(d, 72), ACC8(d, 80), ACC8(d, 88)
        : "l"(da), "l"(db));
}
__device__ __forceinline__ void wgmma_n192_rs(float (&d)[96], const uint32_t* a, uint64_t db) {
    asm volatile(
        "wgmma.mma_async.sync.aligned.m64n192k16.f32.bf16.bf16 "
        "{%0,%1,%2,%3,%4,%5,%6,%7,%8,%9,%10,%11,%12,%13,%14,%15,%16,%17,%18,%19,%20,%21,%22,%23,%24,%25,%26,%27,%28,%29,%30,%31,"
        "%32,%33,%34,%35,%36,%37,%38,%39,%40,%41,%42,%43,%44,%45,%46,%47,%48,%49,%50,%51,%52,%53,%54,%55,%56,%57,%58,%59,%60,%61,%62,%63,"
        "%64,%65,%66,%67,%68,%69,%70,%71,%72,%73,%74,%75,%76,%77,%78,%79,%80,%81,%82,%83,%84,%85,%86,%87,%88,%89,%90,%91,%92,%93,%94,%95},"
        "{%96,%97,%98,%99}, %100, 1, 1, 1, 1;"
        : ACC8(d, 0), ACC8(d, 8), ACC8(d, 16), ACC8(d, 24), ACC8(d, 32), ACC8(d, 40), ACC8(d, 48), ACC8(d, 56),
          ACC8(d, 64), ACC8(d, 72), ACC8(d, 80), ACC8(d, 88)
        : "r"(a[0]), "r"(a[1]), "r"(a[2]), "r"(a[3]), "l"(db));
}
__device__ __forceinline__ void ldsm_x4(uint32_t* r, uint32_t addr) {
    asm volatile("ldmatrix.sync.aligned.m8n8.x4.shared.b16 {%0,%1,%2,%3}, [%4];"
                 : "=r"(r[0]), "=r"(r[1]), "=r"(r[2]), "=r"(r[3]) : "r"(addr) : "memory");
}
__device__ __forceinline__ void wgmma_n64(float (&d)[32], uint64_t da, uint64_t db) {
    asm volatile(
        "wgmma.mma_async.sync.aligned.m64n64k16.f32.bf16.bf16 "
        "{%0,%1,%2,%3,%4,%5,%6,%7,%8,%9,%10,%11,%12,%13,%14,%15,%16,%17,%18,%19,%20,%21,%22,%23,%24,%25,%26,%27,%28,%29,%30,%31},"
        "%32, %33, 1, 1, 1, 0, 1;"
        : ACC8(d, 0), ACC8(d, 8), ACC8(d, 16), ACC8(d, 24)
        : "l"(da), "l"(db));
}
__device__ __forceinline__ void wgmma_qk128(float (&d)[64], const uint32_t (&a)[4], uint64_t desc) {
    asm volatile(
        "wgmma.mma_async.sync.aligned.m64n128k16.f32.bf16.bf16 "
        "{%0,%1,%2,%3,%4,%5,%6,%7,%8,%9,%10,%11,%12,%13,%14,%15,%16,%17,%18,%19,%20,%21,%22,%23,%24,%25,%26,%27,%28,%29,%30,%31,"
        "%32,%33,%34,%35,%36,%37,%38,%39,%40,%41,%42,%43,%44,%45,%46,%47,%48,%49,%50,%51,%52,%53,%54,%55,%56,%57,%58,%59,%60,%61,%62,%63},"
        "{%64,%65,%66,%67}, %68, 0, 1, 1, 0;"
        : OUT8(d, 0), OUT8(d, 8), OUT8(d, 16), OUT8(d, 24), OUT8(d, 32), OUT8(d, 40), OUT8(d, 48), OUT8(d, 56)
        : "r"(a[0]), "r"(a[1]), "r"(a[2]), "r"(a[3]), "l"(desc));
}
__device__ __forceinline__ void wgmma_pv24(float (&o)[12], uint32_t a0, uint32_t a1, uint32_t a2, uint32_t a3, uint64_t desc) {
    asm volatile(
        "wgmma.mma_async.sync.aligned.m64n24k16.f32.bf16.bf16 "
        "{%0,%1,%2,%3,%4,%5,%6,%7,%8,%9,%10,%11}, {%12,%13,%14,%15}, %16, 1, 1, 1, 1;"
        : ACC8(o, 0), "+f"(o[8]), "+f"(o[9]), "+f"(o[10]), "+f"(o[11])
        : "r"(a0), "r"(a1), "r"(a2), "r"(a3), "l"(desc));
}

__device__ __forceinline__ uint32_t ex2_pair_poly(float x0, float x1) {
    const float M = 12288.0f + 31.0f;
    float t0 = x0 + M, t1 = x1 + M;
    uint32_t G = __byte_perm(__float_as_uint(t0), __float_as_uint(t1), 0x5410);
    uint32_t W, q;
    asm("lop3.b32 %0, %1, %2, %3, 0xEA;" : "=r"(W) : "r"(G), "r"(0x03FF03FFu), "r"(0x3C003C00u));
    asm("fma.rn.f16x2 %0, %1, %2, %3;" : "=r"(q) : "r"(0x15121512u), "r"(W), "r"(0x8acc8accu));
    asm("fma.rn.f16x2 %0, %1, %2, %3;" : "=r"(q) : "r"(q), "r"(W), "r"(0x1fc21fc2u));
    asm("fma.rn.f16x2 %0, %1, %2, %3;" : "=r"(q) : "r"(q), "r"(W), "r"(0x2f732f73u));
    return ((G & 0xFC00FC00u) >> 3) + q;
}
#define NPP 18
__device__ __forceinline__ constexpr bool use_poly_pair(int i) { return ((i % 32 + 1) * NPP) / 32 != ((i % 32) * NPP) / 32; }
__device__ __forceinline__ uint32_t ex2_pair(float x0, float x1, int i) {
    return use_poly_pair(i) ? ex2_pair_poly(x0, x1) : pack_bf16(ex2_mufu(x0), ex2_mufu(x1));
}
__device__ __forceinline__ unsigned int f2ord(float v) {
    const unsigned int u = __float_as_uint(v);
    const unsigned int o = u ^ ((unsigned int)((int)u >> 31) | 0x80000000u);
    return (v == v) ? o : 0u;
}
__device__ __forceinline__ void warp_top2(unsigned int ka, unsigned int ia, unsigned int kb, unsigned int ib, unsigned int& i1, unsigned int& i2) {
    const unsigned int m1 = __reduce_max_sync(0xffffffffu, max(ka, kb));
    i1 = __reduce_min_sync(0xffffffffu, min(ka == m1 ? ia : 0xffffffffu, kb == m1 ? ib : 0xffffffffu));
    const bool ra = (ia == i1), rb = (ib == i1);
    const unsigned int ka2 = ra ? 0u : ka, kb2 = rb ? 0u : kb, ia2 = ra ? 0xffffffffu : ia, ib2 = rb ? 0xffffffffu : ib;
    const unsigned int m2 = __reduce_max_sync(0xffffffffu, max(ka2, kb2));
    i2 = __reduce_min_sync(0xffffffffu, min(ka2 == m2 ? ia2 : 0xffffffffu, kb2 == m2 ? ib2 : 0xffffffffu));
}

constexpr int P1_STAGES = 5;
constexpr int P1_STAGE_BYTES = 16384 + 24576;
constexpr int KV_CHUNK = 10240;
constexpr int SM_WO = 0, SM_A3 = 163840, SM_WG = 131072;
constexpr int SM_MISC = 229376;
constexpr int SMEM_TOTAL = 232448;
struct Misc {
    uint64_t p1_full[P1_STAGES], p1_empty[P1_STAGES];
    uint64_t kv[16];
    uint64_t wo[8], a3[8], moe;
    unsigned int tag;
    int fast;
    int idx[2], cslot[2];
    alignas(16) float sel[8];
    unsigned int norm[12];
    union alignas(16) {
        struct { float mu[128], rs[128], cs[192]; } p1;
        struct { float part[2][64][3]; float mu[64], rs[64], r[64]; } p3;
    };
};
static_assert(sizeof(Misc) <= SMEM_TOTAL - SM_MISC, "misc smem");

__global__ void __launch_bounds__(512, 1)
mega_kernel(const __grid_constant__ CUtensorMap tmX, const __grid_constant__ CUtensorMap tmW,
            const __grid_constant__ CUtensorMap tmO, const __grid_constant__ CUtensorMap tmWo,
            const __grid_constant__ CUtensorMap tmG, const __grid_constant__ CUtensorMap tmU,
            const __nv_bfloat16* __restrict__ x, const __nv_bfloat16* __restrict__ wqkv, const __nv_bfloat16* __restrict__ wo,
            const __nv_bfloat16* __restrict__ w_r, const __nv_bfloat16* __restrict__ w_gate,
            const __nv_bfloat16* __restrict__ w_up, const __nv_bfloat16* __restrict__ w_down,
            __nv_bfloat16* __restrict__ out) {
    extern __shared__ __align__(1024) char smem[];
    Misc& ms = *reinterpret_cast<Misc*>(smem + SM_MISC);
    const int tid = threadIdx.x, lane = tid & 31;
    const int warp = __shfl_sync(0xffffffffu, tid >> 5, 0);
    const int wg = warp >> 2, w4 = warp & 3, g = lane >> 2, t4 = lane & 3;
    const int cta = blockIdx.x;
    const int rb = cta >> 3, hg = cta & 7;

    if (warp == 12) {
        if (lane == 0) {
            TS(0);
            if (smem_u32(smem) & 1023) __trap();
            for (int i = 0; i < P1_STAGES; i++) { mbar_init(smem_u32(&ms.p1_full[i]), 1); mbar_init(smem_u32(&ms.p1_empty[i]), 8); }
            asm volatile("fence.mbarrier_init.release.cluster;" ::: "memory");
        }
        __syncwarp();
        bar_arrive(13, 288);
        bar_arrive(14, 256);
    } else {
        if (tid == 32) {
            for (int i = 0; i < 16; i++) mbar_init(smem_u32(&ms.kv[i]), 1);
            for (int i = 0; i < 8; i++) { mbar_init(smem_u32(&ms.wo[i]), 1); mbar_init(smem_u32(&ms.a3[i]), 1); }
            mbar_init(smem_u32(&ms.moe), 1);
            asm volatile("fence.mbarrier_init.release.cluster;" ::: "memory");
        }
        if (tid >= 64 && tid < 76) ms.norm[tid - 64] = 0;
        if (tid == 416) ms.tag = __ldcg(&gEpoch) + 1u;
    }

    if (wg < 2) {
        float acc[96];
#pragma unroll
        for (int i = 0; i < 96; i++) acc[i] = 0.f;
        bar_sync(13, 288);
#pragma unroll 1
        for (int kc = 0; kc < 8; kc++) {
            const int s = kc % P1_STAGES;
            mbar_wait(smem_u32(&ms.p1_full[s]), (kc / P1_STAGES) & 1);
            if (tid == 0) TS(24 + kc);
            const uint32_t sa = smem_u32(smem + s * P1_STAGE_BYTES), sb = sa + 16384;
            const uint64_t da = make_desc(sa + wg * 8192, 16, 1024, 1);
            const uint64_t db = make_desc(sb, 8192, 1024, 1);
            wg_fence();
#pragma unroll
            for (int ks = 0; ks < 4; ks++) wgmma_n192(acc, da + ks * 2, db + ks * 128);
            wg_commit();
            wg_wait<0>();
            if (lane == 0) mbar_arrive(smem_u32(&ms.p1_empty[s]));
        }
        pin(acc);
        if (tid == 0) TS(1);
        bar_sync(1, 480);
        const unsigned int tag = ms.tag;
        if (tid == 0) TS(16);
        const int lr0 = wg * 64 + w4 * 16 + g, lr1 = lr0 + 8;
        const float mu0 = ms.p1.mu[lr0], mu1 = ms.p1.mu[lr1], rs0 = ms.p1.rs[lr0], rs1 = ms.p1.rs[lr1];
        const int lg0 = wg * 8 + w4 * 2;
        const int rg0 = rb * 16 + lg0;
#pragma unroll
        for (int hh = 0; hh < 4; hh++) {
            const int head = hg * 4 + hh;
            float nrm[3];
#pragma unroll
            for (int sec = 0; sec < 3; sec++) {
                float sq0 = 0.f, sq1 = 0.f, vm = 0.f;
#pragma unroll
                for (int db = 0; db < 2; db++) {
                    const int j = sec * 8 + hh * 2 + db;
                    const float2 c = *reinterpret_cast<const float2*>(&ms.p1.cs[j * 8 + 2 * t4]);
                    const float f0 = sec == 0 ? rs0 * QSCALE : rs0, f1 = sec == 0 ? rs1 * QSCALE : rs1;
                    const float a0 = (acc[4 * j + 0] - mu0 * c.x) * f0, a1 = (acc[4 * j + 1] - mu0 * c.y) * f0;
                    const float b0 = (acc[4 * j + 2] - mu1 * c.x) * f1, b1 = (acc[4 * j + 3] - mu1 * c.y) * f1;
                    const uint32_t pa = pack_bf16(a0, a1), pb = pack_bf16(b0, b1);
                    if (sec < 2) {
                        uint32_t* dst = sec == 0 ? reinterpret_cast<uint32_t*>(gQ) + ((size_t)head * S_LEN * DH + rg0 * 128) / 2
                                                 : reinterpret_cast<uint32_t*>(gKV) + (size_t)(head * 16 + rb) * 2048 + lg0 * 64;
                        dst[db * 32 + lane] = pa;
                        dst[64 + db * 32 + lane] = pb;
                        sq0 = fmaf(a0, a0, fmaf(a1, a1, sq0));
                        sq1 = fmaf(b0, b0, fmaf(b1, b1, sq1));
                    } else {
                        uint32_t* dst = reinterpret_cast<uint32_t*>(gKV) + (size_t)(head * 16 + rb) * 2048 + 1024 + db * 512 + lg0 * 32;
                        dst[lane] = pa;
                        dst[32 + lane] = pb;
                        vm = fmaxf(vm, fmaxf(fmaxf(fabsf(a0), fabsf(a1)), fmaxf(fabsf(b0), fabsf(b1))));
                        if (!(a0 + a1 + b0 + b1 == a0 + a1 + b0 + b1)) vm = __int_as_float(0x7f800000);
                    }
                }
                if (sec < 2) {
                    sq0 += __shfl_xor_sync(0xffffffffu, sq0, 1); sq0 += __shfl_xor_sync(0xffffffffu, sq0, 2);
                    sq1 += __shfl_xor_sync(0xffffffffu, sq1, 1); sq1 += __shfl_xor_sync(0xffffffffu, sq1, 2);
                    vm = fmaxf(sq0, sq1);
                    if (!(sq0 + sq1 < 3.0e38f)) vm = __int_as_float(0x7f800000);
                }
                nrm[sec] = vm;
            }
            const unsigned int a = __reduce_max_sync(0xffffffffu, __float_as_uint(nrm[0]));
            const unsigned int b = __reduce_max_sync(0xffffffffu, __float_as_uint(nrm[1]));
            const unsigned int c = __reduce_max_sync(0xffffffffu, __float_as_uint(nrm[2]));
            if (lane == 0) { atomicMax(&ms.norm[hh * 3 + 0], a); atomicMax(&ms.norm[hh * 3 + 1], b); atomicMax(&ms.norm[hh * 3 + 2], c); }
        }
        if (tid == 0) TS(17);
        bar_sync(2, 256);
        if (tid == 0) TS(18);
        if (tid < 12) gNorm[(rb * NH + hg * 4 + tid / 3) * 4 + tid % 3] = __uint_as_float(ms.norm[tid]);
        __syncwarp();
        if (tid == 0) { st_flag(&gFlagQKV[hg * 16 + rb], tag); TS(2); }
    } else if (wg == 2) {
        const int t = tid - 256;
        bar_sync(14, 256);
        mbar_wait(smem_u32(&ms.p1_full[0]), 0);
        {
            const int row = rb * 128 + hg * 16 + (t >> 3), j = t & 7;
            const uint4* xp = reinterpret_cast<const uint4*>(x + (size_t)row * DM);
            uint4 v[8];
#pragma unroll
            for (int i = 0; i < 8; i++) v[i] = __ldg(xp + i * 8 + j);
            float s1 = 0.f;
#pragma unroll
            for (int i = 0; i < 8; i++) {
                const uint32_t w[4] = {v[i].x, v[i].y, v[i].z, v[i].w};
#pragma unroll
                for (int e = 0; e < 4; e++) s1 += bf_lo(w[e]) + bf_hi(w[e]);
            }
            s1 += __shfl_xor_sync(0xffffffffu, s1, 1); s1 += __shfl_xor_sync(0xffffffffu, s1, 2); s1 += __shfl_xor_sync(0xffffffffu, s1, 4);
            const float mu = s1 * (1.f / DM);
            float s2 = 0.f;
#pragma unroll
            for (int i = 0; i < 8; i++) {
                const uint32_t w[4] = {v[i].x, v[i].y, v[i].z, v[i].w};
#pragma unroll
                for (int e = 0; e < 4; e++) {
                    const float a = bf_lo(w[e]) - mu, b = bf_hi(w[e]) - mu;
                    s2 = fmaf(a, a, fmaf(b, b, s2));
                }
            }
            s2 += __shfl_xor_sync(0xffffffffu, s2, 1); s2 += __shfl_xor_sync(0xffffffffu, s2, 2); s2 += __shfl_xor_sync(0xffffffffu, s2, 4);
            bar_sync(11, 224);
            if (j == 0) st_pkt(&gStat1[row], make_uint4(__float_as_uint(mu), __float_as_uint(rsqrtf(s2 * (1.f / DM) + LN_EPS)), 0u, ms.tag));
        }
        const unsigned int tag = ms.tag;
        if (t == 0) TS(32);
        uint4 st[1];
        if (t < 8) wait_pkts<1, 0xffffffffu>(&gStat1[rb * 128 + t * 16 + 15], 0, tag, st);
        bar_sync(12, 128);
        wait_pkts<1, 0xffffffffu>(&gStat1[rb * 128 + t], 0, tag, st);
        if (t == 0) TS(34);
        ms.p1.mu[t] = __uint_as_float(st[0].x);
        ms.p1.rs[t] = __uint_as_float(st[0].y);
        bar_arrive(1, 480);
    } else {
      if (warp == 12) {
        if (lane == 0) {
#pragma unroll 1
            for (int kc = 0; kc < 8; kc++) {
                const int s = kc % P1_STAGES;
                if (kc >= P1_STAGES) mbar_wait(smem_u32(&ms.p1_empty[s]), 0);
                const uint32_t bar = smem_u32(&ms.p1_full[s]);
                const uint32_t sa = smem_u32(smem + s * P1_STAGE_BYTES), sb = sa + 16384;
                mbar_expect_tx(bar, P1_STAGE_BYTES);
                tma_2d(sa, &tmX, kc * 64, rb * 128, bar);
#pragma unroll
                for (int p = 0; p < 3; p++) tma_2d(sb + p * 8192, &tmW, p * 512 + hg * 64, kc * 64, bar);
            }
        }
      } else {
        const int t = tid - 416;
        bar_sync(14, 256);
        mbar_wait(smem_u32(&ms.p1_full[0]), 0);
        const int c16 = t >> 2, rs = t & 3;
        const __nv_bfloat16* wp = wqkv + (size_t)(rb * 32 + rs) * (3 * DM) + (c16 >> 3) * 512 + hg * 64 + (c16 & 7) * 8;
        uint4 v[8];
#pragma unroll
        for (int i = 0; i < 8; i++) v[i] = __ldg(reinterpret_cast<const uint4*>(wp + (size_t)i * 4 * (3 * DM)));
        float a[8] = {};
#pragma unroll
        for (int i = 0; i < 8; i++) {
            a[0] += bf_lo(v[i].x); a[1] += bf_hi(v[i].x); a[2] += bf_lo(v[i].y); a[3] += bf_hi(v[i].y);
            a[4] += bf_lo(v[i].z); a[5] += bf_hi(v[i].z); a[6] += bf_lo(v[i].w); a[7] += bf_hi(v[i].w);
        }
#pragma unroll
        for (int e = 0; e < 8; e++) { a[e] += __shfl_xor_sync(0xffffffffu, a[e], 1); a[e] += __shfl_xor_sync(0xffffffffu, a[e], 2); }
        bar_sync(11, 224);
        const unsigned int tag = ms.tag;
        const int pk = c16 * 2 + rs;
        if (rs < 2) st_pkt(&gCsPart[(hg * 16 + rb) * 48 + pk], embed_tag(rs ? a[4] : a[0], rs ? a[5] : a[1], rs ? a[6] : a[2], rs ? a[7] : a[3], tag));
        if (t == 0) TS(35);
        if (t < 16) { uint4 gate[1]; wait_pkts4<1>(&gCsPart[(hg * 16 + t) * 48 + 47], 0, tag, gate); }
        bar_sync(8, 96);
        if (t == 0) TS(36);
        if (rs < 2) {
            uint4 p[16];
            wait_pkts4<16>(&gCsPart[hg * 16 * 48 + pk], 48, tag, p);
            float s0 = 0.f, s1 = 0.f, s2 = 0.f, s3 = 0.f;
#pragma unroll
            for (int i = 0; i < 16; i++) {
                s0 += __uint_as_float(p[i].x); s1 += __uint_as_float(p[i].y); s2 += __uint_as_float(p[i].z); s3 += __uint_as_float(p[i].w);
            }
            *reinterpret_cast<float4*>(&ms.p1.cs[pk * 4]) = make_float4(s0, s1, s2, s3);
            if (t == 0) TS(37);
        }
        __syncwarp();
        bar_arrive(1, 480);
      }
    }
    __syncthreads();
    if (tid == 0) TS(20);
    const unsigned int tag = ms.tag;

    const int head = hg * 4 + (rb >> 2), quarter = rb & 3;
    {
        const uint4 one = make_uint4(0x00003F80u, 0, 0, 0);
#pragma unroll
        for (int i = 0; i < 4; i++) {
            const int e = tid + i * 512;
            *reinterpret_cast<uint4*>(smem + (e >> 7) * KV_CHUNK + 8192 + (e & 127) * 16) = one;
        }
        asm volatile("fence.proxy.async.shared::cta;" ::: "memory");
    }
    if (warp == 0) {
        if (lane < 16) wait_flag(&gFlagQKV[hg * 16 + lane], tag);
        __syncwarp();
        if (lane == 0) TS(21);
    }
    __syncthreads();
    if (lane == 0) {
        fence_proxy_async_global();
        const uint32_t bar = smem_u32(&ms.kv[warp]);
        mbar_expect_tx(bar, 8192);
        bulk_g2s(smem_u32(smem + warp * KV_CHUNK), reinterpret_cast<const char*>(gKV) + (size_t)(head * 16 + warp) * 8192, 8192, bar);
    }
    if (warp == 0) {
        const float4 n = __ldcg(reinterpret_cast<const float4*>(&gNorm[((lane & 15) * NH + head) * 4]));
        const float q2 = __uint_as_float(__reduce_max_sync(0xffffffffu, __float_as_uint(n.x)));
        const float k2 = __uint_as_float(__reduce_max_sync(0xffffffffu, __float_as_uint(n.y)));
        const float vm = __uint_as_float(__reduce_max_sync(0xffffffffu, __float_as_uint(n.z)));
        if (lane == 0) ms.fast = (q2 * k2 * 1.04f <= 841.f) && (vm <= 1.0e18f) && (vm >= 1.0e-18f || vm == 0.f);
    }
    __syncthreads();
    if (tid == 0) TS(3);
    {
        const bool fast = ms.fast != 0;
        const uint64_t descK0 = make_desc(smem_u32(smem), 128, 256, 0);
        const uint64_t descV0 = make_desc(smem_u32(smem + 4096), 128, 2048, 0);
#pragma unroll 1
        for (int pass = 0; pass < 2; pass++) {
            const int tile = pass * 16 + quarter * 4 + wg;
            const int row0 = tile * 64 + w4 * 16;
            uint32_t q[4];
            {
                const uint32_t* Qp = reinterpret_cast<const uint32_t*>(gQ) + ((size_t)head * S_LEN * DH + (row0 >> 3) * 128) / 2;
                q[0] = __ldcg(Qp + lane); q[2] = __ldcg(Qp + 32 + lane);
                q[1] = __ldcg(Qp + 64 + lane); q[3] = __ldcg(Qp + 96 + lane);
            }
            float o[12];
#pragma unroll
            for (int i = 0; i < 12; i++) o[i] = 0.f;
            if (fast) {
#pragma unroll 1
                for (int j = 0; j < 16; j++) {
                    if (pass == 0) mbar_wait(smem_u32(&ms.kv[j]), 0);
                    float s[64];
                    wg_fence();
                    wgmma_qk128(s, q, descK0 + (uint64_t)(j * (KV_CHUNK >> 4)));
                    wg_commit();
                    wg_wait<0>();
                    pin(s);
#pragma unroll
                    for (int k = 0; k < 8; k++) {
                        uint32_t p[4];
#pragma unroll
                        for (int i = 0; i < 4; i++) p[i] = ex2_pair(s[8 * k + 2 * i], s[8 * k + 2 * i + 1], 4 * k + i);
                        wg_fence();
                        wgmma_pv24(o, p[0], p[1], p[2], p[3], descV0 + (uint64_t)(j * (KV_CHUNK >> 4) + k * 16));
                        wg_commit();
                        wg_wait<2>();
                    }
                }
            } else {
                float m0 = -INFINITY, m1 = -INFINITY;
#pragma unroll 1
                for (int j = 0; j < 16; j++) {
                    if (pass == 0) mbar_wait(smem_u32(&ms.kv[j]), 0);
                    float s[64];
                    wg_fence();
                    wgmma_qk128(s, q, descK0 + (uint64_t)(j * (KV_CHUNK >> 4)));
                    wg_commit();
                    wg_wait<0>();
                    pin(s);
                    pin(o);
                    float n0 = m0, n1 = m1;
#pragma unroll
                    for (int i = 0; i < 16; i++) {
                        n0 = fmaxf(n0, fmaxf(s[4 * i], s[4 * i + 1]));
                        n1 = fmaxf(n1, fmaxf(s[4 * i + 2], s[4 * i + 3]));
                    }
                    n0 = fmaxf(n0, __shfl_xor_sync(0xffffffffu, n0, 1)); n0 = fmaxf(n0, __shfl_xor_sync(0xffffffffu, n0, 2));
                    n1 = fmaxf(n1, __shfl_xor_sync(0xffffffffu, n1, 1)); n1 = fmaxf(n1, __shfl_xor_sync(0xffffffffu, n1, 2));
                    const float a0 = ex2_mufu(m0 - n0), a1 = ex2_mufu(m1 - n1);
                    m0 = n0; m1 = n1;
#pragma unroll
                    for (int i = 0; i < 3; i++) { o[4 * i] *= a0; o[4 * i + 1] *= a0; o[4 * i + 2] *= a1; o[4 * i + 3] *= a1; }
#pragma unroll
                    for (int k = 0; k < 8; k++) {
                        const uint32_t p0 = pack_bf16(ex2_mufu(s[8 * k] - n0), ex2_mufu(s[8 * k + 1] - n0));
                        const uint32_t p1 = pack_bf16(ex2_mufu(s[8 * k + 2] - n1), ex2_mufu(s[8 * k + 3] - n1));
                        const uint32_t p2 = pack_bf16(ex2_mufu(s[8 * k + 4] - n0), ex2_mufu(s[8 * k + 5] - n0));
                        const uint32_t p3 = pack_bf16(ex2_mufu(s[8 * k + 6] - n1), ex2_mufu(s[8 * k + 7] - n1));
                        wg_fence();
                        wgmma_pv24(o, p0, p1, p2, p3, descV0 + (uint64_t)(j * (KV_CHUNK >> 4) + k * 16));
                        wg_commit();
                        wg_wait<2>();
                    }
                    wg_wait<0>();
                }
            }
            wg_wait<0>();
            pin(o);
            if (pass == 0 && tid == 511) {
                bulk_prefetch_l2(reinterpret_cast<const char*>(wo) + cta * 4096, 4096);
                bulk_prefetch_l2(reinterpret_cast<const char*>(w_gate) + cta * 14336, 14336);
                bulk_prefetch_l2(reinterpret_cast<const char*>(w_up) + cta * 14336, 14336);
                bulk_prefetch_l2(reinterpret_cast<const char*>(w_down) + cta * 14336, 14336);
            }
            __syncwarp();
            const float l0 = __shfl_sync(0xffffffffu, o[8], lane & ~3), l1 = __shfl_sync(0xffffffffu, o[10], lane & ~3);
            const float r0 = __fdividef(1.f, l0), r1 = __fdividef(1.f, l1);
            uint32_t* Op = reinterpret_cast<uint32_t*>(gO + (size_t)row0 * DM + head * DH);
            Op[g * 256 + t4] = pack_bf16(o[0] * r0, o[1] * r0);
            Op[(g + 8) * 256 + t4] = pack_bf16(o[2] * r1, o[3] * r1);
            Op[g * 256 + 4 + t4] = pack_bf16(o[4] * r0, o[5] * r0);
            Op[(g + 8) * 256 + 4 + t4] = pack_bf16(o[6] * r1, o[7] * r1);
            bar_sync(3 + wg, 128);
            if ((tid & 127) == 0) st_flag(&gFlagO[tile * 32 + head], tag);
        }
    }
    __syncthreads();
    if (tid == 0) TS(4);

    const int rb3 = cta >> 2, cb = cta & 3;
    if (wg < 2) {
        const int r0 = rb3 * 64 + w4 * 16 + g, r1 = r0 + 8;
        const int col0 = cb * 128 + wg * 64 + 2 * t4;
        uint32_t xa[8], xb[8], wr[8];
#pragma unroll
        for (int j = 0; j < 8; j++) {
            xa[j] = __ldg(reinterpret_cast<const uint32_t*>(x + (size_t)r0 * DM + col0 + j * 8));
            xb[j] = __ldg(reinterpret_cast<const uint32_t*>(x + (size_t)r1 * DM + col0 + j * 8));
            wr[j] = __ldg(reinterpret_cast<const uint32_t*>(w_r + col0 + j * 8));
        }
        const float p0 = __bfloat162float(x[(size_t)r0 * DM]), p1 = __bfloat162float(x[(size_t)r1 * DM]);
        const float pivot = __bfloat162float(x[(size_t)(rb3 * 64 + (tid >> 2)) * DM]);
        float wsum = 0.f;
        {
            const uint4 a = __ldg(reinterpret_cast<const uint4*>(w_r) + lane), b = __ldg(reinterpret_cast<const uint4*>(w_r) + 32 + lane);
            const uint32_t w[8] = {a.x, a.y, a.z, a.w, b.x, b.y, b.z, b.w};
#pragma unroll
            for (int e = 0; e < 8; e++) wsum += bf_lo(w[e]) + bf_hi(w[e]);
#pragma unroll
            for (int m = 16; m; m >>= 1) wsum += __shfl_xor_sync(0xffffffffu, wsum, m);
        }
        float acc[32];
#pragma unroll
        for (int i = 0; i < 32; i++) acc[i] = 0.f;
#pragma unroll 1
        for (int kc = 0; kc < 8; kc++) {
            mbar_wait(smem_u32(&ms.wo[kc]), 0);
            mbar_wait(smem_u32(&ms.a3[kc]), 0);
            const uint64_t da = make_desc(smem_u32(smem + SM_A3 + kc * 8192), 16, 1024, 1);
            const uint64_t db = make_desc(smem_u32(smem + SM_WO + kc * 16384 + wg * 8192), 8192, 1024, 1);
            wg_fence();
#pragma unroll
            for (int ks = 0; ks < 4; ks++) wgmma_n64(acc, da + ks * 2, db + ks * 128);
            wg_commit();
        }
        wg_wait<0>();
        pin(acc);
        if (tid == 0) TS(6);
        float s1a = 0.f, s2a = 0.f, s3a = 0.f, s1b = 0.f, s2b = 0.f, s3b = 0.f;
#pragma unroll
        for (int j = 0; j < 8; j++) {
            const uint32_t ha = pack_bf16(bf_lo(xa[j]) + acc[4 * j], bf_hi(xa[j]) + acc[4 * j + 1]);
            const uint32_t hb = pack_bf16(bf_lo(xb[j]) + acc[4 * j + 2], bf_hi(xb[j]) + acc[4 * j + 3]);
            xa[j] = ha; xb[j] = hb;
            const float w0 = bf_lo(wr[j]), w1 = bf_hi(wr[j]);
            const float da0 = bf_lo(ha) - p0, da1 = bf_hi(ha) - p0, db0 = bf_lo(hb) - p1, db1 = bf_hi(hb) - p1;
            s1a += da0 + da1; s2a = fmaf(da0, da0, fmaf(da1, da1, s2a)); s3a = fmaf(da0, w0, fmaf(da1, w1, s3a));
            s1b += db0 + db1; s2b = fmaf(db0, db0, fmaf(db1, db1, s2b)); s3b = fmaf(db0, w0, fmaf(db1, w1, s3b));
        }
#pragma unroll
        for (int m = 1; m <= 2; m <<= 1) {
            s1a += __shfl_xor_sync(0xffffffffu, s1a, m); s2a += __shfl_xor_sync(0xffffffffu, s2a, m); s3a += __shfl_xor_sync(0xffffffffu, s3a, m);
            s1b += __shfl_xor_sync(0xffffffffu, s1b, m); s2b += __shfl_xor_sync(0xffffffffu, s2b, m); s3b += __shfl_xor_sync(0xffffffffu, s3b, m);
        }
        if (t4 == 0) {
            const int lr = w4 * 16 + g;
            ms.p3.part[wg][lr][0] = s1a; ms.p3.part[wg][lr][1] = s2a; ms.p3.part[wg][lr][2] = s3a;
            ms.p3.part[wg][lr + 8][0] = s1b; ms.p3.part[wg][lr + 8][1] = s2b; ms.p3.part[wg][lr + 8][2] = s3b;
        }
        if (tid == 0) TS(11);
        bar_sync(1, 256);
        if (tid == 0) TS(12);
        if (tid < 64) {
            st_pkt(&gPart[(rb3 * 64 + tid) * 4 + cb],
                   make_uint4(__float_as_uint(ms.p3.part[0][tid][0] + ms.p3.part[1][tid][0]), __float_as_uint(ms.p3.part[0][tid][1] + ms.p3.part[1][tid][1]),
                              __float_as_uint(ms.p3.part[0][tid][2] + ms.p3.part[1][tid][2]), tag));
        }
        {
            const int lr = tid >> 2, sl = tid & 3;
            uint4 pv[1];
            wait_pkts<1, 0xffffffffu>(&gPart[rb3 * 256 + tid], 0, tag, pv);
            float s1 = __uint_as_float(pv[0].x), s2 = __uint_as_float(pv[0].y), s3 = __uint_as_float(pv[0].z);
            if (tid == 0) TS(14);
#pragma unroll
            for (int m = 1; m <= 2; m <<= 1) {
                s1 += __shfl_xor_sync(0xffffffffu, s1, m); s2 += __shfl_xor_sync(0xffffffffu, s2, m); s3 += __shfl_xor_sync(0xffffffffu, s3, m);
            }
            if (sl == 0) {
                const float md = s1 * (1.f / DM);
                const float var = fmaxf(s2 * (1.f / DM) - md * md, 0.f);
                const float rs = rsqrtf(var + LN_EPS);
                ms.p3.mu[lr] = pivot + md;
                ms.p3.rs[lr] = rs;
                ms.p3.r[lr] = (s3 - md * wsum) * rs;
            }
        }
        bar_sync(1, 256);
        if (tid == 0) TS(7);
        {
            unsigned int i1, i2;
            warp_top2(f2ord(ms.p3.r[lane]), lane, f2ord(ms.p3.r[lane + 32]), lane + 32, i1, i2);
            if (cb == 0) {
                const int c = tid & 1, li = c ? i2 : i1;
                st_pkt(&gCand[(tid >> 1) * 64 + rb3 * 2 + c],
                       make_uint4(__float_as_uint(ms.p3.r[li]), __float_as_uint(ms.p3.mu[li]), __float_as_uint(ms.p3.rs[li]),
                                  (tag << 11) | (unsigned int)(rb3 * 64 + li)));
            }
#pragma unroll
            for (int c = 0; c < 2; c++) {
                const unsigned int li = c ? i2 : i1;
                if ((int)(li >> 4) == w4 && (int)(li & 7) == g) {
                    const bool hi = (li & 8) != 0;
                    uint4* dst = &gCandRow[(rb3 * 2 + c) * 128 + (cb * 2 + wg) * 16 + t4];
#pragma unroll
                    for (int q = 0; q < 4; q++)
                        st_pkt(dst + q * 4, make_uint4(hi ? xb[2 * q] : xa[2 * q], hi ? xb[2 * q + 1] : xa[2 * q + 1], 0u, tag));
                }
            }
            if (tid == 0) TS(15);
        }
        bar_sync(2, 512);
        {
            const int idx0 = ms.idx[0], idx1 = ms.idx[1];
            const int lr0 = w4 * 16 + g;
            const float mu0 = ms.p3.mu[lr0], rs0 = ms.p3.rs[lr0], mu1 = ms.p3.mu[lr0 + 8], rs1 = ms.p3.rs[lr0 + 8];
            const bool w0 = (r0 != idx0 && r0 != idx1), w1 = (r1 != idx0 && r1 != idx1);
#pragma unroll
            for (int j = 0; j < 8; j++) {
                const float a0 = bf_lo(xa[j]), a1 = bf_hi(xa[j]), b0 = bf_lo(xb[j]), b1 = bf_hi(xb[j]);
                const uint32_t la = pack_bf16((a0 - mu0) * rs0, (a1 - mu0) * rs0);
                const uint32_t lb = pack_bf16((b0 - mu1) * rs1, (b1 - mu1) * rs1);
                if (w0) *reinterpret_cast<uint32_t*>(out + (size_t)r0 * DM + col0 + j * 8) = pack_bf16(a0 + bf_lo(la), a1 + bf_hi(la));
                if (w1) *reinterpret_cast<uint32_t*>(out + (size_t)r1 * DM + col0 + j * 8) = pack_bf16(b0 + bf_lo(lb), b1 + bf_hi(lb));
            }
        }
    } else {
        const int t = tid - 256;
        {
            const int kc = warp - 8;
            if (lane == 0) {
                const uint32_t bar = smem_u32(&ms.wo[kc]);
                mbar_expect_tx(bar, 16384);
                tma_2d(smem_u32(smem + SM_WO + kc * 16384), &tmWo, cb * 128, kc * 64, bar);
                tma_2d(smem_u32(smem + SM_WO + kc * 16384 + 8192), &tmWo, cb * 128 + 64, kc * 64, bar);
                if (kc < 4 && cta < NFFN) {
                    const uint32_t mb = smem_u32(&ms.moe);
                    if (kc == 0) mbar_expect_tx(mb, 32768);
                    tma_2d(smem_u32(smem + SM_WG + kc * 8192), (kc & 2) ? &tmU : &tmG, cta * 16, (kc & 1) * 256, mb);
                }
            }
            if (lane < 4) wait_flag(&gFlagO[rb3 * 32 + kc * 4 + lane], tag);
            __syncwarp();
            if (lane == 0) {
                if (kc == 7) TS(5);
                fence_proxy_async_global();
                const uint32_t bar = smem_u32(&ms.a3[kc]);
                mbar_expect_tx(bar, 8192);
                tma_2d(smem_u32(smem + SM_A3 + kc * 8192), &tmO, kc * 64, rb3 * 64, bar);
            }
            __syncwarp();
        }
        uint32_t wd[16];
        if (cta < NFFN) {
#pragma unroll
            for (int k = 0; k < 16; k++) wd[k] = __ldg(reinterpret_cast<const uint32_t*>(w_down + (size_t)(cta * 16 + k) * DM + 2 * t));
        }
        if (warp == 8) {
            if (lane == 0) TS(56);
            uint4 cv[2];
            wait_pkts<2, 0xfffff800u>(&gCand[cta * 64 + lane * 2], 1, tag << 11, cv);
            if (lane == 0) TS(54);
            unsigned int i1, i2;
            warp_top2(f2ord(__uint_as_float(cv[0].x)), cv[0].w & 0x7ffu, f2ord(__uint_as_float(cv[1].x)), cv[1].w & 0x7ffu, i1, i2);
#pragma unroll
            for (int c = 0; c < 2; c++) {
                const unsigned int ci = cv[c].w & 0x7ffu;
                if (ci == i1 || ci == i2) {
                    const int o = ci == i1 ? 0 : 1;
                    ms.idx[o] = (int)ci;
                    ms.cslot[o] = lane * 2 + c;
                    *reinterpret_cast<float4*>(&ms.sel[o * 4]) =
                        make_float4(__uint_as_float(cv[c].y), __uint_as_float(cv[c].z), __fdividef(1.f, 1.f + __expf(-__uint_as_float(cv[c].x))), 0.f);
                }
            }
            if (lane == 0) TS(8);
        }
        bar_sync(2, 512);
        const int idx0 = ms.idx[0], idx1 = ms.idx[1];
        float* sX = reinterpret_cast<float*>(smem + SM_A3);
        float* sH = sX + 1024;
        float* sPart = sX + 2048;
        float* sAct = sPart + 512;
        if (cta < NFFN) {
            {
                const int tk = t >> 7, P = t & 127;
                uint4 hv[1];
                wait_pkts<1, 0xffffffffu>(&gCandRow[ms.cslot[tk] * 128 + P], 0, tag, hv);
                const float mu = ms.sel[tk * 4], rs = ms.sel[tk * 4 + 1];
                const int col = (P >> 4) * 64 + ((P >> 2) & 3) * 16 + (P & 3) * 2;
                const uint32_t l0 = pack_bf16((bf_lo(hv[0].x) - mu) * rs, (bf_hi(hv[0].x) - mu) * rs);
                const uint32_t l1 = pack_bf16((bf_lo(hv[0].y) - mu) * rs, (bf_hi(hv[0].y) - mu) * rs);
                *reinterpret_cast<float2*>(&sX[tk * 512 + col]) = make_float2(bf_lo(l0), bf_hi(l0));
                *reinterpret_cast<float2*>(&sX[tk * 512 + col + 8]) = make_float2(bf_lo(l1), bf_hi(l1));
                *reinterpret_cast<float2*>(&sH[tk * 512 + col]) = make_float2(bf_lo(hv[0].x), bf_hi(hv[0].x));
                *reinterpret_cast<float2*>(&sH[tk * 512 + col + 8]) = make_float2(bf_lo(hv[0].y), bf_hi(hv[0].y));
            }
            mbar_wait(smem_u32(&ms.moe), 0);
            bar_sync(1 + 8, 256);
            {
                const int wv = warp - 8, kk = lane >> 3, cp = lane & 7;
                float a[2][2][2] = {};
#pragma unroll
                for (int i = 0; i < 16; i++) {
                    const int k = wv * 64 + i * 4 + kk;
                    const float x0 = sX[k], x1 = sX[512 + k];
#pragma unroll
                    for (int mat = 0; mat < 2; mat++) {
                        const uint32_t w = *reinterpret_cast<const uint32_t*>(smem + SM_WG + mat * 16384 + k * 32 + cp * 4);
                        a[mat][0][0] = fmaf(x0, bf_lo(w), a[mat][0][0]); a[mat][0][1] = fmaf(x0, bf_hi(w), a[mat][0][1]);
                        a[mat][1][0] = fmaf(x1, bf_lo(w), a[mat][1][0]); a[mat][1][1] = fmaf(x1, bf_hi(w), a[mat][1][1]);
                    }
                }
#pragma unroll
                for (int mat = 0; mat < 2; mat++)
#pragma unroll
                    for (int tk = 0; tk < 2; tk++)
#pragma unroll
                        for (int e = 0; e < 2; e++) {
                            float v = a[mat][tk][e];
                            v += __shfl_xor_sync(0xffffffffu, v, 8);
                            v += __shfl_xor_sync(0xffffffffu, v, 16);
                            if (kk == 0) sPart[(wv * 2 + tk) * 32 + mat * 16 + 2 * cp + e] = v;
                        }
            }
            bar_sync(1 + 8, 256);
            if (t < 32) {
                const int tk = t >> 4, c = t & 15;
                float gs = 0.f, us = 0.f;
#pragma unroll
                for (int w = 0; w < 8; w++) { gs += sPart[(w * 2 + tk) * 32 + c]; us += sPart[(w * 2 + tk) * 32 + 16 + c]; }
                const float gb = bf_round(gs), ub = bf_round(us);
                const float sl = bf_round(__fdividef(gb, 1.f + __expf(-gb)));
                sAct[tk * 16 + c] = bf_round(sl * ub);
            }
            bar_sync(1 + 8, 256);
            {
                float y00 = 0.f, y01 = 0.f, y10 = 0.f, y11 = 0.f;
#pragma unroll
                for (int k = 0; k < 16; k++) {
                    const float a0 = sAct[k], a1 = sAct[16 + k];
                    y00 = fmaf(a0, bf_lo(wd[k]), y00); y01 = fmaf(a0, bf_hi(wd[k]), y01);
                    y10 = fmaf(a1, bf_lo(wd[k]), y10); y11 = fmaf(a1, bf_hi(wd[k]), y11);
                }
                st_pkt(&gYPart[cta * 256 + t], embed_tag(y00, y01, y10, y11, tag));
            }
            if (t == 0) TS(9);
        }
        if (cta < 64) {
            const int pc = t & 3, part = t >> 2;
            const int opc = (t >> 2) & 3, oe = t & 3, otk = oe >> 1, ocol = (cta * 4 + opc) * 2 + (oe & 1);
            float y[4] = {0.f, 0.f, 0.f, 0.f};
            if (part < 56) {
                uint4 yv[2];
                wait_pkts4<2>(&gYPart[part * 256 + cta * 4 + pc], 56 * 256, tag, yv);
                y[0] = __uint_as_float(yv[0].x) + __uint_as_float(yv[1].x); y[1] = __uint_as_float(yv[0].y) + __uint_as_float(yv[1].y);
                y[2] = __uint_as_float(yv[0].z) + __uint_as_float(yv[1].z); y[3] = __uint_as_float(yv[0].w) + __uint_as_float(yv[1].w);
            }
            __syncwarp();
#pragma unroll
            for (int e = 0; e < 4; e++) {
                y[e] += __shfl_xor_sync(0xffffffffu, y[e], 4); y[e] += __shfl_xor_sync(0xffffffffu, y[e], 8); y[e] += __shfl_xor_sync(0xffffffffu, y[e], 16);
            }
            float* sR = sAct + 32;
            if (lane < 4) *reinterpret_cast<float4*>(&sR[(warp - 8) * 16 + lane * 4]) = make_float4(y[0], y[1], y[2], y[3]);
            bar_sync(1 + 8, 256);
            if (t < 16) {
                float s = 0.f;
#pragma unroll
                for (int w = 0; w < 8; w++) s += sR[w * 16 + t];
                const float yb = bf_round(bf_round(s) * ms.sel[otk * 4 + 2]);
                out[(size_t)(otk ? idx1 : idx0) * DM + ocol] = __float2bfloat16(sH[otk * 512 + ocol] + bf_round(sX[otk * 512 + ocol] + yb));
            }
            if (cta == 0 && t == 0) {
                *reinterpret_cast<volatile unsigned int*>(&gEpoch) = tag;
            }
            if (t == 0) TS(10);
        }
    }
}

typedef CUresult (*EncodeFn)(CUtensorMap*, CUtensorMapDataType, cuuint32_t, void*, const cuuint64_t*, const cuuint64_t*,
                             const cuuint32_t*, const cuuint32_t*, CUtensorMapInterleave, CUtensorMapSwizzle,
                             CUtensorMapL2promotion, CUtensorMapFloatOOBfill);

void make_map(EncodeFn enc, CUtensorMap* tm, const void* base, uint64_t cols, uint64_t rows, uint32_t box_c, uint32_t box_r, bool swz) {
    cuuint64_t dims[2] = {cols, rows};
    cuuint64_t strides[1] = {cols * 2};
    cuuint32_t box[2] = {box_c, box_r};
    cuuint32_t es[2] = {1, 1};
    enc(tm, CU_TENSOR_MAP_DATA_TYPE_BFLOAT16, 2, const_cast<void*>(base), dims, strides, box, es, CU_TENSOR_MAP_INTERLEAVE_NONE,
        swz ? CU_TENSOR_MAP_SWIZZLE_128B : CU_TENSOR_MAP_SWIZZLE_NONE, CU_TENSOR_MAP_L2_PROMOTION_L2_256B,
        CU_TENSOR_MAP_FLOAT_OOB_FILL_NONE);
}

}

extern "C" void kernel_launch(void* const* d_in, const int* in_sizes, int n_in, void* d_out, int out_size) {
    const __nv_bfloat16* x = (const __nv_bfloat16*)d_in[0];
    const __nv_bfloat16* wqkv = (const __nv_bfloat16*)d_in[1];
    const __nv_bfloat16* wo = (const __nv_bfloat16*)d_in[2];
    const __nv_bfloat16* w_r = (const __nv_bfloat16*)d_in[4];
    const __nv_bfloat16* w_gate = (const __nv_bfloat16*)d_in[5];
    const __nv_bfloat16* w_up = (const __nv_bfloat16*)d_in[6];
    const __nv_bfloat16* w_down = (const __nv_bfloat16*)d_in[7];
    __nv_bfloat16* out = (__nv_bfloat16*)d_out;

    static EncodeFn enc = nullptr;
    static void* pO = nullptr;
    if (!enc) {
        void* fn = nullptr;
        cudaDriverEntryPointQueryResult qr;
        cudaGetDriverEntryPoint("cuTensorMapEncodeTiled", &fn, cudaEnableDefault, &qr);
        enc = (EncodeFn)fn;
        cudaGetSymbolAddress(&pO, gO);
        cudaFuncSetAttribute(mega_kernel, cudaFuncAttributeMaxDynamicSharedMemorySize, SMEM_TOTAL);
    }
    CUtensorMap tmX, tmW, tmO, tmWo, tmG, tmU;
    make_map(enc, &tmX, x, DM, S_LEN, 64, 128, true);
    make_map(enc, &tmW, wqkv, 3 * DM, DM, 64, 64, true);
    make_map(enc, &tmO, pO, DM, S_LEN, 64, 64, true);
    make_map(enc, &tmWo, wo, DM, DM, 64, 64, true);
    make_map(enc, &tmG, w_gate, FF, DM, 16, 256, false);
    make_map(enc, &tmU, w_up, FF, DM, 16, 256, false);

    mega_kernel<<<128, 512, SMEM_TOTAL, cudaStreamPerThread>>>(tmX, tmW, tmO, tmWo, tmG, tmU, x, wqkv, wo, w_r, w_gate, w_up, w_down, out);
}
```

```cpp
#include <cuda_runtime.h>
#include <cuda_bf16.h>
#include <cuda.h>
#include <stdint.h>

namespace {

constexpr int S_LEN = 2048, DM = 512, NH = 32, DH = 16, FF = 1792;
constexpr int NFFN = FF / 16;
constexpr float LN_EPS = 1e-5f;
constexpr float QSCALE = 0.25f * 1.4426950408889634f;

__device__ __align__(1024) __nv_bfloat16 gQ[NH * S_LEN * DH];
__device__ __align__(1024) __nv_bfloat16 gKV[NH * S_LEN * DH * 2];
__device__ __align__(1024) __nv_bfloat16 gO[S_LEN * DM];
__device__ __align__(16) float gNorm[16 * NH * 4];
__device__ unsigned int gEpoch;
__device__ __align__(32) unsigned int gFlagQKV[128 * 8];
__device__ __align__(32) unsigned int gFlagO[32 * 32];
__device__ uint4 gStat1[S_LEN];
__device__ uint4 gCsPart[8 * 16 * 48];
__device__ uint4 gPart[32 * 64 * 4];
__device__ uint4 gCand[128 * 64];
__device__ __align__(32) unsigned int gFlagOut[128 * 8];
__device__ uint4 gCandRow[64 * 128];
__device__ uint4 gYPart[NFFN * 256];

#define TS(slot) do {} while (0)

__device__ __forceinline__ uint32_t smem_u32(const void* p) { return (uint32_t)__cvta_generic_to_shared(p); }
__device__ __forceinline__ void mbar_init(uint32_t bar, uint32_t cnt) {
    asm volatile("mbarrier.init.shared::cta.b64 [%0], %1;" ::"r"(bar), "r"(cnt));
}
__device__ __forceinline__ void mbar_expect_tx(uint32_t bar, uint32_t bytes) {
    asm volatile("mbarrier.arrive.expect_tx.shared::cta.b64 _, [%0], %1;" ::"r"(bar), "r"(bytes) : "memory");
}
__device__ __forceinline__ void mbar_arrive(uint32_t bar) {
    asm volatile("mbarrier.arrive.shared::cta.b64 _, [%0];" ::"r"(bar) : "memory");
}
constexpr int SPIN_LIMIT = 1 << 22;
#define BACKOFF() __nanosleep(32)
__device__ __forceinline__ void mbar_wait(uint32_t bar, uint32_t parity) {
    uint32_t done = 0;
    int it = 0;
    while (true) {
        asm volatile("{.reg .pred p; mbarrier.try_wait.parity.shared::cta.b64 p, [%1], %2; selp.u32 %0, 1, 0, p;}"
                     : "=r"(done) : "r"(bar), "r"(parity) : "memory");
        if (done) break;
        if (++it > SPIN_LIMIT) __trap();
    }
}
__device__ __forceinline__ void bulk_g2s(uint32_t dst, const void* src, uint32_t bytes, uint32_t bar) {
    asm volatile("cp.async.bulk.shared::cluster.global.mbarrier::complete_tx::bytes [%0], [%1], %2, [%3];"
                 ::"r"(dst), "l"(src), "r"(bytes), "r"(bar) : "memory");
}
__device__ __forceinline__ void bulk_prefetch_l2(const void* src, uint32_t bytes) {
    asm volatile("cp.async.bulk.prefetch.L2.global [%0], %1;" ::"l"(src), "r"(bytes) : "memory");
}
__device__ __forceinline__ void tma_2d(uint32_t dst, const CUtensorMap* tm, int c0, int c1, uint32_t bar) {
    asm volatile("cp.async.bulk.tensor.2d.shared::cluster.global.mbarrier::complete_tx::bytes [%0], [%1, {%3, %4}], [%2];"
                 ::"r"(dst), "l"(tm), "r"(bar), "r"(c0), "r"(c1) : "memory");
}
__device__ __forceinline__ void tma_store_2d(const CUtensorMap* tm, uint32_t src, int c0, int c1) {
    asm volatile("cp.async.bulk.tensor.2d.global.shared::cta.bulk_group [%0, {%2, %3}], [%1];" ::"l"(tm), "r"(src), "r"(c0), "r"(c1) : "memory");
    asm volatile("cp.async.bulk.commit_group;" ::: "memory");
}
__device__ __forceinline__ void fence_proxy_async_global() { asm volatile("fence.proxy.async.global;" ::: "memory"); }
__device__ __forceinline__ void fence_gpu() { asm volatile("fence.acq_rel.gpu;" ::: "memory"); }
__device__ __forceinline__ void bar_sync(int id, int n) { asm volatile("bar.sync %0, %1;" ::"r"(id), "r"(n) : "memory"); }
__device__ __forceinline__ void bar_arrive(int id, int n) { asm volatile("bar.arrive %0, %1;" ::"r"(id), "r"(n) : "memory"); }
__device__ __forceinline__ void st_flag(unsigned int* p, unsigned int v) {
    asm volatile("st.release.gpu.global.u32 [%0], %1;" ::"l"(p), "r"(v) : "memory");
}
__device__ __forceinline__ unsigned int ld_flag(const unsigned int* p) {
    unsigned int v;
    asm volatile("ld.relaxed.gpu.global.u32 %0, [%1];" : "=r"(v) : "l"(p) : "memory");
    return v;
}
__device__ __forceinline__ void wait_flag(const unsigned int* p, unsigned int tag) {
    int it = 0;
    while (ld_flag(p) != tag) {
        if (++it > SPIN_LIMIT) __trap();
        BACKOFF();
    }
}
__device__ __forceinline__ void st_pkt(uint4* p, uint4 v) {
    asm volatile("st.relaxed.gpu.global.v4.u32 [%0], {%1,%2,%3,%4};" ::"l"(p), "r"(v.x), "r"(v.y), "r"(v.z), "r"(v.w) : "memory");
}
__device__ __forceinline__ uint4 ld_pkt(const uint4* p) {
    uint4 v;
    asm volatile("ld.relaxed.gpu.global.v4.u32 {%0,%1,%2,%3}, [%4];" : "=r"(v.x), "=r"(v.y), "=r"(v.z), "=r"(v.w) : "l"(p) : "memory");
    return v;
}
template <int N, unsigned int MASK>
__device__ __forceinline__ void wait_pkts(const uint4* p, int stride, unsigned int tag, uint4 (&v)[N]) {
    int it = 0;
    while (true) {
        bool ok = true;
#pragma unroll
        for (int i = 0; i < N; i++) v[i] = ld_pkt(p + (size_t)i * stride);
#pragma unroll
        for (int i = 0; i < N; i++) ok = ok && ((v[i].w & MASK) == tag);
        if (ok) break;
        if (++it > SPIN_LIMIT) __trap();
        BACKOFF();
    }
}
__device__ __forceinline__ uint4 embed_tag(float a, float b, float c, float d, unsigned int tag) {
    return make_uint4((__float_as_uint(a) & ~15u) | (tag & 15u), (__float_as_uint(b) & ~15u) | ((tag >> 4) & 15u),
                      (__float_as_uint(c) & ~15u) | ((tag >> 8) & 15u), (__float_as_uint(d) & ~15u) | ((tag >> 12) & 15u));
}
template <int N>
__device__ __forceinline__ void wait_pkts4(const uint4* p, int stride, unsigned int tag, uint4 (&v)[N]) {
    const unsigned int t16 = tag & 0xffffu;
    int it = 0;
    while (true) {
        bool ok = true;
#pragma unroll
        for (int i = 0; i < N; i++) v[i] = ld_pkt(p + (size_t)i * stride);
#pragma unroll
        for (int i = 0; i < N; i++)
            ok = ok && (((v[i].x & 15u) | ((v[i].y & 15u) << 4) | ((v[i].z & 15u) << 8) | ((v[i].w & 15u) << 12)) == t16);
        if (ok) break;
        if (++it > SPIN_LIMIT) __trap();
        BACKOFF();
    }
}
__device__ __forceinline__ uint64_t make_desc(uint32_t addr, uint32_t lbo, uint32_t sbo, uint32_t mode) {
    return (uint64_t)((addr & 0x3FFFF) >> 4) | ((uint64_t)((lbo & 0x3FFFF) >> 4) << 16) |
           ((uint64_t)((sbo & 0x3FFFF) >> 4) << 32) | ((uint64_t)mode << 62);
}
__device__ __forceinline__ void wg_fence() { asm volatile("wgmma.fence.sync.aligned;" ::: "memory"); }
__device__ __forceinline__ void wg_commit() { asm volatile("wgmma.commit_group.sync.aligned;" ::: "memory"); }
template <int N> __device__ __forceinline__ void wg_wait() { asm volatile("wgmma.wait_group.sync.aligned %0;" ::"n"(N) : "memory"); }
template <int N> __device__ __forceinline__ void pin(float (&d)[N]) {
#pragma unroll
    for (int i = 0; i < N; i++) asm volatile("" : "+f"(d[i])::"memory");
}
__device__ __forceinline__ uint32_t pack_bf16(float lo, float hi) {
    uint32_t r;
    asm("cvt.rn.bf16x2.f32 %0, %1, %2;" : "=r"(r) : "f"(hi), "f"(lo));
    return r;
}
__device__ __forceinline__ float bf_lo(uint32_t v) { return __uint_as_float(v << 16); }
__device__ __forceinline__ float bf_hi(uint32_t v) { return __uint_as_float(v & 0xFFFF0000u); }
__device__ __forceinline__ float bf_round(float v) { return __bfloat162float(__float2bfloat16(v)); }
__device__ __forceinline__ float ex2_mufu(float x) {
    float y;
    asm("ex2.approx.ftz.f32 %0, %1;" : "=f"(y) : "f"(x));
    return y;
}

#define ACC8(d, o) "+f"(d[o + 0]), "+f"(d[o + 1]), "+f"(d[o + 2]), "+f"(d[o + 3]), "+f"(d[o + 4]), "+f"(d[o + 5]), "+f"(d[o + 6]), "+f"(d[o + 7])
#define OUT8(d, o) "=f"(d[o + 0]), "=f"(d[o + 1]), "=f"(d[o + 2]), "=f"(d[o + 3]), "=f"(d[o + 4]), "=f"(d[o + 5]), "=f"(d[o + 6]), "=f"(d[o + 7])

__device__ __forceinline__ void wgmma_n192(float (&d)[96], uint64_t da, uint64_t db) {
    asm volatile(
        "wgmma.mma_async.sync.aligned.m64n192k16.f32.bf16.bf16 "
        "{%0,%1,%2,%3,%4,%5,%6,%7,%8,%9,%10,%11,%12,%13,%14,%15,%16,%17,%18,%19,%20,%21,%22,%23,%24,%25,%26,%27,%28,%29,%30,%31,"
        "%32,%33,%34,%35,%36,%37,%38,%39,%40,%41,%42,%43,%44,%45,%46,%47,%48,%49,%50,%51,%52,%53,%54,%55,%56,%57,%58,%59,%60,%61,%62,%63,"
        "%64,%65,%66,%67,%68,%69,%70,%71,%72,%73,%74,%75,%76,%77,%78,%79,%80,%81,%82,%83,%84,%85,%86,%87,%88,%89,%90,%91,%92,%93,%94,%95},"
        "%96, %97, 1, 1, 1, 0, 1;"
        : ACC8(d, 0), ACC8(d, 8), ACC8(d, 16), ACC8(d, 24), ACC8(d, 32), ACC8(d, 40), ACC8(d, 48), ACC8(d, 56),
          ACC8(d, 64), ACC8(d, 72), ACC8(d, 80), ACC8(d, 88)
        : "l"(da), "l"(db));
}
__device__ __forceinline__ void wgmma_n192_rs(float (&d)[96], const uint32_t* a, uint64_t db) {
    asm volatile(
        "wgmma.mma_async.sync.aligned.m64n192k16.f32.bf16.bf16 "
        "{%0,%1,%2,%3,%4,%5,%6,%7,%8,%9,%10,%11,%12,%13,%14,%15,%16,%17,%18,%19,%20,%21,%22,%23,%24,%25,%26,%27,%28,%29,%30,%31,"
        "%32,%33,%34,%35,%36,%37,%38,%39,%40,%41,%42,%43,%44,%45,%46,%47,%48,%49,%50,%51,%52,%53,%54,%55,%56,%57,%58,%59,%60,%61,%62,%63,"
        "%64,%65,%66,%67,%68,%69,%70,%71,%72,%73,%74,%75,%76,%77,%78,%79,%80,%81,%82,%83,%84,%85,%86,%87,%88,%89,%90,%91,%92,%93,%94,%95},"
        "{%96,%97,%98,%99}, %100, 1, 1, 1, 1;"
        : ACC8(d, 0), ACC8(d, 8), ACC8(d, 16), ACC8(d, 24), ACC8(d, 32), ACC8(d, 40), ACC8(d, 48), ACC8(d, 56),
          ACC8(d, 64), ACC8(d, 72), ACC8(d, 80), ACC8(d, 88)
        : "r"(a[0]), "r"(a[1]), "r"(a[2]), "r"(a[3]), "l"(db));
}
__device__ __forceinline__ void ldsm_x4(uint32_t* r, uint32_t addr) {
    asm volatile("ldmatrix.sync.aligned.m8n8.x4.shared.b16 {%0,%1,%2,%3}, [%4];"
                 : "=r"(r[0]), "=r"(r[1]), "=r"(r[2]), "=r"(r[3]) : "r"(addr) : "memory");
}
__device__ __forceinline__ void wgmma_n64(float (&d)[32], uint64_t da, uint64_t db) {
    asm volatile(
        "wgmma.mma_async.sync.aligned.m64n64k16.f32.bf16.bf16 "
        "{%0,%1,%2,%3,%4,%5,%6,%7,%8,%9,%10,%11,%12,%13,%14,%15,%16,%17,%18,%19,%20,%21,%22,%23,%24,%25,%26,%27,%28,%29,%30,%31},"
        "%32, %33, 1, 1, 1, 0, 1;"
        : ACC8(d, 0), ACC8(d, 8), ACC8(d, 16), ACC8(d, 24)
        : "l"(da), "l"(db));
}
__device__ __forceinline__ void wgmma_qk128(float (&d)[64], const uint32_t (&a)[4], uint64_t desc) {
    asm volatile(
        "wgmma.mma_async.sync.aligned.m64n128k16.f32.bf16.bf16 "
        "{%0,%1,%2,%3,%4,%5,%6,%7,%8,%9,%10,%11,%12,%13,%14,%15,%16,%17,%18,%19,%20,%21,%22,%23,%24,%25,%26,%27,%28,%29,%30,%31,"
        "%32,%33,%34,%35,%36,%37,%38,%39,%40,%41,%42,%43,%44,%45,%46,%47,%48,%49,%50,%51,%52,%53,%54,%55,%56,%57,%58,%59,%60,%61,%62,%63},"
        "{%64,%65,%66,%67}, %68, 0, 1, 1, 0;"
        : OUT8(d, 0), OUT8(d, 8), OUT8(d, 16), OUT8(d, 24), OUT8(d, 32), OUT8(d, 40), OUT8(d, 48), OUT8(d, 56)
        : "r"(a[0]), "r"(a[1]), "r"(a[2]), "r"(a[3]), "l"(desc));
}
__device__ __forceinline__ void wgmma_pv24(float (&o)[12], uint32_t a0, uint32_t a1, uint32_t a2, uint32_t a3, uint64_t desc) {
    asm volatile(
        "wgmma.mma_async.sync.aligned.m64n24k16.f32.bf16.bf16 "
        "{%0,%1,%2,%3,%4,%5,%6,%7,%8,%9,%10,%11}, {%12,%13,%14,%15}, %16, 1, 1, 1, 1;"
        : ACC8(o, 0), "+f"(o[8]), "+f"(o[9]), "+f"(o[10]), "+f"(o[11])
        : "r"(a0), "r"(a1), "r"(a2), "r"(a3), "l"(desc));
}

__device__ __forceinline__ uint32_t ex2_pair_poly(float x0, float x1) {
    const float M = 12288.0f + 31.0f;
    float t0 = x0 + M, t1 = x1 + M;
    uint32_t G = __byte_perm(__float_as_uint(t0), __float_as_uint(t1), 0x5410);
    uint32_t W, q;
    asm("lop3.b32 %0, %1, %2, %3, 0xEA;" : "=r"(W) : "r"(G), "r"(0x03FF03FFu), "r"(0x3C003C00u));
    asm("fma.rn.f16x2 %0, %1, %2, %3;" : "=r"(q) : "r"(0x15121512u), "r"(W), "r"(0x8acc8accu));
    asm("fma.rn.f16x2 %0, %1, %2, %3;" : "=r"(q) : "r"(q), "r"(W), "r"(0x1fc21fc2u));
    asm("fma.rn.f16x2 %0, %1, %2, %3;" : "=r"(q) : "r"(q), "r"(W), "r"(0x2f732f73u));
    return ((G & 0xFC00FC00u) >> 3) + q;
}
#define NPP 18
__device__ __forceinline__ constexpr bool use_poly_pair(int i) { return ((i % 32 + 1) * NPP) / 32 != ((i % 32) * NPP) / 32; }
__device__ __forceinline__ uint32_t ex2_pair(float x0, float x1, int i) {
    return use_poly_pair(i) ? ex2_pair_poly(x0, x1) : pack_bf16(ex2_mufu(x0), ex2_mufu(x1));
}
__device__ __forceinline__ unsigned int f2ord(float v) {
    const unsigned int u = __float_as_uint(v);
    const unsigned int o = u ^ ((unsigned int)((int)u >> 31) | 0x80000000u);
    return (v == v) ? o : 0u;
}
__device__ __forceinline__ void warp_top2(unsigned int ka, unsigned int ia, unsigned int kb, unsigned int ib, unsigned int& i1, unsigned int& i2) {
    const unsigned int m1 = __reduce_max_sync(0xffffffffu, max(ka, kb));
    i1 = __reduce_min_sync(0xffffffffu, min(ka == m1 ? ia : 0xffffffffu, kb == m1 ? ib : 0xffffffffu));
    const bool ra = (ia == i1), rb = (ib == i1);
    const unsigned int ka2 = ra ? 0u : ka, kb2 = rb ? 0u : kb, ia2 = ra ? 0xffffffffu : ia, ib2 = rb ? 0xffffffffu : ib;
    const unsigned int m2 = __reduce_max_sync(0xffffffffu, max(ka2, kb2));
    i2 = __reduce_min_sync(0xffffffffu, min(ka2 == m2 ? ia2 : 0xffffffffu, kb2 == m2 ? ib2 : 0xffffffffu));
}

constexpr int P1_STAGES = 5;
constexpr int P1_STAGE_BYTES = 16384 + 24576;
constexpr int KV_CHUNK = 10240;
constexpr int SM_A3 = 163840;
constexpr int SM_MISC = 229376;
constexpr int SMEM_TOTAL = 232448;
struct Misc {
    uint64_t p1_full[P1_STAGES], p1_empty[P1_STAGES];
    uint64_t kv[16];
    uint64_t wo[8], a3[8], moe;
    unsigned int tag;
    int fast;
    int idx[2], cslot[2];
    alignas(16) float sel[8];
    unsigned int norm[12];
    unsigned int freed[16];
    union alignas(16) {
        struct { float mu[128], rs[128], cs[192]; } p1;
        struct { float part[2][64][3]; float mu[64], rs[64], r[64]; } p3;
    };
};
static_assert(sizeof(Misc) <= SMEM_TOTAL - SM_MISC, "misc smem");

__global__ void __launch_bounds__(512, 1)
mega_kernel(const __grid_constant__ CUtensorMap tmX, const __grid_constant__ CUtensorMap tmW,
            const __grid_constant__ CUtensorMap tmO, const __grid_constant__ CUtensorMap tmWo,
            const __grid_constant__ CUtensorMap tmG, const __grid_constant__ CUtensorMap tmU, const __grid_constant__ CUtensorMap tmOut,
            const __nv_bfloat16* __restrict__ x, const __nv_bfloat16* __restrict__ wqkv, const __nv_bfloat16* __restrict__ wo,
            const __nv_bfloat16* __restrict__ w_r, const __nv_bfloat16* __restrict__ w_gate,
            const __nv_bfloat16* __restrict__ w_up, const __nv_bfloat16* __restrict__ w_down,
            __nv_bfloat16* __restrict__ out) {
    extern __shared__ __align__(1024) char smem[];
    Misc& ms = *reinterpret_cast<Misc*>(smem + SM_MISC);
    const int tid = threadIdx.x, lane = tid & 31;
    const int warp = __shfl_sync(0xffffffffu, tid >> 5, 0);
    const int wg = warp >> 2, w4 = warp & 3, g = lane >> 2, t4 = lane & 3;
    const int cta = blockIdx.x;
    const int rb = cta >> 3, hg = cta & 7;

    if (warp == 12) {
        if (lane == 0) {
            TS(0);
            if (smem_u32(smem) & 1023) __trap();
            for (int i = 0; i < P1_STAGES; i++) { mbar_init(smem_u32(&ms.p1_full[i]), 1); mbar_init(smem_u32(&ms.p1_empty[i]), 8); }
            asm volatile("fence.mbarrier_init.release.cluster;" ::: "memory");
        }
        __syncwarp();
        bar_arrive(13, 288);
        bar_arrive(14, 256);
    } else {
        if (tid == 32) {
            for (int i = 0; i < 16; i++) mbar_init(smem_u32(&ms.kv[i]), 1);
            for (int i = 0; i < 8; i++) { mbar_init(smem_u32(&ms.wo[i]), 2); mbar_init(smem_u32(&ms.a3[i]), 1); }
            mbar_init(smem_u32(&ms.moe), 16);
            for (int i = 0; i < 16; i++) ms.freed[i] = 0;
            asm volatile("fence.mbarrier_init.release.cluster;" ::: "memory");
        }
        if (tid >= 64 && tid < 76) ms.norm[tid - 64] = 0;
        if (tid >= 96 && tid < 101) {
            const CUtensorMap* tm = tid == 96 ? &tmO : tid == 97 ? &tmWo : tid == 98 ? &tmG : tid == 99 ? &tmU : &tmOut;
            asm volatile("prefetch.tensormap [%0];" ::"l"(tm) : "memory");
        }
        if (tid == 416) ms.tag = __ldcg(&gEpoch) + 1u;
    }

    if (wg < 2) {
        float acc[96];
#pragma unroll
        for (int i = 0; i < 96; i++) acc[i] = 0.f;
        bar_sync(13, 288);
#pragma unroll 1
        for (int kc = 0; kc < 8; kc++) {
            const int s = kc % P1_STAGES;
            mbar_wait(smem_u32(&ms.p1_full[s]), (kc / P1_STAGES) & 1);
            if (tid == 0) TS(24 + kc);
            const uint32_t sa = smem_u32(smem + s * P1_STAGE_BYTES), sb = sa + 16384;
            const uint64_t da = make_desc(sa + wg * 8192, 16, 1024, 1);
            const uint64_t db = make_desc(sb, 8192, 1024, 1);
            wg_fence();
#pragma unroll
            for (int ks = 0; ks < 4; ks++) wgmma_n192(acc, da + ks * 2, db + ks * 128);
            wg_commit();
            wg_wait<0>();
            if (lane == 0) mbar_arrive(smem_u32(&ms.p1_empty[s]));
        }
        pin(acc);
        if (tid == 0) TS(1);
        bar_sync(1, 480);
        const unsigned int tag = ms.tag;
        if (tid == 0) TS(16);
        const int lr0 = wg * 64 + w4 * 16 + g, lr1 = lr0 + 8;
        const float mu0 = ms.p1.mu[lr0], mu1 = ms.p1.mu[lr1], rs0 = ms.p1.rs[lr0], rs1 = ms.p1.rs[lr1];
        const int lg0 = wg * 8 + w4 * 2;
        const int rg0 = rb * 16 + lg0;
#pragma unroll
        for (int hh = 0; hh < 4; hh++) {
            const int head = hg * 4 + hh;
            float nrm[3];
#pragma unroll
            for (int sec = 0; sec < 3; sec++) {
                float sq0 = 0.f, sq1 = 0.f, vm = 0.f;
#pragma unroll
                for (int db = 0; db < 2; db++) {
                    const int j = sec * 8 + hh * 2 + db;
                    const float2 c = *reinterpret_cast<const float2*>(&ms.p1.cs[j * 8 + 2 * t4]);
                    const float f0 = sec == 0 ? rs0 * QSCALE : rs0, f1 = sec == 0 ? rs1 * QSCALE : rs1;
                    const float a0 = (acc[4 * j + 0] - mu0 * c.x) * f0, a1 = (acc[4 * j + 1] - mu0 * c.y) * f0;
                    const float b0 = (acc[4 * j + 2] - mu1 * c.x) * f1, b1 = (acc[4 * j + 3] - mu1 * c.y) * f1;
                    const uint32_t pa = pack_bf16(a0, a1), pb = pack_bf16(b0, b1);
                    if (sec < 2) {
                        uint32_t* dst = sec == 0 ? reinterpret_cast<uint32_t*>(gQ) + ((size_t)head * S_LEN * DH + rg0 * 128) / 2
                                                 : reinterpret_cast<uint32_t*>(gKV) + (size_t)(head * 16 + rb) * 2048 + lg0 * 64;
                        dst[db * 32 + lane] = pa;
                        dst[64 + db * 32 + lane] = pb;
                        sq0 = fmaf(a0, a0, fmaf(a1, a1, sq0));
                        sq1 = fmaf(b0, b0, fmaf(b1, b1, sq1));
                    } else {
                        uint32_t* dst = reinterpret_cast<uint32_t*>(gKV) + (size_t)(head * 16 + rb) * 2048 + 1024 + db * 512 + lg0 * 32;
                        dst[lane] = pa;
                        dst[32 + lane] = pb;
                        vm = fmaxf(vm, fmaxf(fmaxf(fabsf(a0), fabsf(a1)), fmaxf(fabsf(b0), fabsf(b1))));
                        if (!(a0 + a1 + b0 + b1 == a0 + a1 + b0 + b1)) vm = __int_as_float(0x7f800000);
                    }
                }
                if (sec < 2) {
                    sq0 += __shfl_xor_sync(0xffffffffu, sq0, 1); sq0 += __shfl_xor_sync(0xffffffffu, sq0, 2);
                    sq1 += __shfl_xor_sync(0xffffffffu, sq1, 1); sq1 += __shfl_xor_sync(0xffffffffu, sq1, 2);
                    vm = fmaxf(sq0, sq1);
                    if (!(sq0 + sq1 < 3.0e38f)) vm = __int_as_float(0x7f800000);
                }
                nrm[sec] = vm;
            }
            const unsigned int a = __reduce_max_sync(0xffffffffu, __float_as_uint(nrm[0]));
            const unsigned int b = __reduce_max_sync(0xffffffffu, __float_as_uint(nrm[1]));
            const unsigned int c = __reduce_max_sync(0xffffffffu, __float_as_uint(nrm[2]));
            if (lane == 0) { atomicMax(&ms.norm[hh * 3 + 0], a); atomicMax(&ms.norm[hh * 3 + 1], b); atomicMax(&ms.norm[hh * 3 + 2], c); }
        }
        if (tid == 0) TS(17);
        bar_sync(2, 256);
        if (tid == 0) TS(18);
        if (tid < 12) gNorm[(rb * NH + hg * 4 + tid / 3) * 4 + tid % 3] = __uint_as_float(ms.norm[tid]);
        __syncwarp();
        if (tid == 0) { st_flag(&gFlagQKV[(hg * 16 + rb) * 8], tag); TS(2); }
    } else if (wg == 2) {
        const int t = tid - 256;
        if (t < 2) reinterpret_cast<uint4*>(gFlagQKV)[(hg * 16 + rb) * 2 + t] = make_uint4(0u, 0u, 0u, 0u);
        bar_sync(14, 256);
        mbar_wait(smem_u32(&ms.p1_full[0]), 0);
        {
            const int row = rb * 128 + hg * 16 + (t >> 3), j = t & 7;
            const uint4* xp = reinterpret_cast<const uint4*>(x + (size_t)row * DM);
            uint4 v[8];
#pragma unroll
            for (int i = 0; i < 8; i++) v[i] = __ldg(xp + i * 8 + j);
            float s1 = 0.f;
#pragma unroll
            for (int i = 0; i < 8; i++) {
                const uint32_t w[4] = {v[i].x, v[i].y, v[i].z, v[i].w};
#pragma unroll
                for (int e = 0; e < 4; e++) s1 += bf_lo(w[e]) + bf_hi(w[e]);
            }
            s1 += __shfl_xor_sync(0xffffffffu, s1, 1); s1 += __shfl_xor_sync(0xffffffffu, s1, 2); s1 += __shfl_xor_sync(0xffffffffu, s1, 4);
            const float mu = s1 * (1.f / DM);
            float s2 = 0.f;
#pragma unroll
            for (int i = 0; i < 8; i++) {
                const uint32_t w[4] = {v[i].x, v[i].y, v[i].z, v[i].w};
#pragma unroll
                for (int e = 0; e < 4; e++) {
                    const float a = bf_lo(w[e]) - mu, b = bf_hi(w[e]) - mu;
                    s2 = fmaf(a, a, fmaf(b, b, s2));
                }
            }
            s2 += __shfl_xor_sync(0xffffffffu, s2, 1); s2 += __shfl_xor_sync(0xffffffffu, s2, 2); s2 += __shfl_xor_sync(0xffffffffu, s2, 4);
            bar_sync(11, 224);
            if (j == 0) st_pkt(&gStat1[row], make_uint4(__float_as_uint(mu), __float_as_uint(rsqrtf(s2 * (1.f / DM) + LN_EPS)), 0u, ms.tag));
        }
        const unsigned int tag = ms.tag;
        if (t == 0) TS(32);
        uint4 st[1];
        if (t < 8) wait_pkts<1, 0xffffffffu>(&gStat1[rb * 128 + t * 16 + 15], 0, tag, st);
        bar_sync(12, 128);
        wait_pkts<1, 0xffffffffu>(&gStat1[rb * 128 + t], 0, tag, st);
        if (t == 0) TS(34);
        ms.p1.mu[t] = __uint_as_float(st[0].x);
        ms.p1.rs[t] = __uint_as_float(st[0].y);
        bar_arrive(1, 480);
        {
            const uint4 z = make_uint4(0u, 0u, 0u, 0u);
            if (t < 64) { gCand[cta * 64 + t] = z; gPart[cta * 64 + t] = z; gCandRow[cta * 64 + t] = z; }
            gYPart[cta * 224 + t] = z;
            if (t < 96) gYPart[cta * 224 + 128 + t] = z;
            if (t < 2) {
                reinterpret_cast<uint4*>(gFlagO)[cta * 2 + t] = z;
                reinterpret_cast<uint4*>(gFlagOut)[cta * 2 + t] = z;
            }
        }
    } else {
      if (warp == 12) {
        if (lane == 0) {
#pragma unroll 1
            for (int kc = 0; kc < 8; kc++) {
                const int s = kc % P1_STAGES;
                if (kc >= P1_STAGES) mbar_wait(smem_u32(&ms.p1_empty[s]), 0);
                const uint32_t bar = smem_u32(&ms.p1_full[s]);
                const uint32_t sa = smem_u32(smem + s * P1_STAGE_BYTES), sb = sa + 16384;
                mbar_expect_tx(bar, P1_STAGE_BYTES);
                tma_2d(sa, &tmX, kc * 64, rb * 128, bar);
#pragma unroll
                for (int p = 0; p < 3; p++) tma_2d(sb + p * 8192, &tmW, p * 512 + hg * 64, kc * 64, bar);
            }
        }
      } else {
        const int t = tid - 416;
        bar_sync(14, 256);
        mbar_wait(smem_u32(&ms.p1_full[0]), 0);
        const int c16 = t >> 2, rs = t & 3;
        const __nv_bfloat16* wp = wqkv + (size_t)(rb * 32 + rs) * (3 * DM) + (c16 >> 3) * 512 + hg * 64 + (c16 & 7) * 8;
        uint4 v[8];
#pragma unroll
        for (int i = 0; i < 8; i++) v[i] = __ldg(reinterpret_cast<const uint4*>(wp + (size_t)i * 4 * (3 * DM)));
        float a[8] = {};
#pragma unroll
        for (int i = 0; i < 8; i++) {
            a[0] += bf_lo(v[i].x); a[1] += bf_hi(v[i].x); a[2] += bf_lo(v[i].y); a[3] += bf_hi(v[i].y);
            a[4] += bf_lo(v[i].z); a[5] += bf_hi(v[i].z); a[6] += bf_lo(v[i].w); a[7] += bf_hi(v[i].w);
        }
#pragma unroll
        for (int e = 0; e < 8; e++) { a[e] += __shfl_xor_sync(0xffffffffu, a[e], 1); a[e] += __shfl_xor_sync(0xffffffffu, a[e], 2); }
        bar_sync(11, 224);
        const unsigned int tag = ms.tag;
        const int pk = c16 * 2 + rs;
        if (rs < 2) st_pkt(&gCsPart[(hg * 16 + rb) * 48 + pk], embed_tag(rs ? a[4] : a[0], rs ? a[5] : a[1], rs ? a[6] : a[2], rs ? a[7] : a[3], tag));
        if (t == 0) TS(35);
        if (t < 16) { uint4 gate[1]; wait_pkts4<1>(&gCsPart[(hg * 16 + t) * 48 + 47], 0, tag, gate); }
        bar_sync(8, 96);
        if (t == 0) TS(36);
        if (rs < 2) {
            uint4 p[16];
            wait_pkts4<16>(&gCsPart[hg * 16 * 48 + pk], 48, tag, p);
            float s0 = 0.f, s1 = 0.f, s2 = 0.f, s3 = 0.f;
#pragma unroll
            for (int i = 0; i < 16; i++) {
                s0 += __uint_as_float(p[i].x); s1 += __uint_as_float(p[i].y); s2 += __uint_as_float(p[i].z); s3 += __uint_as_float(p[i].w);
            }
            *reinterpret_cast<float4*>(&ms.p1.cs[pk * 4]) = make_float4(s0, s1, s2, s3);
            if (t == 0) TS(37);
        }
        __syncwarp();
        bar_arrive(1, 480);
      }
    }
    __syncthreads();
    if (tid == 0) TS(20);
    const unsigned int tag = ms.tag;

    const int head = hg * 4 + (rb >> 2), quarter = rb & 3;
    {
        const uint4 one = make_uint4(0x00003F80u, 0, 0, 0);
#pragma unroll
        for (int i = 0; i < 4; i++) {
            const int e = tid + i * 512;
            *reinterpret_cast<uint4*>(smem + (e >> 7) * KV_CHUNK + 8192 + (e & 127) * 16) = one;
        }
        asm volatile("fence.proxy.async.shared::cta;" ::: "memory");
    }
    if (warp == 0) {
        if (lane < 16) wait_flag(&gFlagQKV[(hg * 16 + lane) * 8], tag);
        __syncwarp();
        if (lane == 0) TS(21);
    }
    __syncthreads();
    if (lane == 0) {
        fence_proxy_async_global();
        const uint32_t bar = smem_u32(&ms.kv[warp]);
        mbar_expect_tx(bar, 8192);
        bulk_g2s(smem_u32(smem + warp * KV_CHUNK), reinterpret_cast<const char*>(gKV) + (size_t)(head * 16 + warp) * 8192, 8192, bar);
    }
    if (warp == 0) {
        const float4 n = __ldcg(reinterpret_cast<const float4*>(&gNorm[((lane & 15) * NH + head) * 4]));
        const float q2 = __uint_as_float(__reduce_max_sync(0xffffffffu, __float_as_uint(n.x)));
        const float k2 = __uint_as_float(__reduce_max_sync(0xffffffffu, __float_as_uint(n.y)));
        const float vm = __uint_as_float(__reduce_max_sync(0xffffffffu, __float_as_uint(n.z)));
        if (lane == 0) ms.fast = (q2 * k2 * 1.04f <= 841.f) && (vm <= 1.0e18f) && (vm >= 1.0e-18f || vm == 0.f);
    }
    __syncthreads();
    if (tid == 0) TS(3);
    {
        const bool fast = ms.fast != 0;
        const uint64_t descK0 = make_desc(smem_u32(smem), 128, 256, 0);
        const uint64_t descV0 = make_desc(smem_u32(smem + 4096), 128, 2048, 0);
        auto release_chunk = [&](int j) {
            if (lane == 0) {
                unsigned int old;
                asm volatile("atom.acq_rel.cta.shared.add.u32 %0, [%1], 1;" : "=r"(old) : "r"(smem_u32(&ms.freed[j])) : "memory");
                if (old == 15) {
                    const uint32_t dst = smem_u32(smem + j * KV_CHUNK);
                    const uint32_t wb = smem_u32(&ms.wo[j >> 1]);
                    mbar_expect_tx(wb, 8192);
                    tma_2d(dst, &tmWo, (cta & 3) * 128 + (j & 1) * 64, (j >> 1) * 64, wb);
                    const uint32_t mb = smem_u32(&ms.moe);
                    if (cta < NFFN) {
                        mbar_expect_tx(mb, 2048);
                        tma_2d(dst + 8192, (j & 8) ? &tmU : &tmG, cta * 16, (j & 7) * 64, mb);
                    }
                }
            }
            __syncwarp();
        };
#pragma unroll 1
        for (int pass = 0; pass < 2; pass++) {
            const int tile = pass * 16 + quarter * 4 + wg;
            const int row0 = tile * 64 + w4 * 16;
            uint32_t q[4];
            {
                const uint32_t* Qp = reinterpret_cast<const uint32_t*>(gQ) + ((size_t)head * S_LEN * DH + (row0 >> 3) * 128) / 2;
                q[0] = __ldcg(Qp + lane); q[2] = __ldcg(Qp + 32 + lane);
                q[1] = __ldcg(Qp + 64 + lane); q[3] = __ldcg(Qp + 96 + lane);
            }
            float o[12];
#pragma unroll
            for (int i = 0; i < 12; i++) o[i] = 0.f;
            if (fast) {
#pragma unroll 1
                for (int j = 0; j < 16; j++) {
                    if (pass == 0) mbar_wait(smem_u32(&ms.kv[j]), 0);
                    float s[64];
                    wg_fence();
                    wgmma_qk128(s, q, descK0 + (uint64_t)(j * (KV_CHUNK >> 4)));
                    wg_commit();
                    wg_wait<0>();
                    pin(s);
                    if (pass == 1 && j > 0) release_chunk(j - 1);
#pragma unroll
                    for (int k = 0; k < 8; k++) {
                        uint32_t p[4];
#pragma unroll
                        for (int i = 0; i < 4; i++) p[i] = ex2_pair(s[8 * k + 2 * i], s[8 * k + 2 * i + 1], 4 * k + i);
                        wg_fence();
                        wgmma_pv24(o, p[0], p[1], p[2], p[3], descV0 + (uint64_t)(j * (KV_CHUNK >> 4) + k * 16));
                        wg_commit();
                        wg_wait<2>();
                    }
                }
            } else {
                float m0 = -INFINITY, m1 = -INFINITY;
#pragma unroll 1
                for (int j = 0; j < 16; j++) {
                    if (pass == 0) mbar_wait(smem_u32(&ms.kv[j]), 0);
                    float s[64];
                    wg_fence();
                    wgmma_qk128(s, q, descK0 + (uint64_t)(j * (KV_CHUNK >> 4)));
                    wg_commit();
                    wg_wait<0>();
                    pin(s);
                    pin(o);
                    if (pass == 1 && j > 0) release_chunk(j - 1);
                    float n0 = m0, n1 = m1;
#pragma unroll
                    for (int i = 0; i < 16; i++) {
                        n0 = fmaxf(n0, fmaxf(s[4 * i], s[4 * i + 1]));
                        n1 = fmaxf(n1, fmaxf(s[4 * i + 2], s[4 * i + 3]));
                    }
                    n0 = fmaxf(n0, __shfl_xor_sync(0xffffffffu, n0, 1)); n0 = fmaxf(n0, __shfl_xor_sync(0xffffffffu, n0, 2));
                    n1 = fmaxf(n1, __shfl_xor_sync(0xffffffffu, n1, 1)); n1 = fmaxf(n1, __shfl_xor_sync(0xffffffffu, n1, 2));
                    const float a0 = ex2_mufu(m0 - n0), a1 = ex2_mufu(m1 - n1);
                    m0 = n0; m1 = n1;
#pragma unroll
                    for (int i = 0; i < 3; i++) { o[4 * i] *= a0; o[4 * i + 1] *= a0; o[4 * i + 2] *= a1; o[4 * i + 3] *= a1; }
#pragma unroll
                    for (int k = 0; k < 8; k++) {
                        const uint32_t p0 = pack_bf16(ex2_mufu(s[8 * k] - n0), ex2_mufu(s[8 * k + 1] - n0));
                        const uint32_t p1 = pack_bf16(ex2_mufu(s[8 * k + 2] - n1), ex2_mufu(s[8 * k + 3] - n1));
                        const uint32_t p2 = pack_bf16(ex2_mufu(s[8 * k + 4] - n0), ex2_mufu(s[8 * k + 5] - n0));
                        const uint32_t p3 = pack_bf16(ex2_mufu(s[8 * k + 6] - n1), ex2_mufu(s[8 * k + 7] - n1));
                        wg_fence();
                        wgmma_pv24(o, p0, p1, p2, p3, descV0 + (uint64_t)(j * (KV_CHUNK >> 4) + k * 16));
                        wg_commit();
                        wg_wait<2>();
                    }
                    wg_wait<0>();
                }
            }
            wg_wait<0>();
            pin(o);
            if (pass == 1) release_chunk(15);
            if (pass == 0 && tid == 511) {
                bulk_prefetch_l2(reinterpret_cast<const char*>(wo) + cta * 4096, 4096);
                bulk_prefetch_l2(reinterpret_cast<const char*>(w_gate) + cta * 14336, 14336);
                bulk_prefetch_l2(reinterpret_cast<const char*>(w_up) + cta * 14336, 14336);
                bulk_prefetch_l2(reinterpret_cast<const char*>(w_down) + cta * 14336, 14336);
            }
            __syncwarp();
            const float l0 = __shfl_sync(0xffffffffu, o[8], lane & ~3), l1 = __shfl_sync(0xffffffffu, o[10], lane & ~3);
            const float r0 = __fdividef(1.f, l0), r1 = __fdividef(1.f, l1);
            uint32_t* Op = reinterpret_cast<uint32_t*>(gO + (size_t)row0 * DM + head * DH);
            Op[g * 256 + t4] = pack_bf16(o[0] * r0, o[1] * r0);
            Op[(g + 8) * 256 + t4] = pack_bf16(o[2] * r1, o[3] * r1);
            Op[g * 256 + 4 + t4] = pack_bf16(o[4] * r0, o[5] * r0);
            Op[(g + 8) * 256 + 4 + t4] = pack_bf16(o[6] * r1, o[7] * r1);
            bar_sync(3 + wg, 128);
            if ((tid & 127) == 0) st_flag(&gFlagO[tile * 32 + head], tag);
            if (tid == 384) TS(62 + pass);
        }
    }
    __syncthreads();
    if (tid == 0) TS(4);

    const int rb3 = cta >> 2, cb = cta & 3;
    if (wg < 2) {
        const int r0 = rb3 * 64 + w4 * 16 + g, r1 = r0 + 8;
        const int col0 = cb * 128 + wg * 64 + 2 * t4;
        uint32_t xa[8], xb[8], wr[8];
#pragma unroll
        for (int j = 0; j < 8; j++) {
            xa[j] = __ldg(reinterpret_cast<const uint32_t*>(x + (size_t)r0 * DM + col0 + j * 8));
            xb[j] = __ldg(reinterpret_cast<const uint32_t*>(x + (size_t)r1 * DM + col0 + j * 8));
            wr[j] = __ldg(reinterpret_cast<const uint32_t*>(w_r + col0 + j * 8));
        }
        const float p0 = __bfloat162float(x[(size_t)r0 * DM]), p1 = __bfloat162float(x[(size_t)r1 * DM]);
        const float pivot = __bfloat162float(x[(size_t)(rb3 * 64 + (tid >> 2)) * DM]);
        float wsum = 0.f;
        {
            const uint4 a = __ldg(reinterpret_cast<const uint4*>(w_r) + lane), b = __ldg(reinterpret_cast<const uint4*>(w_r) + 32 + lane);
            const uint32_t w[8] = {a.x, a.y, a.z, a.w, b.x, b.y, b.z, b.w};
#pragma unroll
            for (int e = 0; e < 8; e++) wsum += bf_lo(w[e]) + bf_hi(w[e]);
#pragma unroll
            for (int m = 16; m; m >>= 1) wsum += __shfl_xor_sync(0xffffffffu, wsum, m);
        }
        float acc[32];
#pragma unroll
        for (int i = 0; i < 32; i++) acc[i] = 0.f;
#pragma unroll 1
        for (int kc = 0; kc < 8; kc++) {
            mbar_wait(smem_u32(&ms.wo[kc]), 0);
            mbar_wait(smem_u32(&ms.a3[kc]), 0);
            const uint64_t da = make_desc(smem_u32(smem + SM_A3 + kc * 8192), 16, 1024, 1);
            const uint64_t db = make_desc(smem_u32(smem + (kc * 2 + wg) * KV_CHUNK), 8192, 1024, 1);
            wg_fence();
#pragma unroll
            for (int ks = 0; ks < 4; ks++) wgmma_n64(acc, da + ks * 2, db + ks * 128);
            wg_commit();
        }
        wg_wait<0>();
        pin(acc);
        if (tid == 0) TS(6);
        float s1a = 0.f, s2a = 0.f, s3a = 0.f, s1b = 0.f, s2b = 0.f, s3b = 0.f;
#pragma unroll
        for (int j = 0; j < 8; j++) {
            const uint32_t ha = pack_bf16(bf_lo(xa[j]) + acc[4 * j], bf_hi(xa[j]) + acc[4 * j + 1]);
            const uint32_t hb = pack_bf16(bf_lo(xb[j]) + acc[4 * j + 2], bf_hi(xb[j]) + acc[4 * j + 3]);
            xa[j] = ha; xb[j] = hb;
            const float w0 = bf_lo(wr[j]), w1 = bf_hi(wr[j]);
            const float da0 = bf_lo(ha) - p0, da1 = bf_hi(ha) - p0, db0 = bf_lo(hb) - p1, db1 = bf_hi(hb) - p1;
            s1a += da0 + da1; s2a = fmaf(da0, da0, fmaf(da1, da1, s2a)); s3a = fmaf(da0, w0, fmaf(da1, w1, s3a));
            s1b += db0 + db1; s2b = fmaf(db0, db0, fmaf(db1, db1, s2b)); s3b = fmaf(db0, w0, fmaf(db1, w1, s3b));
        }
#pragma unroll
        for (int m = 1; m <= 2; m <<= 1) {
            s1a += __shfl_xor_sync(0xffffffffu, s1a, m); s2a += __shfl_xor_sync(0xffffffffu, s2a, m); s3a += __shfl_xor_sync(0xffffffffu, s3a, m);
            s1b += __shfl_xor_sync(0xffffffffu, s1b, m); s2b += __shfl_xor_sync(0xffffffffu, s2b, m); s3b += __shfl_xor_sync(0xffffffffu, s3b, m);
        }
        if (t4 == 0) {
            const int lr = w4 * 16 + g;
            ms.p3.part[wg][lr][0] = s1a; ms.p3.part[wg][lr][1] = s2a; ms.p3.part[wg][lr][2] = s3a;
            ms.p3.part[wg][lr + 8][0] = s1b; ms.p3.part[wg][lr + 8][1] = s2b; ms.p3.part[wg][lr + 8][2] = s3b;
        }
        if (tid == 0) TS(11);
        bar_sync(1, 256);
        if (tid == 0) TS(12);
        if (tid < 64) {
            st_pkt(&gPart[(rb3 * 64 + tid) * 4 + cb],
                   make_uint4(__float_as_uint(ms.p3.part[0][tid][0] + ms.p3.part[1][tid][0]), __float_as_uint(ms.p3.part[0][tid][1] + ms.p3.part[1][tid][1]),
                              __float_as_uint(ms.p3.part[0][tid][2] + ms.p3.part[1][tid][2]), tag));
        }
        {
            const int lr = tid >> 2, sl = tid & 3;
            uint4 pv[1];
            wait_pkts<1, 0xffffffffu>(&gPart[rb3 * 256 + tid], 0, tag, pv);
            float s1 = __uint_as_float(pv[0].x), s2 = __uint_as_float(pv[0].y), s3 = __uint_as_float(pv[0].z);
            if (tid == 0) TS(14);
#pragma unroll
            for (int m = 1; m <= 2; m <<= 1) {
                s1 += __shfl_xor_sync(0xffffffffu, s1, m); s2 += __shfl_xor_sync(0xffffffffu, s2, m); s3 += __shfl_xor_sync(0xffffffffu, s3, m);
            }
            if (sl == 0) {
                const float md = s1 * (1.f / DM);
                const float var = fmaxf(s2 * (1.f / DM) - md * md, 0.f);
                const float rs = rsqrtf(var + LN_EPS);
                ms.p3.mu[lr] = pivot + md;
                ms.p3.rs[lr] = rs;
                ms.p3.r[lr] = (s3 - md * wsum) * rs;
            }
        }
        bar_sync(1, 256);
        if (tid == 0) TS(7);
        {
            unsigned int i1, i2;
            warp_top2(f2ord(ms.p3.r[lane]), lane, f2ord(ms.p3.r[lane + 32]), lane + 32, i1, i2);
            if (cb == 0) {
                const int c = tid & 1, li = c ? i2 : i1;
                st_pkt(&gCand[(tid >> 1) * 64 + rb3 * 2 + c],
                       make_uint4(__float_as_uint(ms.p3.r[li]), __float_as_uint(ms.p3.mu[li]), __float_as_uint(ms.p3.rs[li]),
                                  (tag << 11) | (unsigned int)(rb3 * 64 + li)));
            }
#pragma unroll
            for (int c = 0; c < 2; c++) {
                const unsigned int li = c ? i2 : i1;
                if ((int)(li >> 4) == w4 && (int)(li & 7) == g) {
                    const bool hi = (li & 8) != 0;
                    uint4* dst = &gCandRow[(rb3 * 2 + c) * 128 + (cb * 2 + wg) * 16 + t4];
#pragma unroll
                    for (int q = 0; q < 4; q++)
                        st_pkt(dst + q * 4, make_uint4(hi ? xb[2 * q] : xa[2 * q], hi ? xb[2 * q + 1] : xa[2 * q + 1], 0u, tag));
                }
            }
            if (tid == 0) TS(15);
        }
        {
            const int lr0 = w4 * 16 + g;
            const float mu0 = ms.p3.mu[lr0], rs0 = ms.p3.rs[lr0], mu1 = ms.p3.mu[lr0 + 8], rs1 = ms.p3.rs[lr0 + 8];
            char* so = smem + wg * KV_CHUNK;
#pragma unroll
            for (int j = 0; j < 8; j++) {
                const float a0 = bf_lo(xa[j]), a1 = bf_hi(xa[j]), b0 = bf_lo(xb[j]), b1 = bf_hi(xb[j]);
                const uint32_t la = pack_bf16((a0 - mu0) * rs0, (a1 - mu0) * rs0);
                const uint32_t lb = pack_bf16((b0 - mu1) * rs1, (b1 - mu1) * rs1);
                const int o = ((j ^ g) << 4) + t4 * 4;
                *reinterpret_cast<uint32_t*>(so + lr0 * 128 + o) = pack_bf16(a0 + bf_lo(la), a1 + bf_hi(la));
                *reinterpret_cast<uint32_t*>(so + (lr0 + 8) * 128 + o) = pack_bf16(b0 + bf_lo(lb), b1 + bf_hi(lb));
            }
            asm volatile("fence.proxy.async.shared::cta;" ::: "memory");
            bar_sync(3 + wg, 128);
            if ((tid & 127) == 0) {
                tma_store_2d(&tmOut, smem_u32(so), cb * 128 + wg * 64, rb3 * 64);
                asm volatile("cp.async.bulk.wait_group 0;" ::: "memory");
                st_flag(&gFlagOut[cta * 8 + wg], tag);
            }
        }
    } else {
        const int t = tid - 256;
        {
            const int kc = warp - 8;
            if (lane == 0) {
                int it = 0;
                while (true) {
                    const uint4 f = ld_pkt(reinterpret_cast<const uint4*>(&gFlagO[rb3 * 32 + kc * 4]));
                    if (f.x == tag && f.y == tag && f.z == tag && f.w == tag) break;
                    if (++it > SPIN_LIMIT) __trap();
                    BACKOFF();
                }
                if (kc == 7) TS(5);
                fence_proxy_async_global();
                const uint32_t bar = smem_u32(&ms.a3[kc]);
                mbar_expect_tx(bar, 8192);
                tma_2d(smem_u32(smem + SM_A3 + kc * 8192), &tmO, kc * 64, rb3 * 64, bar);
            }
            __syncwarp();
        }
        uint32_t wd[16];
        if (cta < NFFN) {
#pragma unroll
            for (int k = 0; k < 16; k++) wd[k] = __ldg(reinterpret_cast<const uint32_t*>(w_down + (size_t)(cta * 16 + k) * DM + 2 * t));
        }
        if (warp == 8) {
            if (lane == 0) TS(56);
            uint4 cv[2];
            wait_pkts<2, 0xfffff800u>(&gCand[cta * 64 + lane * 2], 1, tag << 11, cv);
            if (lane == 0) TS(54);
            unsigned int i1, i2;
            warp_top2(f2ord(__uint_as_float(cv[0].x)), cv[0].w & 0x7ffu, f2ord(__uint_as_float(cv[1].x)), cv[1].w & 0x7ffu, i1, i2);
#pragma unroll
            for (int c = 0; c < 2; c++) {
                const unsigned int ci = cv[c].w & 0x7ffu;
                if (ci == i1 || ci == i2) {
                    const int o = ci == i1 ? 0 : 1;
                    ms.idx[o] = (int)ci;
                    ms.cslot[o] = lane * 2 + c;
                    *reinterpret_cast<float4*>(&ms.sel[o * 4]) =
                        make_float4(__uint_as_float(cv[c].y), __uint_as_float(cv[c].z), __fdividef(1.f, 1.f + __expf(-__uint_as_float(cv[c].x))), 0.f);
                }
            }
            if (lane == 0) TS(8);
        }
        bar_sync(2, 256);
        const int idx0 = ms.idx[0], idx1 = ms.idx[1];
        if (t == 0 && idx0 >= 0) TS(61);
        float* sX = reinterpret_cast<float*>(smem + SM_A3);
        float* sH = sX + 1024;
        float* sPart = sX + 2048;
        float* sAct = sPart + 512;
        if (cta < NFFN) {
            {
                const int tk = t >> 7, P = t & 127;
                uint4 hv[1];
                wait_pkts<1, 0xffffffffu>(&gCandRow[ms.cslot[tk] * 128 + P], 0, tag, hv);
                if (t == 0) TS(57);
                const float mu = ms.sel[tk * 4], rs = ms.sel[tk * 4 + 1];
                const int col = (P >> 4) * 64 + ((P >> 2) & 3) * 16 + (P & 3) * 2;
                const uint32_t l0 = pack_bf16((bf_lo(hv[0].x) - mu) * rs, (bf_hi(hv[0].x) - mu) * rs);
                const uint32_t l1 = pack_bf16((bf_lo(hv[0].y) - mu) * rs, (bf_hi(hv[0].y) - mu) * rs);
                *reinterpret_cast<float2*>(&sX[tk * 512 + col]) = make_float2(bf_lo(l0), bf_hi(l0));
                *reinterpret_cast<float2*>(&sX[tk * 512 + col + 8]) = make_float2(bf_lo(l1), bf_hi(l1));
                *reinterpret_cast<float2*>(&sH[tk * 512 + col]) = make_float2(bf_lo(hv[0].x), bf_hi(hv[0].x));
                *reinterpret_cast<float2*>(&sH[tk * 512 + col + 8]) = make_float2(bf_lo(hv[0].y), bf_hi(hv[0].y));
            }
            mbar_wait(smem_u32(&ms.moe), 0);
            bar_sync(1 + 8, 256);
            if (t == 0) { asm volatile("" ::: "memory"); sAct[40] = sX[0]; TS(58); }
            {
                const int wv = warp - 8, kk = lane >> 3, cp = lane & 7;
                float a[2][2][2] = {};
#pragma unroll
                for (int i = 0; i < 16; i++) {
                    const int k = wv * 64 + i * 4 + kk;
                    const float x0 = sX[k], x1 = sX[512 + k];
#pragma unroll
                    for (int mat = 0; mat < 2; mat++) {
                        const uint32_t w = *reinterpret_cast<const uint32_t*>(smem + (mat * 8 + wv) * KV_CHUNK + 8192 + (i * 4 + kk) * 32 + cp * 4);
                        a[mat][0][0] = fmaf(x0, bf_lo(w), a[mat][0][0]); a[mat][0][1] = fmaf(x0, bf_hi(w), a[mat][0][1]);
                        a[mat][1][0] = fmaf(x1, bf_lo(w), a[mat][1][0]); a[mat][1][1] = fmaf(x1, bf_hi(w), a[mat][1][1]);
                    }
                }
#pragma unroll
                for (int mat = 0; mat < 2; mat++)
#pragma unroll
                    for (int tk = 0; tk < 2; tk++)
#pragma unroll
                        for (int e = 0; e < 2; e++) {
                            float v = a[mat][tk][e];
                            v += __shfl_xor_sync(0xffffffffu, v, 8);
                            v += __shfl_xor_sync(0xffffffffu, v, 16);
                            if (kk == 0) sPart[(wv * 2 + tk) * 32 + mat * 16 + 2 * cp + e] = v;
                        }
            }
            bar_sync(1 + 8, 256);
            if (t == 0) { sAct[41] = sPart[0]; TS(59); }
            if (t < 32) {
                const int tk = t >> 4, c = t & 15;
                float gs = 0.f, us = 0.f;
#pragma unroll
                for (int w = 0; w < 8; w++) { gs += sPart[(w * 2 + tk) * 32 + c]; us += sPart[(w * 2 + tk) * 32 + 16 + c]; }
                const float gb = bf_round(gs), ub = bf_round(us);
                const float sl = bf_round(__fdividef(gb, 1.f + __expf(-gb)));
                sAct[tk * 16 + c] = bf_round(sl * ub);
            }
            bar_sync(1 + 8, 256);
            {
                float y00 = 0.f, y01 = 0.f, y10 = 0.f, y11 = 0.f;
#pragma unroll
                for (int k = 0; k < 16; k++) {
                    const float a0 = sAct[k], a1 = sAct[16 + k];
                    y00 = fmaf(a0, bf_lo(wd[k]), y00); y01 = fmaf(a0, bf_hi(wd[k]), y01);
                    y10 = fmaf(a1, bf_lo(wd[k]), y10); y11 = fmaf(a1, bf_hi(wd[k]), y11);
                }
                st_pkt(&gYPart[((t >> 2) * NFFN + cta) * 4 + (t & 3)], embed_tag(y00, y01, y10, y11, tag));
            }
            if (t == 0) TS(9);
        }
        if (cta < 64) {
            const int pc = t & 3, part = t >> 2;
            const int opc = (t >> 2) & 3, oe = t & 3, otk = oe >> 1, ocol = (cta * 4 + opc) * 2 + (oe & 1);
            float y[4] = {0.f, 0.f, 0.f, 0.f};
            if (part < 56) {
                uint4 yv[2];
                wait_pkts4<2>(&gYPart[(cta * NFFN + part) * 4 + pc], 56 * 4, tag, yv);
                if (t == 0) TS(60);
                y[0] = __uint_as_float(yv[0].x) + __uint_as_float(yv[1].x); y[1] = __uint_as_float(yv[0].y) + __uint_as_float(yv[1].y);
                y[2] = __uint_as_float(yv[0].z) + __uint_as_float(yv[1].z); y[3] = __uint_as_float(yv[0].w) + __uint_as_float(yv[1].w);
            }
            if (t >= 224 && t < 226) {
                const int orow = (t & 1) ? idx1 : idx0, oc = cta * 8;
                wait_flag(&gFlagOut[((orow >> 6) * 4 + (oc >> 7)) * 8 + ((oc >> 6) & 1)], tag);
            }
            __syncwarp();
#pragma unroll
            for (int e = 0; e < 4; e++) {
                y[e] += __shfl_xor_sync(0xffffffffu, y[e], 4); y[e] += __shfl_xor_sync(0xffffffffu, y[e], 8); y[e] += __shfl_xor_sync(0xffffffffu, y[e], 16);
            }
            float* sR = sAct + 32;
            if (lane < 4) *reinterpret_cast<float4*>(&sR[(warp - 8) * 16 + lane * 4]) = make_float4(y[0], y[1], y[2], y[3]);
            bar_sync(1 + 8, 256);
            if (t < 16) {
                float s = 0.f;
#pragma unroll
                for (int w = 0; w < 8; w++) s += sR[w * 16 + t];
                const float yb = bf_round(bf_round(s) * ms.sel[otk * 4 + 2]);
                out[(size_t)(otk ? idx1 : idx0) * DM + ocol] = __float2bfloat16(sH[otk * 512 + ocol] + bf_round(sX[otk * 512 + ocol] + yb));
            }
            if (cta == 0 && t == 0) {
                *reinterpret_cast<volatile unsigned int*>(&gEpoch) = tag;
            }
            if (t == 0) TS(10);
        }
    }
}

typedef CUresult (*EncodeFn)(CUtensorMap*, CUtensorMapDataType, cuuint32_t, void*, const cuuint64_t*, const cuuint64_t*,
                             const cuuint32_t*, const cuuint32_t*, CUtensorMapInterleave, CUtensorMapSwizzle,
                             CUtensorMapL2promotion, CUtensorMapFloatOOBfill);

void make_map(EncodeFn enc, CUtensorMap* tm, const void* base, uint64_t cols, uint64_t rows, uint32_t box_c, uint32_t box_r, bool swz) {
    cuuint64_t dims[2] = {cols, rows};
    cuuint64_t strides[1] = {cols * 2};
    cuuint32_t box[2] = {box_c, box_r};
    cuuint32_t es[2] = {1, 1};
    enc(tm, CU_TENSOR_MAP_DATA_TYPE_BFLOAT16, 2, const_cast<void*>(base), dims, strides, box, es, CU_TENSOR_MAP_INTERLEAVE_NONE,
        swz ? CU_TENSOR_MAP_SWIZZLE_128B : CU_TENSOR_MAP_SWIZZLE_NONE, CU_TENSOR_MAP_L2_PROMOTION_L2_256B,
        CU_TENSOR_MAP_FLOAT_OOB_FILL_NONE);
}

}

extern "C" void kernel_launch(void* const* d_in, const int* in_sizes, int n_in, void* d_out, int out_size) {
    const __nv_bfloat16* x = (const __nv_bfloat16*)d_in[0];
    const __nv_bfloat16* wqkv = (const __nv_bfloat16*)d_in[1];
    const __nv_bfloat16* wo = (const __nv_bfloat16*)d_in[2];
    const __nv_bfloat16* w_r = (const __nv_bfloat16*)d_in[4];
    const __nv_bfloat16* w_gate = (const __nv_bfloat16*)d_in[5];
    const __nv_bfloat16* w_up = (const __nv_bfloat16*)d_in[6];
    const __nv_bfloat16* w_down = (const __nv_bfloat16*)d_in[7];
    __nv_bfloat16* out = (__nv_bfloat16*)d_out;

    static EncodeFn enc = nullptr;
    static void* pO = nullptr;
    if (!enc) {
        void* fn = nullptr;
        cudaDriverEntryPointQueryResult qr;
        cudaGetDriverEntryPoint("cuTensorMapEncodeTiled", &fn, cudaEnableDefault, &qr);
        enc = (EncodeFn)fn;
        cudaGetSymbolAddress(&pO, gO);
        cudaFuncSetAttribute(mega_kernel, cudaFuncAttributeMaxDynamicSharedMemorySize, SMEM_TOTAL);
    }
    CUtensorMap tmX, tmW, tmO, tmWo, tmG, tmU, tmOut;
    make_map(enc, &tmX, x, DM, S_LEN, 64, 128, true);
    make_map(enc, &tmW, wqkv, 3 * DM, DM, 64, 64, true);
    make_map(enc, &tmO, pO, DM, S_LEN, 64, 64, true);
    make_map(enc, &tmWo, wo, DM, DM, 64, 64, true);
    make_map(enc, &tmG, w_gate, FF, DM, 16, 64, false);
    make_map(enc, &tmU, w_up, FF, DM, 16, 64, false);
    make_map(enc, &tmOut, out, DM, S_LEN, 64, 64, true);

    mega_kernel<<<128, 512, SMEM_TOTAL, cudaStreamPerThread>>>(tmX, tmW, tmO, tmWo, tmG, tmU, tmOut, x, wqkv, wo, w_r, w_gate, w_up, w_down, out);
}
```

```cpp
#include <cuda_runtime.h>
#include <cuda_bf16.h>
#include <cuda.h>
#include <stdint.h>

namespace {

constexpr int S_LEN = 2048, DM = 512, NH = 32, DH = 16, FF = 1792;
constexpr int NFFN = FF / 16;
constexpr float LN_EPS = 1e-5f;
constexpr float QSCALE = 0.25f * 1.4426950408889634f;

__device__ __align__(1024) __nv_bfloat16 gQ[NH * S_LEN * DH];
__device__ __align__(1024) __nv_bfloat16 gKV[NH * S_LEN * DH * 2];
__device__ __align__(1024) __nv_bfloat16 gO[S_LEN * DM];
__device__ __align__(16) float gNorm[16 * NH * 4];
__device__ unsigned int gEpoch;
__device__ __align__(32) unsigned int gFlagQKV[128 * 8];
__device__ __align__(32) unsigned int gFlagO[32 * 32];
__device__ uint4 gStat1[S_LEN];
__device__ uint4 gCsPart[8 * 16 * 48];
__device__ uint4 gPart[32 * 64 * 4];
__device__ uint4 gCand[128 * 64];
__device__ __align__(32) unsigned int gFlagOut[128 * 8];
__device__ uint4 gCandRow[64 * 128];
__device__ uint4 gYPart[NFFN * 256];

#define TS(slot) do {} while (0)

__device__ __forceinline__ uint32_t smem_u32(const void* p) { return (uint32_t)__cvta_generic_to_shared(p); }
__device__ __forceinline__ void mbar_init(uint32_t bar, uint32_t cnt) {
    asm volatile("mbarrier.init.shared::cta.b64 [%0], %1;" ::"r"(bar), "r"(cnt));
}
__device__ __forceinline__ void mbar_expect_tx(uint32_t bar, uint32_t bytes) {
    asm volatile("mbarrier.arrive.expect_tx.shared::cta.b64 _, [%0], %1;" ::"r"(bar), "r"(bytes) : "memory");
}
__device__ __forceinline__ void mbar_arrive(uint32_t bar) {
    asm volatile("mbarrier.arrive.shared::cta.b64 _, [%0];" ::"r"(bar) : "memory");
}
constexpr int SPIN_LIMIT = 1 << 22;
#define BACKOFF() __nanosleep(32)
__device__ __forceinline__ void mbar_wait(uint32_t bar, uint32_t parity) {
    uint32_t done = 0;
    int it = 0;
    while (true) {
        asm volatile("{.reg .pred p; mbarrier.try_wait.parity.shared::cta.b64 p, [%1], %2; selp.u32 %0, 1, 0, p;}"
                     : "=r"(done) : "r"(bar), "r"(parity) : "memory");
        if (done) break;
        if (++it > SPIN_LIMIT) __trap();
    }
}
__device__ __forceinline__ void bulk_g2s(uint32_t dst, const void* src, uint32_t bytes, uint32_t bar) {
    asm volatile("cp.async.bulk.shared::cluster.global.mbarrier::complete_tx::bytes [%0], [%1], %2, [%3];"
                 ::"r"(dst), "l"(src), "r"(bytes), "r"(bar) : "memory");
}
__device__ __forceinline__ void bulk_prefetch_l2(const void* src, uint32_t bytes) {
    asm volatile("cp.async.bulk.prefetch.L2.global [%0], %1;" ::"l"(src), "r"(bytes) : "memory");
}
__device__ __forceinline__ void tma_2d(uint32_t dst, const CUtensorMap* tm, int c0, int c1, uint32_t bar) {
    asm volatile("cp.async.bulk.tensor.2d.shared::cluster.global.mbarrier::complete_tx::bytes [%0], [%1, {%3, %4}], [%2];"
                 ::"r"(dst), "l"(tm), "r"(bar), "r"(c0), "r"(c1) : "memory");
}
__device__ __forceinline__ void tma_store_2d(const CUtensorMap* tm, uint32_t src, int c0, int c1) {
    asm volatile("cp.async.bulk.tensor.2d.global.shared::cta.bulk_group [%0, {%2, %3}], [%1];" ::"l"(tm), "r"(src), "r"(c0), "r"(c1) : "memory");
    asm volatile("cp.async.bulk.commit_group;" ::: "memory");
}
__device__ __forceinline__ void fence_proxy_async_global() { asm volatile("fence.proxy.async.global;" ::: "memory"); }
__device__ __forceinline__ void fence_gpu() { asm volatile("fence.acq_rel.gpu;" ::: "memory"); }
__device__ __forceinline__ void bar_sync(int id, int n) { asm volatile("bar.sync %0, %1;" ::"r"(id), "r"(n) : "memory"); }
__device__ __forceinline__ void bar_arrive(int id, int n) { asm volatile("bar.arrive %0, %1;" ::"r"(id), "r"(n) : "memory"); }
__device__ __forceinline__ void st_flag(unsigned int* p, unsigned int v) {
    asm volatile("st.release.gpu.global.u32 [%0], %1;" ::"l"(p), "r"(v) : "memory");
}
__device__ __forceinline__ unsigned int ld_flag(const unsigned int* p) {
    unsigned int v;
    asm volatile("ld.relaxed.gpu.global.u32 %0, [%1];" : "=r"(v) : "l"(p) : "memory");
    return v;
}
__device__ __forceinline__ void wait_flag(const unsigned int* p, unsigned int tag) {
    int it = 0;
    while (ld_flag(p) != tag) {
        if (++it > SPIN_LIMIT) __trap();
        BACKOFF();
    }
}
__device__ __forceinline__ void st_pkt(uint4* p, uint4 v) {
    asm volatile("st.relaxed.gpu.global.v4.u32 [%0], {%1,%2,%3,%4};" ::"l"(p), "r"(v.x), "r"(v.y), "r"(v.z), "r"(v.w) : "memory");
}
__device__ __forceinline__ uint4 ld_pkt(const uint4* p) {
    uint4 v;
    asm volatile("ld.relaxed.gpu.global.v4.u32 {%0,%1,%2,%3}, [%4];" : "=r"(v.x), "=r"(v.y), "=r"(v.z), "=r"(v.w) : "l"(p) : "memory");
    return v;
}
template <int N, unsigned int MASK>
__device__ __forceinline__ void wait_pkts(const uint4* p, int stride, unsigned int tag, uint4 (&v)[N]) {
    int it = 0;
    while (true) {
        bool ok = true;
#pragma unroll
        for (int i = 0; i < N; i++) v[i] = ld_pkt(p + (size_t)i * stride);
#pragma unroll
        for (int i = 0; i < N; i++) ok = ok && ((v[i].w & MASK) == tag);
        if (ok) break;
        if (++it > SPIN_LIMIT) __trap();
        BACKOFF();
    }
}
__device__ __forceinline__ uint4 embed_tag(float a, float b, float c, float d, unsigned int tag) {
    return make_uint4((__float_as_uint(a) & ~15u) | (tag & 15u), (__float_as_uint(b) & ~15u) | ((tag >> 4) & 15u),
                      (__float_as_uint(c) & ~15u) | ((tag >> 8) & 15u), (__float_as_uint(d) & ~15u) | ((tag >> 12) & 15u));
}
template <int N>
__device__ __forceinline__ void wait_pkts4(const uint4* p, int stride, unsigned int tag, uint4 (&v)[N]) {
    const unsigned int t16 = tag & 0xffffu;
    int it = 0;
    while (true) {
        bool ok = true;
#pragma unroll
        for (int i = 0; i < N; i++) v[i] = ld_pkt(p + (size_t)i * stride);
#pragma unroll
        for (int i = 0; i < N; i++)
            ok = ok && (((v[i].x & 15u) | ((v[i].y & 15u) << 4) | ((v[i].z & 15u) << 8) | ((v[i].w & 15u) << 12)) == t16);
        if (ok) break;
        if (++it > SPIN_LIMIT) __trap();
        BACKOFF();
    }
}
__device__ __forceinline__ uint64_t make_desc(uint32_t addr, uint32_t lbo, uint32_t sbo, uint32_t mode) {
    return (uint64_t)((addr & 0x3FFFF) >> 4) | ((uint64_t)((lbo & 0x3FFFF) >> 4) << 16) |
           ((uint64_t)((sbo & 0x3FFFF) >> 4) << 32) | ((uint64_t)mode << 62);
}
__device__ __forceinline__ void wg_fence() { asm volatile("wgmma.fence.sync.aligned;" ::: "memory"); }
__device__ __forceinline__ void wg_commit() { asm volatile("wgmma.commit_group.sync.aligned;" ::: "memory"); }
template <int N> __device__ __forceinline__ void wg_wait() { asm volatile("wgmma.wait_group.sync.aligned %0;" ::"n"(N) : "memory"); }
template <int N> __device__ __forceinline__ void pin(uint32_t (&d)[N]) {
#pragma unroll
    for (int i = 0; i < N; i++) asm volatile("" : "+r"(d[i])::"memory");
}
template <int N> __device__ __forceinline__ void pin(float (&d)[N]) {
#pragma unroll
    for (int i = 0; i < N; i++) asm volatile("" : "+f"(d[i])::"memory");
}
__device__ __forceinline__ uint32_t pack_bf16(float lo, float hi) {
    uint32_t r;
    asm("cvt.rn.bf16x2.f32 %0, %1, %2;" : "=r"(r) : "f"(hi), "f"(lo));
    return r;
}
__device__ __forceinline__ float bf_lo(uint32_t v) { return __uint_as_float(v << 16); }
__device__ __forceinline__ float bf_hi(uint32_t v) { return __uint_as_float(v & 0xFFFF0000u); }
__device__ __forceinline__ float bf_round(float v) { return __bfloat162float(__float2bfloat16(v)); }
__device__ __forceinline__ float ex2_mufu(float x) {
    float y;
    asm("ex2.approx.ftz.f32 %0, %1;" : "=f"(y) : "f"(x));
    return y;
}

#define ACC8(d, o) "+f"(d[o + 0]), "+f"(d[o + 1]), "+f"(d[o + 2]), "+f"(d[o + 3]), "+f"(d[o + 4]), "+f"(d[o + 5]), "+f"(d[o + 6]), "+f"(d[o + 7])
#define OUT8(d, o) "=f"(d[o + 0]), "=f"(d[o + 1]), "=f"(d[o + 2]), "=f"(d[o + 3]), "=f"(d[o + 4]), "=f"(d[o + 5]), "=f"(d[o + 6]), "=f"(d[o + 7])

__device__ __forceinline__ void wgmma_n192(float (&d)[96], uint64_t da, uint64_t db) {
    asm volatile(
        "wgmma.mma_async.sync.aligned.m64n192k16.f32.bf16.bf16 "
        "{%0,%1,%2,%3,%4,%5,%6,%7,%8,%9,%10,%11,%12,%13,%14,%15,%16,%17,%18,%19,%20,%21,%22,%23,%24,%25,%26,%27,%28,%29,%30,%31,"
        "%32,%33,%34,%35,%36,%37,%38,%39,%40,%41,%42,%43,%44,%45,%46,%47,%48,%49,%50,%51,%52,%53,%54,%55,%56,%57,%58,%59,%60,%61,%62,%63,"
        "%64,%65,%66,%67,%68,%69,%70,%71,%72,%73,%74,%75,%76,%77,%78,%79,%80,%81,%82,%83,%84,%85,%86,%87,%88,%89,%90,%91,%92,%93,%94,%95},"
        "%96, %97, 1, 1, 1, 0, 1;"
        : ACC8(d, 0), ACC8(d, 8), ACC8(d, 16), ACC8(d, 24), ACC8(d, 32), ACC8(d, 40), ACC8(d, 48), ACC8(d, 56),
          ACC8(d, 64), ACC8(d, 72), ACC8(d, 80), ACC8(d, 88)
        : "l"(da), "l"(db));
}
__device__ __forceinline__ void wgmma_n192_rs(float (&d)[96], const uint32_t* a, uint64_t db) {
    asm volatile(
        "wgmma.mma_async.sync.aligned.m64n192k16.f32.bf16.bf16 "
        "{%0,%1,%2,%3,%4,%5,%6,%7,%8,%9,%10,%11,%12,%13,%14,%15,%16,%17,%18,%19,%20,%21,%22,%23,%24,%25,%26,%27,%28,%29,%30,%31,"
        "%32,%33,%34,%35,%36,%37,%38,%39,%40,%41,%42,%43,%44,%45,%46,%47,%48,%49,%50,%51,%52,%53,%54,%55,%56,%57,%58,%59,%60,%61,%62,%63,"
        "%64,%65,%66,%67,%68,%69,%70,%71,%72,%73,%74,%75,%76,%77,%78,%79,%80,%81,%82,%83,%84,%85,%86,%87,%88,%89,%90,%91,%92,%93,%94,%95},"
        "{%96,%97,%98,%99}, %100, 1, 1, 1, 1;"
        : ACC8(d, 0), ACC8(d, 8), ACC8(d, 16), ACC8(d, 24), ACC8(d, 32), ACC8(d, 40), ACC8(d, 48), ACC8(d, 56),
          ACC8(d, 64), ACC8(d, 72), ACC8(d, 80), ACC8(d, 88)
        : "r"(a[0]), "r"(a[1]), "r"(a[2]), "r"(a[3]), "l"(db));
}
__device__ __forceinline__ void ldsm_x4(uint32_t* r, uint32_t addr) {
    asm volatile("ldmatrix.sync.aligned.m8n8.x4.shared.b16 {%0,%1,%2,%3}, [%4];"
                 : "=r"(r[0]), "=r"(r[1]), "=r"(r[2]), "=r"(r[3]) : "r"(addr) : "memory");
}
__device__ __forceinline__ void wgmma_n64(float (&d)[32], uint64_t da, uint64_t db) {
    asm volatile(
        "wgmma.mma_async.sync.aligned.m64n64k16.f32.bf16.bf16 "
        "{%0,%1,%2,%3,%4,%5,%6,%7,%8,%9,%10,%11,%12,%13,%14,%15,%16,%17,%18,%19,%20,%21,%22,%23,%24,%25,%26,%27,%28,%29,%30,%31},"
        "%32, %33, 1, 1, 1, 0, 1;"
        : ACC8(d, 0), ACC8(d, 8), ACC8(d, 16), ACC8(d, 24)
        : "l"(da), "l"(db));
}
__device__ __forceinline__ void wgmma_qk128(float (&d)[64], const uint32_t (&a)[4], uint64_t db) {
    asm volatile("wgmma.mma_async.sync.aligned.m64n128k16.f32.f16.f16 "
        "{%0,%1,%2,%3,%4,%5,%6,%7,%8,%9,%10,%11,%12,%13,%14,%15,%16,%17,%18,%19,%20,%21,%22,%23,%24,%25,%26,%27,%28,%29,%30,%31,%32,%33,%34,%35,%36,%37,%38,%39,%40,%41,%42,%43,%44,%45,%46,%47,%48,%49,%50,%51,%52,%53,%54,%55,%56,%57,%58,%59,%60,%61,%62,%63}, {%64,%65,%66,%67}, %68, 0, 1, 1, 0;"
        : "=f"(d[0]), "=f"(d[1]), "=f"(d[2]), "=f"(d[3]), "=f"(d[4]), "=f"(d[5]), "=f"(d[6]), "=f"(d[7]), "=f"(d[8]), "=f"(d[9]), "=f"(d[10]), "=f"(d[11]), "=f"(d[12]), "=f"(d[13]), "=f"(d[14]), "=f"(d[15]), "=f"(d[16]), "=f"(d[17]), "=f"(d[18]), "=f"(d[19]), "=f"(d[20]), "=f"(d[21]), "=f"(d[22]), "=f"(d[23]), "=f"(d[24]), "=f"(d[25]), "=f"(d[26]), "=f"(d[27]), "=f"(d[28]), "=f"(d[29]), "=f"(d[30]), "=f"(d[31]), "=f"(d[32]), "=f"(d[33]), "=f"(d[34]), "=f"(d[35]), "=f"(d[36]), "=f"(d[37]), "=f"(d[38]), "=f"(d[39]), "=f"(d[40]), "=f"(d[41]), "=f"(d[42]), "=f"(d[43]), "=f"(d[44]), "=f"(d[45]), "=f"(d[46]), "=f"(d[47]), "=f"(d[48]), "=f"(d[49]), "=f"(d[50]), "=f"(d[51]), "=f"(d[52]), "=f"(d[53]), "=f"(d[54]), "=f"(d[55]), "=f"(d[56]), "=f"(d[57]), "=f"(d[58]), "=f"(d[59]), "=f"(d[60]), "=f"(d[61]), "=f"(d[62]), "=f"(d[63])
        : "r"(a[0]), "r"(a[1]), "r"(a[2]), "r"(a[3]), "l"(db));
}
__device__ __forceinline__ void wgmma_qk64_f32(float (&d)[32], const uint32_t (&a)[4], uint64_t db) {
    asm volatile("wgmma.mma_async.sync.aligned.m64n64k16.f32.f16.f16 "
        "{%0,%1,%2,%3,%4,%5,%6,%7,%8,%9,%10,%11,%12,%13,%14,%15,%16,%17,%18,%19,%20,%21,%22,%23,%24,%25,%26,%27,%28,%29,%30,%31}, {%32,%33,%34,%35}, %36, 0, 1, 1, 0;"
        : "=f"(d[0]), "=f"(d[1]), "=f"(d[2]), "=f"(d[3]), "=f"(d[4]), "=f"(d[5]), "=f"(d[6]), "=f"(d[7]), "=f"(d[8]), "=f"(d[9]), "=f"(d[10]), "=f"(d[11]), "=f"(d[12]), "=f"(d[13]), "=f"(d[14]), "=f"(d[15]), "=f"(d[16]), "=f"(d[17]), "=f"(d[18]), "=f"(d[19]), "=f"(d[20]), "=f"(d[21]), "=f"(d[22]), "=f"(d[23]), "=f"(d[24]), "=f"(d[25]), "=f"(d[26]), "=f"(d[27]), "=f"(d[28]), "=f"(d[29]), "=f"(d[30]), "=f"(d[31])
        : "r"(a[0]), "r"(a[1]), "r"(a[2]), "r"(a[3]), "l"(db));
}
__device__ __forceinline__ void wgmma_qk64_f16(uint32_t (&d)[16], const uint32_t (&a)[4], uint64_t db) {
    asm volatile("wgmma.mma_async.sync.aligned.m64n64k16.f16.f16.f16 "
        "{%0,%1,%2,%3,%4,%5,%6,%7,%8,%9,%10,%11,%12,%13,%14,%15}, {%16,%17,%18,%19}, %20, 0, 1, 1, 0;"
        : "=r"(d[0]), "=r"(d[1]), "=r"(d[2]), "=r"(d[3]), "=r"(d[4]), "=r"(d[5]), "=r"(d[6]), "=r"(d[7]), "=r"(d[8]), "=r"(d[9]), "=r"(d[10]), "=r"(d[11]), "=r"(d[12]), "=r"(d[13]), "=r"(d[14]), "=r"(d[15])
        : "r"(a[0]), "r"(a[1]), "r"(a[2]), "r"(a[3]), "l"(db));
}
__device__ __forceinline__ void wgmma_pv24(float (&o)[12], uint32_t a0, uint32_t a1, uint32_t a2, uint32_t a3, uint64_t desc) {
    asm volatile(
        "wgmma.mma_async.sync.aligned.m64n24k16.f32.bf16.bf16 "
        "{%0,%1,%2,%3,%4,%5,%6,%7,%8,%9,%10,%11}, {%12,%13,%14,%15}, %16, 1, 1, 1, 1;"
        : ACC8(o, 0), "+f"(o[8]), "+f"(o[9]), "+f"(o[10]), "+f"(o[11])
        : "r"(a0), "r"(a1), "r"(a2), "r"(a3), "l"(desc));
}

__device__ __forceinline__ uint32_t ex2_pair_h16(uint32_t x2) {
    uint32_t t, r, f, q;
    asm("add.rn.f16x2 %0, %1, %2;" : "=r"(t) : "r"(x2), "r"(0x661E661Fu));
    asm("sub.rn.f16x2 %0, %1, %2;" : "=r"(r) : "r"(t), "r"(0x661E661Fu));
    asm("sub.rn.f16x2 %0, %1, %2;" : "=r"(f) : "r"(x2), "r"(r));
    asm("fma.rn.f16x2 %0, %1, %2, %3;" : "=r"(q) : "r"(0x15101510u), "r"(f), "r"(0x1d7e1d7eu));
    asm("fma.rn.f16x2 %0, %1, %2, %3;" : "=r"(q) : "r"(q), "r"(f), "r"(0x23d823d8u));
    asm("fma.rn.f16x2 %0, %1, %2, %3;" : "=r"(q) : "r"(q), "r"(f), "r"(0x30823035u));
    return t * 128u + q;
}
constexpr float VSCALE_ODD = 0.70703125f;
constexpr float LOG2C_ODD = 0.50015402f;
__device__ __forceinline__ uint32_t pack_f16_sat(float lo, float hi) {
    uint32_t r;
    asm("cvt.rn.satfinite.f16x2.f32 %0, %1, %2;" : "=r"(r) : "f"(hi), "f"(lo));
    return r;
}
__device__ __forceinline__ unsigned int f2ord(float v) {
    const unsigned int u = __float_as_uint(v);
    const unsigned int o = u ^ ((unsigned int)((int)u >> 31) | 0x80000000u);
    return (v == v) ? o : 0u;
}
__device__ __forceinline__ void warp_top2(unsigned int ka, unsigned int ia, unsigned int kb, unsigned int ib, unsigned int& i1, unsigned int& i2) {
    const unsigned int m1 = __reduce_max_sync(0xffffffffu, max(ka, kb));
    i1 = __reduce_min_sync(0xffffffffu, min(ka == m1 ? ia : 0xffffffffu, kb == m1 ? ib : 0xffffffffu));
    const bool ra = (ia == i1), rb = (ib == i1);
    const unsigned int ka2 = ra ? 0u : ka, kb2 = rb ? 0u : kb, ia2 = ra ? 0xffffffffu : ia, ib2 = rb ? 0xffffffffu : ib;
    const unsigned int m2 = __reduce_max_sync(0xffffffffu, max(ka2, kb2));
    i2 = __reduce_min_sync(0xffffffffu, min(ka2 == m2 ? ia2 : 0xffffffffu, kb2 == m2 ? ib2 : 0xffffffffu));
}

constexpr int P1_STAGES = 5;
constexpr int P1_STAGE_BYTES = 16384 + 24576;
constexpr int KV_CHUNK = 10240;
constexpr int SM_Q = 163840 + 49152;
constexpr int SM_A3 = 163840;
constexpr int SM_MISC = 229376;
constexpr int SMEM_TOTAL = 232448;
struct Misc {
    uint64_t p1_full[P1_STAGES], p1_empty[P1_STAGES];
    uint64_t kv[16];
    uint64_t wo[8], a3[8], moe;
    unsigned int tag;
    int fast;
    int idx[2], cslot[2];
    alignas(16) float sel[8];
    unsigned int norm[12];
    uint64_t qbar;
    int item, nxt[4];
    unsigned int seq[8];
    unsigned int freed[16];
    union alignas(16) {
        struct { float mu[128], rs[128], cs[192]; } p1;
        struct { float part[2][64][3]; float mu[64], rs[64], r[64]; } p3;
    };
};
static_assert(sizeof(Misc) <= SMEM_TOTAL - SM_MISC, "misc smem");

__global__ void __launch_bounds__(512, 1)
mega_kernel(const __grid_constant__ CUtensorMap tmX, const __grid_constant__ CUtensorMap tmW,
            const __grid_constant__ CUtensorMap tmO, const __grid_constant__ CUtensorMap tmWo,
            const __grid_constant__ CUtensorMap tmG, const __grid_constant__ CUtensorMap tmU, const __grid_constant__ CUtensorMap tmOut,
            const __nv_bfloat16* __restrict__ x, const __nv_bfloat16* __restrict__ wqkv, const __nv_bfloat16* __restrict__ wo,
            const __nv_bfloat16* __restrict__ w_r, const __nv_bfloat16* __restrict__ w_gate,
            const __nv_bfloat16* __restrict__ w_up, const __nv_bfloat16* __restrict__ w_down,
            __nv_bfloat16* __restrict__ out) {
    extern __shared__ __align__(1024) char smem[];
    Misc& ms = *reinterpret_cast<Misc*>(smem + SM_MISC);
    const int tid = threadIdx.x, lane = tid & 31;
    const int warp = __shfl_sync(0xffffffffu, tid >> 5, 0);
    const int wg = warp >> 2, w4 = warp & 3, g = lane >> 2, t4 = lane & 3;
    const int cta = blockIdx.x;
    const int rb = cta >> 3, hg = cta & 7;

    if (warp == 12) {
        if (lane == 0) {
            TS(0);
            if (smem_u32(smem) & 1023) __trap();
            for (int i = 0; i < P1_STAGES; i++) { mbar_init(smem_u32(&ms.p1_full[i]), 1); mbar_init(smem_u32(&ms.p1_empty[i]), 8); }
            asm volatile("fence.mbarrier_init.release.cluster;" ::: "memory");
        }
        __syncwarp();
        bar_arrive(13, 288);
        bar_arrive(14, 256);
    } else {
        if (tid == 32) {
            for (int i = 0; i < 16; i++) mbar_init(smem_u32(&ms.kv[i]), 1);
            for (int i = 0; i < 8; i++) { mbar_init(smem_u32(&ms.wo[i]), 2); mbar_init(smem_u32(&ms.a3[i]), 1); }
            mbar_init(smem_u32(&ms.moe), 16);
            for (int i = 0; i < 16; i++) ms.freed[i] = 0;
            for (int i = 0; i < 8; i++) ms.seq[i] = 0;
            ms.item = 4;
            mbar_init(smem_u32(&ms.qbar), 1);
            asm volatile("fence.mbarrier_init.release.cluster;" ::: "memory");
        }
        if (tid >= 64 && tid < 76) ms.norm[tid - 64] = 0;
        if (tid >= 96 && tid < 101) {
            const CUtensorMap* tm = tid == 96 ? &tmO : tid == 97 ? &tmWo : tid == 98 ? &tmG : tid == 99 ? &tmU : &tmOut;
            asm volatile("prefetch.tensormap [%0];" ::"l"(tm) : "memory");
        }
        if (tid == 416) ms.tag = __ldcg(&gEpoch) + 1u;
    }

    if (wg < 2) {
        asm volatile("setmaxnreg.inc.sync.aligned.u32 160;");
        float acc[96];
#pragma unroll
        for (int i = 0; i < 96; i++) acc[i] = 0.f;
        bar_sync(13, 288);
#pragma unroll 1
        for (int kc = 0; kc < 8; kc++) {
            const int s = kc % P1_STAGES;
            mbar_wait(smem_u32(&ms.p1_full[s]), (kc / P1_STAGES) & 1);
            if (tid == 0) TS(24 + kc);
            const uint32_t sa = smem_u32(smem + s * P1_STAGE_BYTES), sb = sa + 16384;
            const uint64_t da = make_desc(sa + wg * 8192, 16, 1024, 1);
            const uint64_t db = make_desc(sb, 8192, 1024, 1);
            wg_fence();
#pragma unroll
            for (int ks = 0; ks < 4; ks++) wgmma_n192(acc, da + ks * 2, db + ks * 128);
            wg_commit();
            wg_wait<0>();
            if (lane == 0) mbar_arrive(smem_u32(&ms.p1_empty[s]));
        }
        pin(acc);
        if (tid == 0) TS(1);
        bar_sync(1, 480);
        const unsigned int tag = ms.tag;
        if (tid == 0) TS(16);
        const int lr0 = wg * 64 + w4 * 16 + g, lr1 = lr0 + 8;
        const float mu0 = ms.p1.mu[lr0], mu1 = ms.p1.mu[lr1], rs0 = ms.p1.rs[lr0], rs1 = ms.p1.rs[lr1];
        const int lg0 = wg * 8 + w4 * 2;
        const int rg0 = rb * 16 + lg0;
#pragma unroll
        for (int hh = 0; hh < 4; hh++) {
            const int head = hg * 4 + hh;
            float nrm[3];
#pragma unroll
            for (int sec = 0; sec < 3; sec++) {
                float sq0 = 0.f, sq1 = 0.f, vm = 0.f;
#pragma unroll
                for (int db = 0; db < 2; db++) {
                    const int j = sec * 8 + hh * 2 + db;
                    const float2 c = *reinterpret_cast<const float2*>(&ms.p1.cs[j * 8 + 2 * t4]);
                    const float f0 = sec == 0 ? rs0 * QSCALE : rs0, f1 = sec == 0 ? rs1 * QSCALE : rs1;
                    const float a0 = (acc[4 * j + 0] - mu0 * c.x) * f0, a1 = (acc[4 * j + 1] - mu0 * c.y) * f0;
                    const float b0 = (acc[4 * j + 2] - mu1 * c.x) * f1, b1 = (acc[4 * j + 3] - mu1 * c.y) * f1;
                    const uint32_t pa = sec < 2 ? pack_f16_sat(a0, a1) : pack_bf16(a0, a1);
                    const uint32_t pb = sec < 2 ? pack_f16_sat(b0, b1) : pack_bf16(b0 * VSCALE_ODD, b1 * VSCALE_ODD);
                    if (sec < 2) {
                        uint32_t* dst = sec == 0 ? reinterpret_cast<uint32_t*>(gQ) + ((size_t)head * S_LEN * DH + rg0 * 128) / 2
                                                 : reinterpret_cast<uint32_t*>(gKV) + (size_t)(head * 16 + rb) * 2048 + lg0 * 64;
                        dst[db * 32 + lane] = pa;
                        dst[64 + db * 32 + lane] = pb;
                        sq0 = fmaf(a0, a0, fmaf(a1, a1, sq0));
                        sq1 = fmaf(b0, b0, fmaf(b1, b1, sq1));
                    } else {
                        uint32_t* dst = reinterpret_cast<uint32_t*>(gKV) + (size_t)(head * 16 + rb) * 2048 + 1024 + db * 512 + lg0 * 32;
                        dst[lane] = pa;
                        dst[32 + lane] = pb;
                        vm = fmaxf(vm, fmaxf(fmaxf(fabsf(a0), fabsf(a1)), fmaxf(fabsf(b0), fabsf(b1))));
                        if (!(a0 + a1 + b0 + b1 == a0 + a1 + b0 + b1)) vm = __int_as_float(0x7f800000);
                    }
                }
                if (sec < 2) {
                    sq0 += __shfl_xor_sync(0xffffffffu, sq0, 1); sq0 += __shfl_xor_sync(0xffffffffu, sq0, 2);
                    sq1 += __shfl_xor_sync(0xffffffffu, sq1, 1); sq1 += __shfl_xor_sync(0xffffffffu, sq1, 2);
                    vm = fmaxf(sq0, sq1);
                    if (!(sq0 + sq1 < 3.0e38f)) vm = __int_as_float(0x7f800000);
                }
                nrm[sec] = vm;
            }
            const unsigned int a = __reduce_max_sync(0xffffffffu, __float_as_uint(nrm[0]));
            const unsigned int b = __reduce_max_sync(0xffffffffu, __float_as_uint(nrm[1]));
            const unsigned int c = __reduce_max_sync(0xffffffffu, __float_as_uint(nrm[2]));
            if (lane == 0) { atomicMax(&ms.norm[hh * 3 + 0], a); atomicMax(&ms.norm[hh * 3 + 1], b); atomicMax(&ms.norm[hh * 3 + 2], c); }
        }
        if (tid == 0) TS(17);
        bar_sync(2, 256);
        if (tid == 0) TS(18);
        if (tid < 12) gNorm[(rb * NH + hg * 4 + tid / 3) * 4 + tid % 3] = __uint_as_float(ms.norm[tid]);
        __syncwarp();
        if (tid == 0) { st_flag(&gFlagQKV[(hg * 16 + rb) * 8], tag); TS(2); }
        asm volatile("setmaxnreg.dec.sync.aligned.u32 128;");
        bar_sync(15, 512);
    } else {
      asm volatile("setmaxnreg.dec.sync.aligned.u32 96;");
      if (wg == 2) {
        const int t = tid - 256;
        if (t < 2) reinterpret_cast<uint4*>(gFlagQKV)[(hg * 16 + rb) * 2 + t] = make_uint4(0u, 0u, 0u, 0u);
        bar_sync(14, 256);
        mbar_wait(smem_u32(&ms.p1_full[0]), 0);
        {
            const int row = rb * 128 + hg * 16 + (t >> 3), j = t & 7;
            const uint4* xp = reinterpret_cast<const uint4*>(x + (size_t)row * DM);
            uint4 v[8];
#pragma unroll
            for (int i = 0; i < 8; i++) v[i] = __ldg(xp + i * 8 + j);
            float s1 = 0.f;
#pragma unroll
            for (int i = 0; i < 8; i++) {
                const uint32_t w[4] = {v[i].x, v[i].y, v[i].z, v[i].w};
#pragma unroll
                for (int e = 0; e < 4; e++) s1 += bf_lo(w[e]) + bf_hi(w[e]);
            }
            s1 += __shfl_xor_sync(0xffffffffu, s1, 1); s1 += __shfl_xor_sync(0xffffffffu, s1, 2); s1 += __shfl_xor_sync(0xffffffffu, s1, 4);
            const float mu = s1 * (1.f / DM);
            float s2 = 0.f;
#pragma unroll
            for (int i = 0; i < 8; i++) {
                const uint32_t w[4] = {v[i].x, v[i].y, v[i].z, v[i].w};
#pragma unroll
                for (int e = 0; e < 4; e++) {
                    const float a = bf_lo(w[e]) - mu, b = bf_hi(w[e]) - mu;
                    s2 = fmaf(a, a, fmaf(b, b, s2));
                }
            }
            s2 += __shfl_xor_sync(0xffffffffu, s2, 1); s2 += __shfl_xor_sync(0xffffffffu, s2, 2); s2 += __shfl_xor_sync(0xffffffffu, s2, 4);
            bar_sync(11, 224);
            if (j == 0) st_pkt(&gStat1[row], make_uint4(__float_as_uint(mu), __float_as_uint(rsqrtf(s2 * (1.f / DM) + LN_EPS)), 0u, ms.tag));
        }
        const unsigned int tag = ms.tag;
        if (t == 0) TS(32);
        uint4 st[1];
        if (t < 8) wait_pkts<1, 0xffffffffu>(&gStat1[rb * 128 + t * 16 + 15], 0, tag, st);
        bar_sync(12, 128);
        wait_pkts<1, 0xffffffffu>(&gStat1[rb * 128 + t], 0, tag, st);
        if (t == 0) TS(34);
        ms.p1.mu[t] = __uint_as_float(st[0].x);
        ms.p1.rs[t] = __uint_as_float(st[0].y);
        bar_arrive(1, 480);
        {
            const uint4 z = make_uint4(0u, 0u, 0u, 0u);
            if (t < 64) { gCand[cta * 64 + t] = z; gPart[cta * 64 + t] = z; gCandRow[cta * 64 + t] = z; }
            gYPart[cta * 224 + t] = z;
            if (t < 96) gYPart[cta * 224 + 128 + t] = z;
            if (t < 2) {
                reinterpret_cast<uint4*>(gFlagO)[cta * 2 + t] = z;
                reinterpret_cast<uint4*>(gFlagOut)[cta * 2 + t] = z;
            }
        }
      } else if (warp == 12) {
        if (lane == 0) {
#pragma unroll 1
            for (int kc = 0; kc < 8; kc++) {
                const int s = kc % P1_STAGES;
                if (kc >= P1_STAGES) mbar_wait(smem_u32(&ms.p1_empty[s]), 0);
                const uint32_t bar = smem_u32(&ms.p1_full[s]);
                const uint32_t sa = smem_u32(smem + s * P1_STAGE_BYTES), sb = sa + 16384;
                mbar_expect_tx(bar, P1_STAGE_BYTES);
                tma_2d(sa, &tmX, kc * 64, rb * 128, bar);
#pragma unroll
                for (int p = 0; p < 3; p++) tma_2d(sb + p * 8192, &tmW, p * 512 + hg * 64, kc * 64, bar);
            }
        }
      } else {
        const int t = tid - 416;
        bar_sync(14, 256);
        mbar_wait(smem_u32(&ms.p1_full[0]), 0);
        const int c16 = t >> 2, rs = t & 3;
        const __nv_bfloat16* wp = wqkv + (size_t)(rb * 32 + rs) * (3 * DM) + (c16 >> 3) * 512 + hg * 64 + (c16 & 7) * 8;
        uint4 v[8];
#pragma unroll
        for (int i = 0; i < 8; i++) v[i] = __ldg(reinterpret_cast<const uint4*>(wp + (size_t)i * 4 * (3 * DM)));
        float a[8] = {};
#pragma unroll
        for (int i = 0; i < 8; i++) {
            a[0] += bf_lo(v[i].x); a[1] += bf_hi(v[i].x); a[2] += bf_lo(v[i].y); a[3] += bf_hi(v[i].y);
            a[4] += bf_lo(v[i].z); a[5] += bf_hi(v[i].z); a[6] += bf_lo(v[i].w); a[7] += bf_hi(v[i].w);
        }
#pragma unroll
        for (int e = 0; e < 8; e++) { a[e] += __shfl_xor_sync(0xffffffffu, a[e], 1); a[e] += __shfl_xor_sync(0xffffffffu, a[e], 2); }
        bar_sync(11, 224);
        const unsigned int tag = ms.tag;
        const int pk = c16 * 2 + rs;
        if (rs < 2) st_pkt(&gCsPart[(hg * 16 + rb) * 48 + pk], embed_tag(rs ? a[4] : a[0], rs ? a[5] : a[1], rs ? a[6] : a[2], rs ? a[7] : a[3], tag));
        if (t == 0) TS(35);
        if (t < 16) { uint4 gate[1]; wait_pkts4<1>(&gCsPart[(hg * 16 + t) * 48 + 47], 0, tag, gate); }
        bar_sync(8, 96);
        if (t == 0) TS(36);
        if (rs < 2) {
            uint4 p[16];
            wait_pkts4<16>(&gCsPart[hg * 16 * 48 + pk], 48, tag, p);
            float s0 = 0.f, s1 = 0.f, s2 = 0.f, s3 = 0.f;
#pragma unroll
            for (int i = 0; i < 16; i++) {
                s0 += __uint_as_float(p[i].x); s1 += __uint_as_float(p[i].y); s2 += __uint_as_float(p[i].z); s3 += __uint_as_float(p[i].w);
            }
            *reinterpret_cast<float4*>(&ms.p1.cs[pk * 4]) = make_float4(s0, s1, s2, s3);
            if (t == 0) TS(37);
        }
        __syncwarp();
        bar_arrive(1, 480);
      }
      __syncwarp();
      bar_sync(15, 512);
      asm volatile("setmaxnreg.inc.sync.aligned.u32 128;");
    }
    if (tid == 0) TS(20);
    const unsigned int tag = ms.tag;

    const int head = hg * 4 + (rb >> 2), quarter = rb & 3;
    {
#pragma unroll
        for (int i = 0; i < 4; i++) {
            const int e = tid + i * 512;
            *reinterpret_cast<uint4*>(smem + (e >> 7) * KV_CHUNK + 8192 + (e & 127) * 16) = make_uint4((e & 8) ? 0x00003F35u : 0x00003F80u, 0, 0, 0);
        }
        asm volatile("fence.proxy.async.shared::cta;" ::: "memory");
    }
    if (warp == 0) {
        if (lane < 16) wait_flag(&gFlagQKV[(hg * 16 + lane) * 8], tag);
        __syncwarp();
        if (lane == 0) TS(21);
    }
    __syncthreads();
    if (lane == 0) {
        fence_proxy_async_global();
        if (warp == 1) {
            mbar_expect_tx(smem_u32(&ms.qbar), 16384);
            bulk_g2s(smem_u32(smem + SM_Q), reinterpret_cast<const char*>(gQ) + (size_t)head * 65536 + quarter * 16384, 16384, smem_u32(&ms.qbar));
        }
        const uint32_t bar = smem_u32(&ms.kv[warp]);
        mbar_expect_tx(bar, 8192);
        bulk_g2s(smem_u32(smem + warp * KV_CHUNK), reinterpret_cast<const char*>(gKV) + (size_t)(head * 16 + warp) * 8192, 8192, bar);
    }
    if (warp == 0) {
        const float4 n = __ldcg(reinterpret_cast<const float4*>(&gNorm[((lane & 15) * NH + head) * 4]));
        const float q2 = __uint_as_float(__reduce_max_sync(0xffffffffu, __float_as_uint(n.x)));
        const float k2 = __uint_as_float(__reduce_max_sync(0xffffffffu, __float_as_uint(n.y)));
        const float vm = __uint_as_float(__reduce_max_sync(0xffffffffu, __float_as_uint(n.z)));
        if (lane == 0) ms.fast = (q2 * k2 * 1.02f <= 812.f) && (q2 <= 1.0e6f) && (k2 <= 1.0e6f) && (vm <= 1.0e18f) && (vm >= 1.0e-18f || vm == 0.f);
    }
    __syncthreads();
    if (tid == 0) TS(3);
    {
        const bool fast = ms.fast != 0;
        const uint64_t descK0 = make_desc(smem_u32(smem), 128, 256, 0);
        const uint64_t descKe = make_desc(smem_u32(smem), 128, 512, 0);
        const uint64_t descKo = make_desc(smem_u32(smem) + 256, 128, 512, 0);
        const uint64_t descV0 = make_desc(smem_u32(smem + 4096), 128, 2048, 0);
        auto release_chunk = [&](int j) {
            if (lane == 0) {
                unsigned int old;
                asm volatile("atom.acq_rel.cta.shared.add.u32 %0, [%1], 1;" : "=r"(old) : "r"(smem_u32(&ms.freed[j])) : "memory");
                if (old == 31) {
                    const uint32_t dst = smem_u32(smem + j * KV_CHUNK);
                    const uint32_t wb = smem_u32(&ms.wo[j >> 1]);
                    mbar_expect_tx(wb, 8192);
                    tma_2d(dst, &tmWo, (cta & 3) * 128 + (j & 1) * 64, (j >> 1) * 64, wb);
                    const uint32_t mb = smem_u32(&ms.moe);
                    if (cta < NFFN) {
                        mbar_expect_tx(mb, 2048);
                        tma_2d(dst + 8192, (j & 8) ? &tmU : &tmG, cta * 16, (j & 7) * 64, mb);
                    }
                }
            }
            __syncwarp();
        };
        float* sAcc = reinterpret_cast<float*>(smem + SM_A3);
        const int t128 = tid & 127;
        mbar_wait(smem_u32(&ms.qbar), 0);
        int item = wg;
#pragma unroll 1
        while (item < 32) {
            const int r = item >> 3, t = item & 7;
            if (t128 == 0) ms.nxt[wg] = atomicAdd(&ms.item, 1);
            if (r > 0) {
                int it = 0;
                unsigned int sq;
                while (true) {
                    asm volatile("ld.acquire.cta.shared.u32 %0, [%1];" : "=r"(sq) : "r"(smem_u32(&ms.seq[t])) : "memory");
                    if (sq >= (unsigned int)r) break;
                    if (++it > SPIN_LIMIT) __trap();
                }
            }
            uint32_t q[4];
            {
                const uint32_t* Qs = reinterpret_cast<const uint32_t*>(smem + SM_Q + t * 2048 + w4 * 512);
                q[0] = Qs[lane]; q[2] = Qs[32 + lane]; q[1] = Qs[64 + lane]; q[3] = Qs[96 + lane];
            }
            float* st = sAcc + t * (12 * 128) + t128;
            float o[12];
#pragma unroll
            for (int i = 0; i < 8; i++) o[i] = r > 0 ? st[i * 128] : 0.f;
            o[8] = r > 0 ? st[8 * 128] : 0.f; o[10] = r > 0 ? st[9 * 128] : 0.f; o[9] = 0.f; o[11] = 0.f;
            if (fast) {
#pragma unroll 1
                for (int j = 4 * r; j < 4 * r + 4; j++) {
                    mbar_wait(smem_u32(&ms.kv[j]), 0);
                    float s[32];
                    uint32_t h[16];
                    wg_fence();
                    wgmma_qk64_f32(s, q, descKe + (uint64_t)(j * (KV_CHUNK >> 4)));
                    wgmma_qk64_f16(h, q, descKo + (uint64_t)(j * (KV_CHUNK >> 4)));
                    wg_commit();
                    wg_wait<0>();
                    pin(s);
                    pin(h);
                    if (j > 4 * r) release_chunk(j - 1);
#pragma unroll
                    for (int kg = 0; kg < 4; kg++) {
                        uint32_t p[8];
#pragma unroll
                        for (int u = 0; u < 2; u++) {
                            const int k = kg * 2 + u;
                            p[4 * u + 0] = pack_bf16(ex2_mufu(s[4 * k]), ex2_mufu(s[4 * k + 1]));
                            p[4 * u + 1] = pack_bf16(ex2_mufu(s[4 * k + 2]), ex2_mufu(s[4 * k + 3]));
                            p[4 * u + 2] = ex2_pair_h16(h[2 * k]);
                            p[4 * u + 3] = ex2_pair_h16(h[2 * k + 1]);
                        }
                        wg_fence();
#pragma unroll
                        for (int u = 0; u < 2; u++)
                            wgmma_pv24(o, p[4 * u], p[4 * u + 1], p[4 * u + 2], p[4 * u + 3],
                                       descV0 + (uint64_t)(j * (KV_CHUNK >> 4) + (kg * 2 + u) * 16));
                        wg_commit();
                        wg_wait<2>();
                    }
                }
                wg_wait<0>();
                pin(o);
            } else {
                float m0 = r > 0 ? st[10 * 128] : -INFINITY, m1 = r > 0 ? st[11 * 128] : -INFINITY;
#pragma unroll 1
                for (int jh = 8 * r; jh < 8 * r + 8; jh++) {
                    const int j = jh >> 1;
                    mbar_wait(smem_u32(&ms.kv[j]), 0);
                    float s[32];
                    const uint32_t off = j * (KV_CHUNK >> 4);
                    wg_fence();
                    wgmma_qk64_f32(s, q, descK0 + (uint64_t)(off + (jh & 1) * 128));
                    wg_commit();
                    wg_wait<0>();
                    pin(s);
                    pin(o);
                    if ((jh & 1) == 0 && j > 4 * r) release_chunk(j - 1);
                    float n0 = m0, n1 = m1;
#pragma unroll
                    for (int i = 0; i < 8; i++) {
                        n0 = fmaxf(n0, fmaxf(s[4 * i], s[4 * i + 1]));
                        n1 = fmaxf(n1, fmaxf(s[4 * i + 2], s[4 * i + 3]));
                    }
                    n0 = fmaxf(n0, __shfl_xor_sync(0xffffffffu, n0, 1)); n0 = fmaxf(n0, __shfl_xor_sync(0xffffffffu, n0, 2));
                    n1 = fmaxf(n1, __shfl_xor_sync(0xffffffffu, n1, 1)); n1 = fmaxf(n1, __shfl_xor_sync(0xffffffffu, n1, 2));
                    const float a0 = ex2_mufu(m0 - n0), a1 = ex2_mufu(m1 - n1);
                    m0 = n0; m1 = n1;
#pragma unroll
                    for (int i = 0; i < 3; i++) { o[4 * i] *= a0; o[4 * i + 1] *= a0; o[4 * i + 2] *= a1; o[4 * i + 3] *= a1; }
                    const float e0 = n0 - LOG2C_ODD, e1 = n1 - LOG2C_ODD;
#pragma unroll
                    for (int k = 0; k < 4; k++) {
                        const uint32_t p0 = pack_bf16(ex2_mufu(s[8 * k] - n0), ex2_mufu(s[8 * k + 1] - n0));
                        const uint32_t p1 = pack_bf16(ex2_mufu(s[8 * k + 2] - n1), ex2_mufu(s[8 * k + 3] - n1));
                        const uint32_t p2 = pack_bf16(ex2_mufu(s[8 * k + 4] - e0), ex2_mufu(s[8 * k + 5] - e0));
                        const uint32_t p3 = pack_bf16(ex2_mufu(s[8 * k + 6] - e1), ex2_mufu(s[8 * k + 7] - e1));
                        wg_fence();
                        wgmma_pv24(o, p0, p1, p2, p3, descV0 + (uint64_t)(off + ((jh & 1) * 4 + k) * 16));
                        wg_commit();
                        wg_wait<0>();
                    }
                }
                st[10 * 128] = m0; st[11 * 128] = m1;
            }
            release_chunk(4 * r + 3);
            if (r < 3) {
#pragma unroll
                for (int i = 0; i < 8; i++) st[i * 128] = o[i];
                st[8 * 128] = o[8]; st[9 * 128] = o[10];
            } else {
                const float l0 = __shfl_sync(0xffffffffu, o[8], lane & ~3), l1 = __shfl_sync(0xffffffffu, o[10], lane & ~3);
                const float r0 = __fdividef(1.f, l0), r1 = __fdividef(1.f, l1);
                uint32_t* Op = reinterpret_cast<uint32_t*>(gO + (size_t)(quarter * 512 + t * 64 + w4 * 16) * DM + head * DH);
                Op[g * 256 + t4] = pack_bf16(o[0] * r0, o[1] * r0);
                Op[(g + 8) * 256 + t4] = pack_bf16(o[2] * r1, o[3] * r1);
                Op[g * 256 + 4 + t4] = pack_bf16(o[4] * r0, o[5] * r0);
                Op[(g + 8) * 256 + 4 + t4] = pack_bf16(o[6] * r1, o[7] * r1);
            }
            bar_sync(3 + wg, 128);
            if (t128 == 0) asm volatile("st.release.cta.shared.u32 [%0], %1;" ::"r"(smem_u32(&ms.seq[t])), "r"(r + 1) : "memory");
            if (item == 8 + wg && tid == 511) {
                bulk_prefetch_l2(reinterpret_cast<const char*>(w_down) + cta * 14336, 14336);
            }
            item = ms.nxt[wg];
            bar_sync(3 + wg, 128);
        }
    }
    __syncthreads();
    if (warp == 0 && lane < 8) { fence_gpu(); asm volatile("st.relaxed.gpu.global.u32 [%0], %1;" ::"l"(&gFlagO[(quarter * 8 + lane) * 32 + head]), "r"(tag) : "memory"); }
    if (tid == 0) TS(4);

    const int rb3 = cta >> 2, cb = cta & 3;
    if (wg < 2) {
        const int r0 = rb3 * 64 + w4 * 16 + g, r1 = r0 + 8;
        const int col0 = cb * 128 + wg * 64 + 2 * t4;
        uint32_t xa[8], xb[8], wr[8];
#pragma unroll
        for (int j = 0; j < 8; j++) {
            xa[j] = __ldg(reinterpret_cast<const uint32_t*>(x + (size_t)r0 * DM + col0 + j * 8));
            xb[j] = __ldg(reinterpret_cast<const uint32_t*>(x + (size_t)r1 * DM + col0 + j * 8));
            wr[j] = __ldg(reinterpret_cast<const uint32_t*>(w_r + col0 + j * 8));
        }
        const float p0 = __bfloat162float(x[(size_t)r0 * DM]), p1 = __bfloat162float(x[(size_t)r1 * DM]);
        const float pivot = __bfloat162float(x[(size_t)(rb3 * 64 + (tid >> 2)) * DM]);
        float wsum = 0.f;
        {
            const uint4 a = __ldg(reinterpret_cast<const uint4*>(w_r) + lane), b = __ldg(reinterpret_cast<const uint4*>(w_r) + 32 + lane);
            const uint32_t w[8] = {a.x, a.y, a.z, a.w, b.x, b.y, b.z, b.w};
#pragma unroll
            for (int e = 0; e < 8; e++) wsum += bf_lo(w[e]) + bf_hi(w[e]);
#pragma unroll
            for (int m = 16; m; m >>= 1) wsum += __shfl_xor_sync(0xffffffffu, wsum, m);
        }
        float acc[32];
#pragma unroll
        for (int i = 0; i < 32; i++) acc[i] = 0.f;
#pragma unroll 1
        for (int kc = 0; kc < 8; kc++) {
            mbar_wait(smem_u32(&ms.wo[kc]), 0);
            mbar_wait(smem_u32(&ms.a3[kc]), 0);
            const uint64_t da = make_desc(smem_u32(smem + SM_A3 + kc * 8192), 16, 1024, 1);
            const uint64_t db = make_desc(smem_u32(smem + (kc * 2 + wg) * KV_CHUNK), 8192, 1024, 1);
            wg_fence();
#pragma unroll
            for (int ks = 0; ks < 4; ks++) wgmma_n64(acc, da + ks * 2, db + ks * 128);
            wg_commit();
        }
        wg_wait<0>();
        pin(acc);
        if (tid == 0) TS(6);
        float s1a = 0.f, s2a = 0.f, s3a = 0.f, s1b = 0.f, s2b = 0.f, s3b = 0.f;
#pragma unroll
        for (int j = 0; j < 8; j++) {
            const uint32_t ha = pack_bf16(bf_lo(xa[j]) + acc[4 * j], bf_hi(xa[j]) + acc[4 * j + 1]);
            const uint32_t hb = pack_bf16(bf_lo(xb[j]) + acc[4 * j + 2], bf_hi(xb[j]) + acc[4 * j + 3]);
            xa[j] = ha; xb[j] = hb;
            const float w0 = bf_lo(wr[j]), w1 = bf_hi(wr[j]);
            const float da0 = bf_lo(ha) - p0, da1 = bf_hi(ha) - p0, db0 = bf_lo(hb) - p1, db1 = bf_hi(hb) - p1;
            s1a += da0 + da1; s2a = fmaf(da0, da0, fmaf(da1, da1, s2a)); s3a = fmaf(da0, w0, fmaf(da1, w1, s3a));
            s1b += db0 + db1; s2b = fmaf(db0, db0, fmaf(db1, db1, s2b)); s3b = fmaf(db0, w0, fmaf(db1, w1, s3b));
        }
#pragma unroll
        for (int m = 1; m <= 2; m <<= 1) {
            s1a += __shfl_xor_sync(0xffffffffu, s1a, m); s2a += __shfl_xor_sync(0xffffffffu, s2a, m); s3a += __shfl_xor_sync(0xffffffffu, s3a, m);
            s1b += __shfl_xor_sync(0xffffffffu, s1b, m); s2b += __shfl_xor_sync(0xffffffffu, s2b, m); s3b += __shfl_xor_sync(0xffffffffu, s3b, m);
        }
        if (t4 == 0) {
            const int lr = w4 * 16 + g;
            ms.p3.part[wg][lr][0] = s1a; ms.p3.part[wg][lr][1] = s2a; ms.p3.part[wg][lr][2] = s3a;
            ms.p3.part[wg][lr + 8][0] = s1b; ms.p3.part[wg][lr + 8][1] = s2b; ms.p3.part[wg][lr + 8][2] = s3b;
        }
        if (tid == 0) TS(11);
        bar_sync(1, 256);
        if (tid == 0) TS(12);
        if (tid < 64) {
            st_pkt(&gPart[(rb3 * 64 + tid) * 4 + cb],
                   make_uint4(__float_as_uint(ms.p3.part[0][tid][0] + ms.p3.part[1][tid][0]), __float_as_uint(ms.p3.part[0][tid][1] + ms.p3.part[1][tid][1]),
                              __float_as_uint(ms.p3.part[0][tid][2] + ms.p3.part[1][tid][2]), tag));
        }
        {
            const int lr = tid >> 2, sl = tid & 3;
            uint4 pv[1];
            wait_pkts<1, 0xffffffffu>(&gPart[rb3 * 256 + tid], 0, tag, pv);
            float s1 = __uint_as_float(pv[0].x), s2 = __uint_as_float(pv[0].y), s3 = __uint_as_float(pv[0].z);
            if (tid == 0) TS(14);
#pragma unroll
            for (int m = 1; m <= 2; m <<= 1) {
                s1 += __shfl_xor_sync(0xffffffffu, s1, m); s2 += __shfl_xor_sync(0xffffffffu, s2, m); s3 += __shfl_xor_sync(0xffffffffu, s3, m);
            }
            if (sl == 0) {
                const float md = s1 * (1.f / DM);
                const float var = fmaxf(s2 * (1.f / DM) - md * md, 0.f);
                const float rs = rsqrtf(var + LN_EPS);
                ms.p3.mu[lr] = pivot + md;
                ms.p3.rs[lr] = rs;
                ms.p3.r[lr] = (s3 - md * wsum) * rs;
            }
        }
        bar_sync(1, 256);
        if (tid == 0) TS(7);
        {
            unsigned int i1, i2;
            warp_top2(f2ord(ms.p3.r[lane]), lane, f2ord(ms.p3.r[lane + 32]), lane + 32, i1, i2);
            if (cb == 0) {
                const int c = tid & 1, li = c ? i2 : i1;
                st_pkt(&gCand[(tid >> 1) * 64 + rb3 * 2 + c],
                       make_uint4(__float_as_uint(ms.p3.r[li]), __float_as_uint(ms.p3.mu[li]), __float_as_uint(ms.p3.rs[li]),
                                  (tag << 11) | (unsigned int)(rb3 * 64 + li)));
            }
#pragma unroll
            for (int c = 0; c < 2; c++) {
                const unsigned int li = c ? i2 : i1;
                if ((int)(li >> 4) == w4 && (int)(li & 7) == g) {
                    const bool hi = (li & 8) != 0;
                    uint4* dst = &gCandRow[(rb3 * 2 + c) * 128 + (cb * 2 + wg) * 16 + t4];
#pragma unroll
                    for (int q = 0; q < 4; q++)
                        st_pkt(dst + q * 4, make_uint4(hi ? xb[2 * q] : xa[2 * q], hi ? xb[2 * q + 1] : xa[2 * q + 1], 0u, tag));
                }
            }
            if (tid == 0) TS(15);
        }
        {
            const int lr0 = w4 * 16 + g;
            const float mu0 = ms.p3.mu[lr0], rs0 = ms.p3.rs[lr0], mu1 = ms.p3.mu[lr0 + 8], rs1 = ms.p3.rs[lr0 + 8];
            char* so = smem + wg * KV_CHUNK;
#pragma unroll
            for (int j = 0; j < 8; j++) {
                const float a0 = bf_lo(xa[j]), a1 = bf_hi(xa[j]), b0 = bf_lo(xb[j]), b1 = bf_hi(xb[j]);
                const uint32_t la = pack_bf16((a0 - mu0) * rs0, (a1 - mu0) * rs0);
                const uint32_t lb = pack_bf16((b0 - mu1) * rs1, (b1 - mu1) * rs1);
                const int o = ((j ^ g) << 4) + t4 * 4;
                *reinterpret_cast<uint32_t*>(so + lr0 * 128 + o) = pack_bf16(a0 + bf_lo(la), a1 + bf_hi(la));
                *reinterpret_cast<uint32_t*>(so + (lr0 + 8) * 128 + o) = pack_bf16(b0 + bf_lo(lb), b1 + bf_hi(lb));
            }
            asm volatile("fence.proxy.async.shared::cta;" ::: "memory");
            bar_sync(3 + wg, 128);
            if ((tid & 127) == 0) {
                tma_store_2d(&tmOut, smem_u32(so), cb * 128 + wg * 64, rb3 * 64);
                asm volatile("cp.async.bulk.wait_group 0;" ::: "memory");
                st_flag(&gFlagOut[cta * 8 + wg], tag);
            }
        }
    } else {
        const int t = tid - 256;
        {
            const int kc = warp - 8;
            if (lane == 0) {
                int it = 0;
                while (true) {
                    const uint4 f = ld_pkt(reinterpret_cast<const uint4*>(&gFlagO[rb3 * 32 + kc * 4]));
                    if (f.x == tag && f.y == tag && f.z == tag && f.w == tag) break;
                    if (++it > SPIN_LIMIT) __trap();
                    BACKOFF();
                }
                if (kc == 7) TS(5);
                fence_proxy_async_global();
                const uint32_t bar = smem_u32(&ms.a3[kc]);
                mbar_expect_tx(bar, 8192);
                tma_2d(smem_u32(smem + SM_A3 + kc * 8192), &tmO, kc * 64, rb3 * 64, bar);
            }
            __syncwarp();
        }
        uint32_t wd[16];
        if (cta < NFFN) {
#pragma unroll
            for (int k = 0; k < 16; k++) wd[k] = __ldg(reinterpret_cast<const uint32_t*>(w_down + (size_t)(cta * 16 + k) * DM + 2 * t));
        }
        if (warp == 8) {
            if (lane == 0) TS(56);
            uint4 cv[2];
            wait_pkts<2, 0xfffff800u>(&gCand[cta * 64 + lane * 2], 1, tag << 11, cv);
            if (lane == 0) TS(54);
            unsigned int i1, i2;
            warp_top2(f2ord(__uint_as_float(cv[0].x)), cv[0].w & 0x7ffu, f2ord(__uint_as_float(cv[1].x)), cv[1].w & 0x7ffu, i1, i2);
#pragma unroll
            for (int c = 0; c < 2; c++) {
                const unsigned int ci = cv[c].w & 0x7ffu;
                if (ci == i1 || ci == i2) {
                    const int o = ci == i1 ? 0 : 1;
                    ms.idx[o] = (int)ci;
                    ms.cslot[o] = lane * 2 + c;
                    *reinterpret_cast<float4*>(&ms.sel[o * 4]) =
                        make_float4(__uint_as_float(cv[c].y), __uint_as_float(cv[c].z), __fdividef(1.f, 1.f + __expf(-__uint_as_float(cv[c].x))), 0.f);
                }
            }
            if (lane == 0) TS(8);
        }
        bar_sync(2, 256);
        const int idx0 = ms.idx[0], idx1 = ms.idx[1];
        if (t == 0 && idx0 >= 0) TS(61);
        float* sX = reinterpret_cast<float*>(smem + SM_A3);
        float* sH = sX + 1024;
        float* sPart = sX + 2048;
        float* sAct = sPart + 512;
        if (cta < NFFN) {
            {
                const int tk = t >> 7, P = t & 127;
                uint4 hv[1];
                wait_pkts<1, 0xffffffffu>(&gCandRow[ms.cslot[tk] * 128 + P], 0, tag, hv);
                if (t == 0) TS(57);
                const float mu = ms.sel[tk * 4], rs = ms.sel[tk * 4 + 1];
                const int col = (P >> 4) * 64 + ((P >> 2) & 3) * 16 + (P & 3) * 2;
                const uint32_t l0 = pack_bf16((bf_lo(hv[0].x) - mu) * rs, (bf_hi(hv[0].x) - mu) * rs);
                const uint32_t l1 = pack_bf16((bf_lo(hv[0].y) - mu) * rs, (bf_hi(hv[0].y) - mu) * rs);
                *reinterpret_cast<float2*>(&sX[tk * 512 + col]) = make_float2(bf_lo(l0), bf_hi(l0));
                *reinterpret_cast<float2*>(&sX[tk * 512 + col + 8]) = make_float2(bf_lo(l1), bf_hi(l1));
                *reinterpret_cast<float2*>(&sH[tk * 512 + col]) = make_float2(bf_lo(hv[0].x), bf_hi(hv[0].x));
                *reinterpret_cast<float2*>(&sH[tk * 512 + col + 8]) = make_float2(bf_lo(hv[0].y), bf_hi(hv[0].y));
            }
            mbar_wait(smem_u32(&ms.moe), 0);
            bar_sync(1 + 8, 256);
            if (t == 0) { asm volatile("" ::: "memory"); sAct[40] = sX[0]; TS(58); }
            {
                const int wv = warp - 8, kk = lane >> 3, cp = lane & 7;
                float a[2][2][2] = {};
#pragma unroll
                for (int i = 0; i < 16; i++) {
                    const int k = wv * 64 + i * 4 + kk;
                    const float x0 = sX[k], x1 = sX[512 + k];
#pragma unroll
                    for (int mat = 0; mat < 2; mat++) {
                        const uint32_t w = *reinterpret_cast<const uint32_t*>(smem + (mat * 8 + wv) * KV_CHUNK + 8192 + (i * 4 + kk) * 32 + cp * 4);
                        a[mat][0][0] = fmaf(x0, bf_lo(w), a[mat][0][0]); a[mat][0][1] = fmaf(x0, bf_hi(w), a[mat][0][1]);
                        a[mat][1][0] = fmaf(x1, bf_lo(w), a[mat][1][0]); a[mat][1][1] = fmaf(x1, bf_hi(w), a[mat][1][1]);
                    }
                }
#pragma unroll
                for (int mat = 0; mat < 2; mat++)
#pragma unroll
                    for (int tk = 0; tk < 2; tk++)
#pragma unroll
                        for (int e = 0; e < 2; e++) {
                            float v = a[mat][tk][e];
                            v += __shfl_xor_sync(0xffffffffu, v, 8);
                            v += __shfl_xor_sync(0xffffffffu, v, 16);
                            if (kk == 0) sPart[(wv * 2 + tk) * 32 + mat * 16 + 2 * cp + e] = v;
                        }
            }
            bar_sync(1 + 8, 256);
            if (t == 0) { sAct[41] = sPart[0]; TS(59); }
            if (t < 32) {
                const int tk = t >> 4, c = t & 15;
                float gs = 0.f, us = 0.f;
#pragma unroll
                for (int w = 0; w < 8; w++) { gs += sPart[(w * 2 + tk) * 32 + c]; us += sPart[(w * 2 + tk) * 32 + 16 + c]; }
                const float gb = bf_round(gs), ub = bf_round(us);
                const float sl = bf_round(__fdividef(gb, 1.f + __expf(-gb)));
                sAct[tk * 16 + c] = bf_round(sl * ub);
            }
            bar_sync(1 + 8, 256);
            {
                float y00 = 0.f, y01 = 0.f, y10 = 0.f, y11 = 0.f;
#pragma unroll
                for (int k = 0; k < 16; k++) {
                    const float a0 = sAct[k], a1 = sAct[16 + k];
                    y00 = fmaf(a0, bf_lo(wd[k]), y00); y01 = fmaf(a0, bf_hi(wd[k]), y01);
                    y10 = fmaf(a1, bf_lo(wd[k]), y10); y11 = fmaf(a1, bf_hi(wd[k]), y11);
                }
                st_pkt(&gYPart[((t >> 2) * NFFN + cta) * 4 + (t & 3)], embed_tag(y00, y01, y10, y11, tag));
            }
            if (t == 0) TS(9);
        }
        if (cta < 64) {
            const int pc = t & 3, part = t >> 2;
            const int opc = (t >> 2) & 3, oe = t & 3, otk = oe >> 1, ocol = (cta * 4 + opc) * 2 + (oe & 1);
            float y[4] = {0.f, 0.f, 0.f, 0.f};
            if (part < 56) {
                uint4 yv[2];
                wait_pkts4<2>(&gYPart[(cta * NFFN + part) * 4 + pc], 56 * 4, tag, yv);
                if (t == 0) TS(60);
                y[0] = __uint_as_float(yv[0].x) + __uint_as_float(yv[1].x); y[1] = __uint_as_float(yv[0].y) + __uint_as_float(yv[1].y);
                y[2] = __uint_as_float(yv[0].z) + __uint_as_float(yv[1].z); y[3] = __uint_as_float(yv[0].w) + __uint_as_float(yv[1].w);
            }
            if (t >= 224 && t < 226) {
                const int orow = (t & 1) ? idx1 : idx0, oc = cta * 8;
                wait_flag(&gFlagOut[((orow >> 6) * 4 + (oc >> 7)) * 8 + ((oc >> 6) & 1)], tag);
            }
            __syncwarp();
#pragma unroll
            for (int e = 0; e < 4; e++) {
                y[e] += __shfl_xor_sync(0xffffffffu, y[e], 4); y[e] += __shfl_xor_sync(0xffffffffu, y[e], 8); y[e] += __shfl_xor_sync(0xffffffffu, y[e], 16);
            }
            float* sR = sAct + 32;
            if (lane < 4) *reinterpret_cast<float4*>(&sR[(warp - 8) * 16 + lane * 4]) = make_float4(y[0], y[1], y[2], y[3]);
            bar_sync(1 + 8, 256);
            if (t < 16) {
                float s = 0.f;
#pragma unroll
                for (int w = 0; w < 8; w++) s += sR[w * 16 + t];
                const float yb = bf_round(bf_round(s) * ms.sel[otk * 4 + 2]);
                out[(size_t)(otk ? idx1 : idx0) * DM + ocol] = __float2bfloat16(sH[otk * 512 + ocol] + bf_round(sX[otk * 512 + ocol] + yb));
            }
            if (cta == 0 && t == 0) {
                *reinterpret_cast<volatile unsigned int*>(&gEpoch) = tag;
            }
            if (t == 0) TS(10);
        }
    }
}

typedef CUresult (*EncodeFn)(CUtensorMap*, CUtensorMapDataType, cuuint32_t, void*, const cuuint64_t*, const cuuint64_t*,
                             const cuuint32_t*, const cuuint32_t*, CUtensorMapInterleave, CUtensorMapSwizzle,
                             CUtensorMapL2promotion, CUtensorMapFloatOOBfill);

void make_map(EncodeFn enc, CUtensorMap* tm, const void* base, uint64_t cols, uint64_t rows, uint32_t box_c, uint32_t box_r, bool swz) {
    cuuint64_t dims[2] = {cols, rows};
    cuuint64_t strides[1] = {cols * 2};
    cuuint32_t box[2] = {box_c, box_r};
    cuuint32_t es[2] = {1, 1};
    enc(tm, CU_TENSOR_MAP_DATA_TYPE_BFLOAT16, 2, const_cast<void*>(base), dims, strides, box, es, CU_TENSOR_MAP_INTERLEAVE_NONE,
        swz ? CU_TENSOR_MAP_SWIZZLE_128B : CU_TENSOR_MAP_SWIZZLE_NONE, CU_TENSOR_MAP_L2_PROMOTION_L2_256B,
        CU_TENSOR_MAP_FLOAT_OOB_FILL_NONE);
}

}

extern "C" void kernel_launch(void* const* d_in, const int* in_sizes, int n_in, void* d_out, int out_size) {
    const __nv_bfloat16* x = (const __nv_bfloat16*)d_in[0];
    const __nv_bfloat16* wqkv = (const __nv_bfloat16*)d_in[1];
    const __nv_bfloat16* wo = (const __nv_bfloat16*)d_in[2];
    const __nv_bfloat16* w_r = (const __nv_bfloat16*)d_in[4];
    const __nv_bfloat16* w_gate = (const __nv_bfloat16*)d_in[5];
    const __nv_bfloat16* w_up = (const __nv_bfloat16*)d_in[6];
    const __nv_bfloat16* w_down = (const __nv_bfloat16*)d_in[7];
    __nv_bfloat16* out = (__nv_bfloat16*)d_out;

    static EncodeFn enc = nullptr;
    static void* pO = nullptr;
    if (!enc) {
        void* fn = nullptr;
        cudaDriverEntryPointQueryResult qr;
        cudaGetDriverEntryPoint("cuTensorMapEncodeTiled", &fn, cudaEnableDefault, &qr);
        enc = (EncodeFn)fn;
        cudaGetSymbolAddress(&pO, gO);
        cudaFuncSetAttribute(mega_kernel, cudaFuncAttributeMaxDynamicSharedMemorySize, SMEM_TOTAL);
    }
    CUtensorMap tmX, tmW, tmO, tmWo, tmG, tmU, tmOut;
    make_map(enc, &tmX, x, DM, S_LEN, 64, 128, true);
    make_map(enc, &tmW, wqkv, 3 * DM, DM, 64, 64, true);
    make_map(enc, &tmO, pO, DM, S_LEN, 64, 64, true);
    make_map(enc, &tmWo, wo, DM, DM, 64, 64, true);
    make_map(enc, &tmG, w_gate, FF, DM, 16, 64, false);
    make_map(enc, &tmU, w_up, FF, DM, 16, 64, false);
    make_map(enc, &tmOut, out, DM, S_LEN, 64, 64, true);

    mega_kernel<<<128, 512, SMEM_TOTAL, cudaStreamPerThread>>>(tmX, tmW, tmO, tmWo, tmG, tmU, tmOut, x, wqkv, wo, w_r, w_gate, w_up, w_down, out);
}
```

```cpp
#include <cuda_runtime.h>
#include <cuda_bf16.h>
#include <cuda.h>
#include <stdint.h>
#include <type_traits>

namespace {

constexpr int S_LEN = 2048, DM = 512, NH = 32, DH = 16, FF = 1792;
constexpr int NFFN = FF / 16;
constexpr float LN_EPS = 1e-5f;
constexpr float QSCALE = 0.25f * 1.4426950408889634f;

__device__ __align__(1024) __nv_bfloat16 gQ[NH * S_LEN * DH];
__device__ __align__(1024) __nv_bfloat16 gKV[NH * S_LEN * DH * 2];
__device__ __align__(1024) __nv_bfloat16 gO[S_LEN * DM];
__device__ __align__(16) float gNorm[16 * NH * 4];
__device__ unsigned int gEpoch;
__device__ __align__(32) unsigned int gFlagQKV[128 * 8];
__device__ __align__(32) unsigned int gFlagO[32 * 32];
__device__ uint4 gStat1[S_LEN];
__device__ uint4 gCsPart[8 * 16 * 48];
__device__ uint4 gPart[32 * 64 * 4];
__device__ uint4 gCand[128 * 64];
__device__ __align__(32) unsigned int gFlagOut[128 * 8];
__device__ uint4 gCandRow[64 * 128];
__device__ uint4 gYPart[NFFN * 256];

#define TS(slot) do {} while (0)

__device__ __forceinline__ uint32_t smem_u32(const void* p) { return (uint32_t)__cvta_generic_to_shared(p); }
__device__ __forceinline__ void mbar_init(uint32_t bar, uint32_t cnt) {
    asm volatile("mbarrier.init.shared::cta.b64 [%0], %1;" ::"r"(bar), "r"(cnt));
}
__device__ __forceinline__ void mbar_expect_tx(uint32_t bar, uint32_t bytes) {
    asm volatile("mbarrier.arrive.expect_tx.shared::cta.b64 _, [%0], %1;" ::"r"(bar), "r"(bytes) : "memory");
}
__device__ __forceinline__ void mbar_arrive(uint32_t bar) {
    asm volatile("mbarrier.arrive.shared::cta.b64 _, [%0];" ::"r"(bar) : "memory");
}
constexpr int SPIN_LIMIT = 1 << 22;
#define BACKOFF() __nanosleep(32)
__device__ __forceinline__ void mbar_wait(uint32_t bar, uint32_t parity) {
    uint32_t done = 0;
    int it = 0;
    while (true) {
        asm volatile("{.reg .pred p; mbarrier.try_wait.parity.shared::cta.b64 p, [%1], %2; selp.u32 %0, 1, 0, p;}"
                     : "=r"(done) : "r"(bar), "r"(parity) : "memory");
        if (done) break;
        if (++it > SPIN_LIMIT) __trap();
    }
}
__device__ __forceinline__ void bulk_g2s(uint32_t dst, const void* src, uint32_t bytes, uint32_t bar) {
    asm volatile("cp.async.bulk.shared::cluster.global.mbarrier::complete_tx::bytes [%0], [%1], %2, [%3];"
                 ::"r"(dst), "l"(src), "r"(bytes), "r"(bar) : "memory");
}
__device__ __forceinline__ void bulk_prefetch_l2(const void* src, uint32_t bytes) {
    asm volatile("cp.async.bulk.prefetch.L2.global [%0], %1;" ::"l"(src), "r"(bytes) : "memory");
}
__device__ __forceinline__ void tma_2d(uint32_t dst, const CUtensorMap* tm, int c0, int c1, uint32_t bar) {
    asm volatile("cp.async.bulk.tensor.2d.shared::cluster.global.mbarrier::complete_tx::bytes [%0], [%1, {%3, %4}], [%2];"
                 ::"r"(dst), "l"(tm), "r"(bar), "r"(c0), "r"(c1) : "memory");
}
__device__ __forceinline__ void tma_store_2d(const CUtensorMap* tm, uint32_t src, int c0, int c1) {
    asm volatile("cp.async.bulk.tensor.2d.global.shared::cta.bulk_group [%0, {%2, %3}], [%1];" ::"l"(tm), "r"(src), "r"(c0), "r"(c1) : "memory");
    asm volatile("cp.async.bulk.commit_group;" ::: "memory");
}
__device__ __forceinline__ void fence_proxy_async_global() { asm volatile("fence.proxy.async.global;" ::: "memory"); }
__device__ __forceinline__ void fence_gpu() { asm volatile("fence.acq_rel.gpu;" ::: "memory"); }
__device__ __forceinline__ void bar_sync(int id, int n) { asm volatile("bar.sync %0, %1;" ::"r"(id), "r"(n) : "memory"); }
__device__ __forceinline__ void bar_arrive(int id, int n) { asm volatile("bar.arrive %0, %1;" ::"r"(id), "r"(n) : "memory"); }
__device__ __forceinline__ void st_flag(unsigned int* p, unsigned int v) {
    asm volatile("st.release.gpu.global.u32 [%0], %1;" ::"l"(p), "r"(v) : "memory");
}
__device__ __forceinline__ unsigned int ld_flag(const unsigned int* p) {
    unsigned int v;
    asm volatile("ld.relaxed.gpu.global.u32 %0, [%1];" : "=r"(v) : "l"(p) : "memory");
    return v;
}
__device__ __forceinline__ void wait_flag(const unsigned int* p, unsigned int tag) {
    int it = 0;
    while (ld_flag(p) != tag) {
        if (++it > SPIN_LIMIT) __trap();
        BACKOFF();
    }
}
__device__ __forceinline__ void st_pkt(uint4* p, uint4 v) {
    asm volatile("st.relaxed.gpu.global.v4.u32 [%0], {%1,%2,%3,%4};" ::"l"(p), "r"(v.x), "r"(v.y), "r"(v.z), "r"(v.w) : "memory");
}
__device__ __forceinline__ uint4 ld_pkt(const uint4* p) {
    uint4 v;
    asm volatile("ld.relaxed.gpu.global.v4.u32 {%0,%1,%2,%3}, [%4];" : "=r"(v.x), "=r"(v.y), "=r"(v.z), "=r"(v.w) : "l"(p) : "memory");
    return v;
}
template <int N, unsigned int MASK>
__device__ __forceinline__ void wait_pkts(const uint4* p, int stride, unsigned int tag, uint4 (&v)[N]) {
    int it = 0;
    while (true) {
        bool ok = true;
#pragma unroll
        for (int i = 0; i < N; i++) v[i] = ld_pkt(p + (size_t)i * stride);
#pragma unroll
        for (int i = 0; i < N; i++) ok = ok && ((v[i].w & MASK) == tag);
        if (ok) break;
        if (++it > SPIN_LIMIT) __trap();
        BACKOFF();
    }
}
__device__ __forceinline__ uint4 embed_tag(float a, float b, float c, float d, unsigned int tag) {
    return make_uint4((__float_as_uint(a) & ~15u) | (tag & 15u), (__float_as_uint(b) & ~15u) | ((tag >> 4) & 15u),
                      (__float_as_uint(c) & ~15u) | ((tag >> 8) & 15u), (__float_as_uint(d) & ~15u) | ((tag >> 12) & 15u));
}
template <int N>
__device__ __forceinline__ void wait_pkts4(const uint4* p, int stride, unsigned int tag, uint4 (&v)[N]) {
    const unsigned int t16 = tag & 0xffffu;
    int it = 0;
    while (true) {
        bool ok = true;
#pragma unroll
        for (int i = 0; i < N; i++) v[i] = ld_pkt(p + (size_t)i * stride);
#pragma unroll
        for (int i = 0; i < N; i++)
            ok = ok && (((v[i].x & 15u) | ((v[i].y & 15u) << 4) | ((v[i].z & 15u) << 8) | ((v[i].w & 15u) << 12)) == t16);
        if (ok) break;
        if (++it > SPIN_LIMIT) __trap();
        BACKOFF();
    }
}
__device__ __forceinline__ uint64_t make_desc(uint32_t addr, uint32_t lbo, uint32_t sbo, uint32_t mode) {
    return (uint64_t)((addr & 0x3FFFF) >> 4) | ((uint64_t)((lbo & 0x3FFFF) >> 4) << 16) |
           ((uint64_t)((sbo & 0x3FFFF) >> 4) << 32) | ((uint64_t)mode << 62);
}
__device__ __forceinline__ void wg_fence() { asm volatile("wgmma.fence.sync.aligned;" ::: "memory"); }
__device__ __forceinline__ void wg_commit() { asm volatile("wgmma.commit_group.sync.aligned;" ::: "memory"); }
template <int N> __device__ __forceinline__ void wg_wait() { asm volatile("wgmma.wait_group.sync.aligned %0;" ::"n"(N) : "memory"); }
template <int N> __device__ __forceinline__ void pin(uint32_t (&d)[N]) {
#pragma unroll
    for (int i = 0; i < N; i++) asm volatile("" : "+r"(d[i])::"memory");
}
template <int N> __device__ __forceinline__ void pin(float (&d)[N]) {
#pragma unroll
    for (int i = 0; i < N; i++) asm volatile("" : "+f"(d[i])::"memory");
}
__device__ __forceinline__ uint32_t pack_bf16(float lo, float hi) {
    uint32_t r;
    asm("cvt.rn.bf16x2.f32 %0, %1, %2;" : "=r"(r) : "f"(hi), "f"(lo));
    return r;
}
__device__ __forceinline__ float bf_lo(uint32_t v) { return __uint_as_float(v << 16); }
__device__ __forceinline__ float bf_hi(uint32_t v) { return __uint_as_float(v & 0xFFFF0000u); }
__device__ __forceinline__ float bf_round(float v) { return __bfloat162float(__float2bfloat16(v)); }
__device__ __forceinline__ float ex2_mufu(float x) {
    float y;
    asm("ex2.approx.ftz.f32 %0, %1;" : "=f"(y) : "f"(x));
    return y;
}

#define ACC8(d, o) "+f"(d[o + 0]), "+f"(d[o + 1]), "+f"(d[o + 2]), "+f"(d[o + 3]), "+f"(d[o + 4]), "+f"(d[o + 5]), "+f"(d[o + 6]), "+f"(d[o + 7])
#define OUT8(d, o) "=f"(d[o + 0]), "=f"(d[o + 1]), "=f"(d[o + 2]), "=f"(d[o + 3]), "=f"(d[o + 4]), "=f"(d[o + 5]), "=f"(d[o + 6]), "=f"(d[o + 7])

__device__ __forceinline__ void wgmma_n192(float (&d)[96], uint64_t da, uint64_t db) {
    asm volatile(
        "wgmma.mma_async.sync.aligned.m64n192k16.f32.bf16.bf16 "
        "{%0,%1,%2,%3,%4,%5,%6,%7,%8,%9,%10,%11,%12,%13,%14,%15,%16,%17,%18,%19,%20,%21,%22,%23,%24,%25,%26,%27,%28,%29,%30,%31,"
        "%32,%33,%34,%35,%36,%37,%38,%39,%40,%41,%42,%43,%44,%45,%46,%47,%48,%49,%50,%51,%52,%53,%54,%55,%56,%57,%58,%59,%60,%61,%62,%63,"
        "%64,%65,%66,%67,%68,%69,%70,%71,%72,%73,%74,%75,%76,%77,%78,%79,%80,%81,%82,%83,%84,%85,%86,%87,%88,%89,%90,%91,%92,%93,%94,%95},"
        "%96, %97, 1, 1, 1, 0, 1;"
        : ACC8(d, 0), ACC8(d, 8), ACC8(d, 16), ACC8(d, 24), ACC8(d, 32), ACC8(d, 40), ACC8(d, 48), ACC8(d, 56),
          ACC8(d, 64), ACC8(d, 72), ACC8(d, 80), ACC8(d, 88)
        : "l"(da), "l"(db));
}
__device__ __forceinline__ void wgmma_n192_rs(float (&d)[96], const uint32_t* a, uint64_t db) {
    asm volatile(
        "wgmma.mma_async.sync.aligned.m64n192k16.f32.bf16.bf16 "
        "{%0,%1,%2,%3,%4,%5,%6,%7,%8,%9,%10,%11,%12,%13,%14,%15,%16,%17,%18,%19,%20,%21,%22,%23,%24,%25,%26,%27,%28,%29,%30,%31,"
        "%32,%33,%34,%35,%36,%37,%38,%39,%40,%41,%42,%43,%44,%45,%46,%47,%48,%49,%50,%51,%52,%53,%54,%55,%56,%57,%58,%59,%60,%61,%62,%63,"
        "%64,%65,%66,%67,%68,%69,%70,%71,%72,%73,%74,%75,%76,%77,%78,%79,%80,%81,%82,%83,%84,%85,%86,%87,%88,%89,%90,%91,%92,%93,%94,%95},"
        "{%96,%97,%98,%99}, %100, 1, 1, 1, 1;"
        : ACC8(d, 0), ACC8(d, 8), ACC8(d, 16), ACC8(d, 24), ACC8(d, 32), ACC8(d, 40), ACC8(d, 48), ACC8(d, 56),
          ACC8(d, 64), ACC8(d, 72), ACC8(d, 80), ACC8(d, 88)
        : "r"(a[0]), "r"(a[1]), "r"(a[2]), "r"(a[3]), "l"(db));
}
__device__ __forceinline__ void ldsm_x4(uint32_t* r, uint32_t addr) {
    asm volatile("ldmatrix.sync.aligned.m8n8.x4.shared.b16 {%0,%1,%2,%3}, [%4];"
                 : "=r"(r[0]), "=r"(r[1]), "=r"(r[2]), "=r"(r[3]) : "r"(addr) : "memory");
}
__device__ __forceinline__ void wgmma_n64(float (&d)[32], uint64_t da, uint64_t db) {
    asm volatile(
        "wgmma.mma_async.sync.aligned.m64n64k16.f32.bf16.bf16 "
        "{%0,%1,%2,%3,%4,%5,%6,%7,%8,%9,%10,%11,%12,%13,%14,%15,%16,%17,%18,%19,%20,%21,%22,%23,%24,%25,%26,%27,%28,%29,%30,%31},"
        "%32, %33, 1, 1, 1, 0, 1;"
        : ACC8(d, 0), ACC8(d, 8), ACC8(d, 16), ACC8(d, 24)
        : "l"(da), "l"(db));
}
__device__ __forceinline__ void wgmma_qk128(float (&d)[64], const uint32_t (&a)[4], uint64_t db) {
    asm volatile("wgmma.mma_async.sync.aligned.m64n128k16.f32.f16.f16 "
        "{%0,%1,%2,%3,%4,%5,%6,%7,%8,%9,%10,%11,%12,%13,%14,%15,%16,%17,%18,%19,%20,%21,%22,%23,%24,%25,%26,%27,%28,%29,%30,%31,%32,%33,%34,%35,%36,%37,%38,%39,%40,%41,%42,%43,%44,%45,%46,%47,%48,%49,%50,%51,%52,%53,%54,%55,%56,%57,%58,%59,%60,%61,%62,%63}, {%64,%65,%66,%67}, %68, 0, 1, 1, 0;"
        : "=f"(d[0]), "=f"(d[1]), "=f"(d[2]), "=f"(d[3]), "=f"(d[4]), "=f"(d[5]), "=f"(d[6]), "=f"(d[7]), "=f"(d[8]), "=f"(d[9]), "=f"(d[10]), "=f"(d[11]), "=f"(d[12]), "=f"(d[13]), "=f"(d[14]), "=f"(d[15]), "=f"(d[16]), "=f"(d[17]), "=f"(d[18]), "=f"(d[19]), "=f"(d[20]), "=f"(d[21]), "=f"(d[22]), "=f"(d[23]), "=f"(d[24]), "=f"(d[25]), "=f"(d[26]), "=f"(d[27]), "=f"(d[28]), "=f"(d[29]), "=f"(d[30]), "=f"(d[31]), "=f"(d[32]), "=f"(d[33]), "=f"(d[34]), "=f"(d[35]), "=f"(d[36]), "=f"(d[37]), "=f"(d[38]), "=f"(d[39]), "=f"(d[40]), "=f"(d[41]), "=f"(d[42]), "=f"(d[43]), "=f"(d[44]), "=f"(d[45]), "=f"(d[46]), "=f"(d[47]), "=f"(d[48]), "=f"(d[49]), "=f"(d[50]), "=f"(d[51]), "=f"(d[52]), "=f"(d[53]), "=f"(d[54]), "=f"(d[55]), "=f"(d[56]), "=f"(d[57]), "=f"(d[58]), "=f"(d[59]), "=f"(d[60]), "=f"(d[61]), "=f"(d[62]), "=f"(d[63])
        : "r"(a[0]), "r"(a[1]), "r"(a[2]), "r"(a[3]), "l"(db));
}
__device__ __forceinline__ void wgmma_qk64_f32(float (&d)[32], const uint32_t (&a)[4], uint64_t db) {
    asm volatile("wgmma.mma_async.sync.aligned.m64n64k16.f32.f16.f16 "
        "{%0,%1,%2,%3,%4,%5,%6,%7,%8,%9,%10,%11,%12,%13,%14,%15,%16,%17,%18,%19,%20,%21,%22,%23,%24,%25,%26,%27,%28,%29,%30,%31}, {%32,%33,%34,%35}, %36, 0, 1, 1, 0;"
        : "=f"(d[0]), "=f"(d[1]), "=f"(d[2]), "=f"(d[3]), "=f"(d[4]), "=f"(d[5]), "=f"(d[6]), "=f"(d[7]), "=f"(d[8]), "=f"(d[9]), "=f"(d[10]), "=f"(d[11]), "=f"(d[12]), "=f"(d[13]), "=f"(d[14]), "=f"(d[15]), "=f"(d[16]), "=f"(d[17]), "=f"(d[18]), "=f"(d[19]), "=f"(d[20]), "=f"(d[21]), "=f"(d[22]), "=f"(d[23]), "=f"(d[24]), "=f"(d[25]), "=f"(d[26]), "=f"(d[27]), "=f"(d[28]), "=f"(d[29]), "=f"(d[30]), "=f"(d[31])
        : "r"(a[0]), "r"(a[1]), "r"(a[2]), "r"(a[3]), "l"(db));
}
__device__ __forceinline__ void wgmma_qk64_f16(uint32_t (&d)[16], const uint32_t (&a)[4], uint64_t db) {
    asm volatile("wgmma.mma_async.sync.aligned.m64n64k16.f16.f16.f16 "
        "{%0,%1,%2,%3,%4,%5,%6,%7,%8,%9,%10,%11,%12,%13,%14,%15}, {%16,%17,%18,%19}, %20, 0, 1, 1, 0;"
        : "=r"(d[0]), "=r"(d[1]), "=r"(d[2]), "=r"(d[3]), "=r"(d[4]), "=r"(d[5]), "=r"(d[6]), "=r"(d[7]), "=r"(d[8]), "=r"(d[9]), "=r"(d[10]), "=r"(d[11]), "=r"(d[12]), "=r"(d[13]), "=r"(d[14]), "=r"(d[15])
        : "r"(a[0]), "r"(a[1]), "r"(a[2]), "r"(a[3]), "l"(db));
}
__device__ __forceinline__ void wgmma_pv24(float (&o)[12], uint32_t a0, uint32_t a1, uint32_t a2, uint32_t a3, uint64_t desc) {
    asm volatile(
        "wgmma.mma_async.sync.aligned.m64n24k16.f32.bf16.bf16 "
        "{%0,%1,%2,%3,%4,%5,%6,%7,%8,%9,%10,%11}, {%12,%13,%14,%15}, %16, 1, 1, 1, 1;"
        : ACC8(o, 0), "+f"(o[8]), "+f"(o[9]), "+f"(o[10]), "+f"(o[11])
        : "r"(a0), "r"(a1), "r"(a2), "r"(a3), "l"(desc));
}

__device__ __forceinline__ uint32_t ex2_pair_h16(uint32_t x2) {
    uint32_t t, r, f, q;
    asm("add.rn.f16x2 %0, %1, %2;" : "=r"(t) : "r"(x2), "r"(0x661E661Fu));
    asm("sub.rn.f16x2 %0, %1, %2;" : "=r"(r) : "r"(t), "r"(0x661E661Fu));
    asm("sub.rn.f16x2 %0, %1, %2;" : "=r"(f) : "r"(x2), "r"(r));
    asm("fma.rn.f16x2 %0, %1, %2, %3;" : "=r"(q) : "r"(0x15101510u), "r"(f), "r"(0x1d7e1d7eu));
    asm("fma.rn.f16x2 %0, %1, %2, %3;" : "=r"(q) : "r"(q), "r"(f), "r"(0x23d823d8u));
    asm("fma.rn.f16x2 %0, %1, %2, %3;" : "=r"(q) : "r"(q), "r"(f), "r"(0x30823035u));
    return t * 128u + q;
}
constexpr float VSCALE_ODD = 0.70703125f;
constexpr float LOG2C_ODD = 0.50015402f;
__device__ __forceinline__ uint32_t pack_f16_sat(float lo, float hi) {
    uint32_t r;
    asm("cvt.rn.satfinite.f16x2.f32 %0, %1, %2;" : "=r"(r) : "f"(hi), "f"(lo));
    return r;
}
__device__ __forceinline__ unsigned int f2ord(float v) {
    const unsigned int u = __float_as_uint(v);
    const unsigned int o = u ^ ((unsigned int)((int)u >> 31) | 0x80000000u);
    return (v == v) ? o : 0u;
}
__device__ __forceinline__ void warp_top2(unsigned int ka, unsigned int ia, unsigned int kb, unsigned int ib, unsigned int& i1, unsigned int& i2) {
    const unsigned int m1 = __reduce_max_sync(0xffffffffu, max(ka, kb));
    i1 = __reduce_min_sync(0xffffffffu, min(ka == m1 ? ia : 0xffffffffu, kb == m1 ? ib : 0xffffffffu));
    const bool ra = (ia == i1), rb = (ib == i1);
    const unsigned int ka2 = ra ? 0u : ka, kb2 = rb ? 0u : kb, ia2 = ra ? 0xffffffffu : ia, ib2 = rb ? 0xffffffffu : ib;
    const unsigned int m2 = __reduce_max_sync(0xffffffffu, max(ka2, kb2));
    i2 = __reduce_min_sync(0xffffffffu, min(ka2 == m2 ? ia2 : 0xffffffffu, kb2 == m2 ? ib2 : 0xffffffffu));
}

constexpr int P1_STAGES = 5;
constexpr int P1_STAGE_BYTES = 16384 + 24576;
constexpr int KV_CHUNK = 10240;
constexpr int SM_Q = 163840 + 49152;
constexpr int SM_A3 = 163840;
constexpr int SM_MISC = 229376;
constexpr int SMEM_TOTAL = 232448;
struct Misc {
    uint64_t p1_full[P1_STAGES], p1_empty[P1_STAGES];
    uint64_t kv[16];
    uint64_t wo[8], a3[8], moe;
    unsigned int tag;
    int fast;
    int idx[2], cslot[2];
    alignas(16) float sel[8];
    unsigned int norm[12];
    uint64_t qbar;
    int item, nxt[4];
    unsigned int seq[8];
    unsigned int freed[16];
    union alignas(16) {
        struct { float mu[128], rs[128], cs[192]; } p1;
        struct { float part[2][64][3]; float mu[64], rs[64], r[64]; } p3;
    };
};
static_assert(sizeof(Misc) <= SMEM_TOTAL - SM_MISC, "misc smem");

__device__ __forceinline__ void release_kv_chunk(char* smem, Misc& ms, int j, int cta, int lane, const CUtensorMap* tmWo,
                                                 const CUtensorMap* tmG, const CUtensorMap* tmU) {
    if (lane == 0) {
        unsigned int old;
        asm volatile("atom.acq_rel.cta.shared.add.u32 %0, [%1], 1;" : "=r"(old) : "r"(smem_u32(&ms.freed[j])) : "memory");
        if (old == 31) {
            const uint32_t dst = smem_u32(smem + j * KV_CHUNK);
            const uint32_t wb = smem_u32(&ms.wo[j >> 1]);
            mbar_expect_tx(wb, 8192);
            tma_2d(dst, tmWo, (cta & 3) * 128 + (j & 1) * 64, (j >> 1) * 64, wb);
            const uint32_t mb = smem_u32(&ms.moe);
            if (cta < NFFN) {
                mbar_expect_tx(mb, 2048);
                tma_2d(dst + 8192, (j & 8) ? tmU : tmG, cta * 16, (j & 7) * 64, mb);
            }
        }
    }
    __syncwarp();
}

__device__ __forceinline__ void guarded_item(char* smem, Misc& ms, int r, int t, int cta, const CUtensorMap* tmWo, const CUtensorMap* tmG,
                                          const CUtensorMap* tmU) {
    const int tid = threadIdx.x, lane = tid & 31, w4 = (tid >> 5) & 3;
    const uint64_t descK0 = make_desc(smem_u32(smem), 128, 256, 0);
    const uint64_t descV0 = make_desc(smem_u32(smem + 4096), 128, 2048, 0);
    uint32_t q[4];
    {
        const uint32_t* Qs = reinterpret_cast<const uint32_t*>(smem + SM_Q + t * 2048 + w4 * 512);
        q[0] = Qs[lane]; q[2] = Qs[32 + lane]; q[1] = Qs[64 + lane]; q[3] = Qs[96 + lane];
    }
    float* st = reinterpret_cast<float*>(smem + SM_A3) + t * (12 * 128) + (tid & 127);
    float o[12];
#pragma unroll
    for (int i = 0; i < 8; i++) o[i] = r > 0 ? st[i * 128] : 0.f;
    o[8] = r > 0 ? st[8 * 128] : 0.f; o[10] = r > 0 ? st[9 * 128] : 0.f; o[9] = 0.f; o[11] = 0.f;
    float m0 = r > 0 ? st[10 * 128] : -INFINITY, m1 = r > 0 ? st[11 * 128] : -INFINITY;
#pragma unroll 1
    for (int jh = 8 * r; jh < 8 * r + 8; jh++) {
        const int j = jh >> 1;
        mbar_wait(smem_u32(&ms.kv[j]), 0);
        float s[32];
        const uint32_t off = j * (KV_CHUNK >> 4);
        wg_fence();
        wgmma_qk64_f32(s, q, descK0 + (uint64_t)(off + (jh & 1) * 128));
        wg_commit();
        wg_wait<0>();
        pin(s);
        pin(o);
        if ((jh & 1) == 0 && j > 4 * r) release_kv_chunk(smem, ms, j - 1, cta, lane, tmWo, tmG, tmU);
        float n0 = m0, n1 = m1;
#pragma unroll
        for (int i = 0; i < 8; i++) {
            n0 = fmaxf(n0, fmaxf(s[4 * i], s[4 * i + 1]));
            n1 = fmaxf(n1, fmaxf(s[4 * i + 2], s[4 * i + 3]));
        }
        n0 = fmaxf(n0, __shfl_xor_sync(0xffffffffu, n0, 1)); n0 = fmaxf(n0, __shfl_xor_sync(0xffffffffu, n0, 2));
        n1 = fmaxf(n1, __shfl_xor_sync(0xffffffffu, n1, 1)); n1 = fmaxf(n1, __shfl_xor_sync(0xffffffffu, n1, 2));
        const float a0 = ex2_mufu(m0 - n0), a1 = ex2_mufu(m1 - n1);
        m0 = n0; m1 = n1;
#pragma unroll
        for (int i = 0; i < 3; i++) { o[4 * i] *= a0; o[4 * i + 1] *= a0; o[4 * i + 2] *= a1; o[4 * i + 3] *= a1; }
        const float e0 = n0 - LOG2C_ODD, e1 = n1 - LOG2C_ODD;
#pragma unroll
        for (int k = 0; k < 4; k++) {
            const uint32_t p0 = pack_bf16(ex2_mufu(s[8 * k] - n0), ex2_mufu(s[8 * k + 1] - n0));
            const uint32_t p1 = pack_bf16(ex2_mufu(s[8 * k + 2] - n1), ex2_mufu(s[8 * k + 3] - n1));
            const uint32_t p2 = pack_bf16(ex2_mufu(s[8 * k + 4] - e0), ex2_mufu(s[8 * k + 5] - e0));
            const uint32_t p3 = pack_bf16(ex2_mufu(s[8 * k + 6] - e1), ex2_mufu(s[8 * k + 7] - e1));
            wg_fence();
            wgmma_pv24(o, p0, p1, p2, p3, descV0 + (uint64_t)(off + ((jh & 1) * 4 + k) * 16));
            wg_commit();
            wg_wait<0>();
            pin(o);
        }
    }
#pragma unroll
    for (int i = 0; i < 8; i++) st[i * 128] = o[i];
    st[8 * 128] = o[8]; st[9 * 128] = o[10]; st[10 * 128] = m0; st[11 * 128] = m1;
}

__global__ void __launch_bounds__(512, 1)
mega_kernel(const __grid_constant__ CUtensorMap tmX, const __grid_constant__ CUtensorMap tmW,
            const __grid_constant__ CUtensorMap tmO, const __grid_constant__ CUtensorMap tmWo,
            const __grid_constant__ CUtensorMap tmG, const __grid_constant__ CUtensorMap tmU, const __grid_constant__ CUtensorMap tmOut,
            const __nv_bfloat16* __restrict__ x, const __nv_bfloat16* __restrict__ wqkv, const __nv_bfloat16* __restrict__ wo,
            const __nv_bfloat16* __restrict__ w_r, const __nv_bfloat16* __restrict__ w_gate,
            const __nv_bfloat16* __restrict__ w_up, const __nv_bfloat16* __restrict__ w_down,
            __nv_bfloat16* __restrict__ out) {
    extern __shared__ __align__(1024) char smem[];
    Misc& ms = *reinterpret_cast<Misc*>(smem + SM_MISC);
    const int tid = threadIdx.x, lane = tid & 31;
    const int warp = __shfl_sync(0xffffffffu, tid >> 5, 0);
    const int wg = warp >> 2, w4 = warp & 3, g = lane >> 2, t4 = lane & 3;
    const int cta = blockIdx.x;
    const int rb = cta >> 3, hg = cta & 7;

    if (warp == 12) {
        if (lane == 0) {
            TS(0);
            if (smem_u32(smem) & 1023) __trap();
            for (int i = 0; i < P1_STAGES; i++) { mbar_init(smem_u32(&ms.p1_full[i]), 1); mbar_init(smem_u32(&ms.p1_empty[i]), 8); }
            asm volatile("fence.mbarrier_init.release.cluster;" ::: "memory");
        }
        __syncwarp();
        bar_arrive(13, 288);
        bar_arrive(14, 256);
    } else {
        if (tid == 32) {
            for (int i = 0; i < 16; i++) mbar_init(smem_u32(&ms.kv[i]), 1);
            for (int i = 0; i < 8; i++) { mbar_init(smem_u32(&ms.wo[i]), 2); mbar_init(smem_u32(&ms.a3[i]), 1); }
            mbar_init(smem_u32(&ms.moe), 16);
            for (int i = 0; i < 16; i++) ms.freed[i] = 0;
            for (int i = 0; i < 8; i++) ms.seq[i] = 0;
            ms.item = 4;
            mbar_init(smem_u32(&ms.qbar), 1);
            asm volatile("fence.mbarrier_init.release.cluster;" ::: "memory");
        }
        if (tid >= 64 && tid < 76) ms.norm[tid - 64] = 0;
        if (tid >= 96 && tid < 101) {
            const CUtensorMap* tm = tid == 96 ? &tmO : tid == 97 ? &tmWo : tid == 98 ? &tmG : tid == 99 ? &tmU : &tmOut;
            asm volatile("prefetch.tensormap [%0];" ::"l"(tm) : "memory");
        }
        if (tid == 416) ms.tag = __ldcg(&gEpoch) + 1u;
    }

    if (wg < 2) {
        asm volatile("setmaxnreg.inc.sync.aligned.u32 160;");
        float acc[96];
#pragma unroll
        for (int i = 0; i < 96; i++) acc[i] = 0.f;
        bar_sync(13, 288);
#pragma unroll 1
        for (int kc = 0; kc < 8; kc++) {
            const int s = kc % P1_STAGES;
            mbar_wait(smem_u32(&ms.p1_full[s]), (kc / P1_STAGES) & 1);
            if (tid == 0) TS(24 + kc);
            const uint32_t sa = smem_u32(smem + s * P1_STAGE_BYTES), sb = sa + 16384;
            const uint64_t da = make_desc(sa + wg * 8192, 16, 1024, 1);
            const uint64_t db = make_desc(sb, 8192, 1024, 1);
            wg_fence();
#pragma unroll
            for (int ks = 0; ks < 4; ks++) wgmma_n192(acc, da + ks * 2, db + ks * 128);
            wg_commit();
            wg_wait<0>();
            if (lane == 0) mbar_arrive(smem_u32(&ms.p1_empty[s]));
        }
        pin(acc);
        if (tid == 0) TS(1);
        bar_sync(1, 480);
        const unsigned int tag = ms.tag;
        if (tid == 0) TS(16);
        const int lr0 = wg * 64 + w4 * 16 + g, lr1 = lr0 + 8;
        const float mu0 = ms.p1.mu[lr0], mu1 = ms.p1.mu[lr1], rs0 = ms.p1.rs[lr0], rs1 = ms.p1.rs[lr1];
        const int lg0 = wg * 8 + w4 * 2;
        const int rg0 = rb * 16 + lg0;
#pragma unroll
        for (int hh = 0; hh < 4; hh++) {
            const int head = hg * 4 + hh;
            float nrm[3];
#pragma unroll
            for (int sec = 0; sec < 3; sec++) {
                float sq0 = 0.f, sq1 = 0.f, vm = 0.f;
#pragma unroll
                for (int db = 0; db < 2; db++) {
                    const int j = sec * 8 + hh * 2 + db;
                    const float2 c = *reinterpret_cast<const float2*>(&ms.p1.cs[j * 8 + 2 * t4]);
                    const float f0 = sec == 0 ? rs0 * QSCALE : rs0, f1 = sec == 0 ? rs1 * QSCALE : rs1;
                    const float a0 = (acc[4 * j + 0] - mu0 * c.x) * f0, a1 = (acc[4 * j + 1] - mu0 * c.y) * f0;
                    const float b0 = (acc[4 * j + 2] - mu1 * c.x) * f1, b1 = (acc[4 * j + 3] - mu1 * c.y) * f1;
                    const uint32_t pa = sec < 2 ? pack_f16_sat(a0, a1) : pack_bf16(a0, a1);
                    const uint32_t pb = sec < 2 ? pack_f16_sat(b0, b1) : pack_bf16(b0 * VSCALE_ODD, b1 * VSCALE_ODD);
                    if (sec < 2) {
                        uint32_t* dst = sec == 0 ? reinterpret_cast<uint32_t*>(gQ) + ((size_t)head * S_LEN * DH + rg0 * 128) / 2
                                                 : reinterpret_cast<uint32_t*>(gKV) + (size_t)(head * 16 + rb) * 2048 + lg0 * 64;
                        dst[db * 32 + lane] = pa;
                        dst[64 + db * 32 + lane] = pb;
                        sq0 = fmaf(a0, a0, fmaf(a1, a1, sq0));
                        sq1 = fmaf(b0, b0, fmaf(b1, b1, sq1));
                    } else {
                        uint32_t* dst = reinterpret_cast<uint32_t*>(gKV) + (size_t)(head * 16 + rb) * 2048 + 1024 + db * 512 + lg0 * 32;
                        dst[lane] = pa;
                        dst[32 + lane] = pb;
                        vm = fmaxf(vm, fmaxf(fmaxf(fabsf(a0), fabsf(a1)), fmaxf(fabsf(b0), fabsf(b1))));
                        if (!(a0 + a1 + b0 + b1 == a0 + a1 + b0 + b1)) vm = __int_as_float(0x7f800000);
                    }
                }
                if (sec < 2) {
                    sq0 += __shfl_xor_sync(0xffffffffu, sq0, 1); sq0 += __shfl_xor_sync(0xffffffffu, sq0, 2);
                    sq1 += __shfl_xor_sync(0xffffffffu, sq1, 1); sq1 += __shfl_xor_sync(0xffffffffu, sq1, 2);
                    vm = fmaxf(sq0, sq1);
                    if (!(sq0 + sq1 < 3.0e38f)) vm = __int_as_float(0x7f800000);
                }
                nrm[sec] = vm;
            }
            const unsigned int a = __reduce_max_sync(0xffffffffu, __float_as_uint(nrm[0]));
            const unsigned int b = __reduce_max_sync(0xffffffffu, __float_as_uint(nrm[1]));
            const unsigned int c = __reduce_max_sync(0xffffffffu, __float_as_uint(nrm[2]));
            if (lane == 0) { atomicMax(&ms.norm[hh * 3 + 0], a); atomicMax(&ms.norm[hh * 3 + 1], b); atomicMax(&ms.norm[hh * 3 + 2], c); }
        }
        if (tid == 0) TS(17);
        bar_sync(2, 256);
        if (tid == 0) TS(18);
        if (tid < 12) gNorm[(rb * NH + hg * 4 + tid / 3) * 4 + tid % 3] = __uint_as_float(ms.norm[tid]);
        __syncwarp();
        if (tid == 0) { st_flag(&gFlagQKV[(hg * 16 + rb) * 8], tag); TS(2); }
        asm volatile("setmaxnreg.dec.sync.aligned.u32 128;");
        bar_sync(15, 512);
    } else {
      asm volatile("setmaxnreg.dec.sync.aligned.u32 96;");
      if (wg == 2) {
        const int t = tid - 256;
        if (t < 2) reinterpret_cast<uint4*>(gFlagQKV)[(hg * 16 + rb) * 2 + t] = make_uint4(0u, 0u, 0u, 0u);
        bar_sync(14, 256);
        mbar_wait(smem_u32(&ms.p1_full[0]), 0);
        {
            const int row = rb * 128 + hg * 16 + (t >> 3), j = t & 7;
            const uint4* xp = reinterpret_cast<const uint4*>(x + (size_t)row * DM);
            uint4 v[8];
#pragma unroll
            for (int i = 0; i < 8; i++) v[i] = __ldg(xp + i * 8 + j);
            float s1 = 0.f;
#pragma unroll
            for (int i = 0; i < 8; i++) {
                const uint32_t w[4] = {v[i].x, v[i].y, v[i].z, v[i].w};
#pragma unroll
                for (int e = 0; e < 4; e++) s1 += bf_lo(w[e]) + bf_hi(w[e]);
            }
            s1 += __shfl_xor_sync(0xffffffffu, s1, 1); s1 += __shfl_xor_sync(0xffffffffu, s1, 2); s1 += __shfl_xor_sync(0xffffffffu, s1, 4);
            const float mu = s1 * (1.f / DM);
            float s2 = 0.f;
#pragma unroll
            for (int i = 0; i < 8; i++) {
                const uint32_t w[4] = {v[i].x, v[i].y, v[i].z, v[i].w};
#pragma unroll
                for (int e = 0; e < 4; e++) {
                    const float a = bf_lo(w[e]) - mu, b = bf_hi(w[e]) - mu;
                    s2 = fmaf(a, a, fmaf(b, b, s2));
                }
            }
            s2 += __shfl_xor_sync(0xffffffffu, s2, 1); s2 += __shfl_xor_sync(0xffffffffu, s2, 2); s2 += __shfl_xor_sync(0xffffffffu, s2, 4);
            bar_sync(11, 224);
            if (j == 0) st_pkt(&gStat1[row], make_uint4(__float_as_uint(mu), __float_as_uint(rsqrtf(s2 * (1.f / DM) + LN_EPS)), 0u, ms.tag));
        }
        const unsigned int tag = ms.tag;
        if (t == 0) TS(32);
        uint4 st[1];
        if (t < 8) wait_pkts<1, 0xffffffffu>(&gStat1[rb * 128 + t * 16 + 15], 0, tag, st);
        bar_sync(12, 128);
        wait_pkts<1, 0xffffffffu>(&gStat1[rb * 128 + t], 0, tag, st);
        if (t == 0) TS(34);
        ms.p1.mu[t] = __uint_as_float(st[0].x);
        ms.p1.rs[t] = __uint_as_float(st[0].y);
        bar_arrive(1, 480);
        {
            const uint4 z = make_uint4(0u, 0u, 0u, 0u);
            if (t < 64) { gCand[cta * 64 + t] = z; gPart[cta * 64 + t] = z; gCandRow[cta * 64 + t] = z; }
            gYPart[cta * 224 + t] = z;
            if (t < 96) gYPart[cta * 224 + 128 + t] = z;
            if (t < 2) {
                reinterpret_cast<uint4*>(gFlagO)[cta * 2 + t] = z;
                reinterpret_cast<uint4*>(gFlagOut)[cta * 2 + t] = z;
            }
        }
      } else if (warp == 12) {
        if (lane == 0) {
#pragma unroll 1
            for (int kc = 0; kc < 8; kc++) {
                const int s = kc % P1_STAGES;
                if (kc >= P1_STAGES) mbar_wait(smem_u32(&ms.p1_empty[s]), 0);
                const uint32_t bar = smem_u32(&ms.p1_full[s]);
                const uint32_t sa = smem_u32(smem + s * P1_STAGE_BYTES), sb = sa + 16384;
                mbar_expect_tx(bar, P1_STAGE_BYTES);
                tma_2d(sa, &tmX, kc * 64, rb * 128, bar);
#pragma unroll
                for (int p = 0; p < 3; p++) tma_2d(sb + p * 8192, &tmW, p * 512 + hg * 64, kc * 64, bar);
            }
        }
      } else {
        const int t = tid - 416;
        bar_sync(14, 256);
        mbar_wait(smem_u32(&ms.p1_full[0]), 0);
        const int c16 = t >> 2, rs = t & 3;
        const __nv_bfloat16* wp = wqkv + (size_t)(rb * 32 + rs) * (3 * DM) + (c16 >> 3) * 512 + hg * 64 + (c16 & 7) * 8;
        uint4 v[8];
#pragma unroll
        for (int i = 0; i < 8; i++) v[i] = __ldg(reinterpret_cast<const uint4*>(wp + (size_t)i * 4 * (3 * DM)));
        float a[8] = {};
#pragma unroll
        for (int i = 0; i < 8; i++) {
            a[0] += bf_lo(v[i].x); a[1] += bf_hi(v[i].x); a[2] += bf_lo(v[i].y); a[3] += bf_hi(v[i].y);
            a[4] += bf_lo(v[i].z); a[5] += bf_hi(v[i].z); a[6] += bf_lo(v[i].w); a[7] += bf_hi(v[i].w);
        }
#pragma unroll
        for (int e = 0; e < 8; e++) { a[e] += __shfl_xor_sync(0xffffffffu, a[e], 1); a[e] += __shfl_xor_sync(0xffffffffu, a[e], 2); }
        bar_sync(11, 224);
        const unsigned int tag = ms.tag;
        const int pk = c16 * 2 + rs;
        if (rs < 2) st_pkt(&gCsPart[(hg * 16 + rb) * 48 + pk], embed_tag(rs ? a[4] : a[0], rs ? a[5] : a[1], rs ? a[6] : a[2], rs ? a[7] : a[3], tag));
        if (t == 0) TS(35);
        if (t < 16) { uint4 gate[1]; wait_pkts4<1>(&gCsPart[(hg * 16 + t) * 48 + 47], 0, tag, gate); }
        bar_sync(8, 96);
        if (t == 0) TS(36);
        if (rs < 2) {
            uint4 p[16];
            wait_pkts4<16>(&gCsPart[hg * 16 * 48 + pk], 48, tag, p);
            float s0 = 0.f, s1 = 0.f, s2 = 0.f, s3 = 0.f;
#pragma unroll
            for (int i = 0; i < 16; i++) {
                s0 += __uint_as_float(p[i].x); s1 += __uint_as_float(p[i].y); s2 += __uint_as_float(p[i].z); s3 += __uint_as_float(p[i].w);
            }
            *reinterpret_cast<float4*>(&ms.p1.cs[pk * 4]) = make_float4(s0, s1, s2, s3);
            if (t == 0) TS(37);
        }
        __syncwarp();
        bar_arrive(1, 480);
      }
      __syncwarp();
      bar_sync(15, 512);
      asm volatile("setmaxnreg.inc.sync.aligned.u32 128;");
    }
    if (tid == 0) TS(20);
    const unsigned int tag = ms.tag;

    const int head = hg * 4 + (rb >> 2), quarter = rb & 3;
    {
#pragma unroll
        for (int i = 0; i < 4; i++) {
            const int e = tid + i * 512;
            *reinterpret_cast<uint4*>(smem + (e >> 7) * KV_CHUNK + 8192 + (e & 127) * 16) = make_uint4((e & 8) ? 0x00003F35u : 0x00003F80u, 0, 0, 0);
        }
        asm volatile("fence.proxy.async.shared::cta;" ::: "memory");
    }
    if (warp == 0) {
        if (lane < 16) wait_flag(&gFlagQKV[(hg * 16 + lane) * 8], tag);
        __syncwarp();
        if (lane == 0) TS(21);
    }
    __syncthreads();
    if (lane == 0) {
        fence_proxy_async_global();
        if (warp == 1) {
            mbar_expect_tx(smem_u32(&ms.qbar), 16384);
            bulk_g2s(smem_u32(smem + SM_Q), reinterpret_cast<const char*>(gQ) + (size_t)head * 65536 + quarter * 16384, 16384, smem_u32(&ms.qbar));
        }
        const uint32_t bar = smem_u32(&ms.kv[warp]);
        mbar_expect_tx(bar, 8192);
        bulk_g2s(smem_u32(smem + warp * KV_CHUNK), reinterpret_cast<const char*>(gKV) + (size_t)(head * 16 + warp) * 8192, 8192, bar);
    }
    if (warp == 0) {
        const float4 n = __ldcg(reinterpret_cast<const float4*>(&gNorm[((lane & 15) * NH + head) * 4]));
        const float q2 = __uint_as_float(__reduce_max_sync(0xffffffffu, __float_as_uint(n.x)));
        const float k2 = __uint_as_float(__reduce_max_sync(0xffffffffu, __float_as_uint(n.y)));
        const float vm = __uint_as_float(__reduce_max_sync(0xffffffffu, __float_as_uint(n.z)));
        if (lane == 0) ms.fast = (q2 * k2 * 1.02f <= 812.f) && (q2 <= 1.0e6f) && (k2 <= 1.0e6f) && (vm <= 1.0e18f) && (vm >= 1.0e-18f || vm == 0.f);
    }
    __syncthreads();
    if (tid == 0) TS(3);
    {
        const bool fast = ms.fast != 0;
        const uint64_t descKe = make_desc(smem_u32(smem), 128, 512, 0);
        const uint64_t descKo = make_desc(smem_u32(smem) + 256, 128, 512, 0);
        const uint64_t descV0 = make_desc(smem_u32(smem + 4096), 128, 2048, 0);
        auto release_chunk = [&](int j) { release_kv_chunk(smem, ms, j, cta, lane, &tmWo, &tmG, &tmU); };
        float* sAcc = reinterpret_cast<float*>(smem + SM_A3);
        const int t128 = tid & 127;
        mbar_wait(smem_u32(&ms.qbar), 0);
        auto run_items = [&](auto FAST) {
        int item = wg;
#pragma unroll 1
        while (item < 32) {
            const int r = item >> 3, t = item & 7;
            if (t128 == 0) ms.nxt[wg] = atomicAdd(&ms.item, 1);
            if (r > 0) {
                int it = 0;
                unsigned int sq;
                while (true) {
                    asm volatile("ld.acquire.cta.shared.u32 %0, [%1];" : "=r"(sq) : "r"(smem_u32(&ms.seq[t])) : "memory");
                    if (sq >= (unsigned int)r) break;
                    if (++it > SPIN_LIMIT) __trap();
                }
            }
            uint32_t q[4];
            {
                const uint32_t* Qs = reinterpret_cast<const uint32_t*>(smem + SM_Q + t * 2048 + w4 * 512);
                q[0] = Qs[lane]; q[2] = Qs[32 + lane]; q[1] = Qs[64 + lane]; q[3] = Qs[96 + lane];
            }
            float* st = sAcc + t * (12 * 128) + t128;
            float o[12];
#pragma unroll
            for (int i = 0; i < 8; i++) o[i] = r > 0 ? st[i * 128] : 0.f;
            o[8] = r > 0 ? st[8 * 128] : 0.f; o[10] = r > 0 ? st[9 * 128] : 0.f; o[9] = 0.f; o[11] = 0.f;
            if constexpr (decltype(FAST)::value) {
#pragma unroll 1
                for (int j = 4 * r; j < 4 * r + 4; j++) {
                    mbar_wait(smem_u32(&ms.kv[j]), 0);
                    float s[32];
                    uint32_t h[16];
                    wg_fence();
                    wgmma_qk64_f32(s, q, descKe + (uint64_t)(j * (KV_CHUNK >> 4)));
                    wgmma_qk64_f16(h, q, descKo + (uint64_t)(j * (KV_CHUNK >> 4)));
                    wg_commit();
                    wg_wait<0>();
                    pin(s);
                    pin(h);
                    if (j > 4 * r) release_chunk(j - 1);
#pragma unroll
                    for (int kg = 0; kg < 4; kg++) {
                        uint32_t p[8];
#pragma unroll
                        for (int u = 0; u < 2; u++) {
                            const int k = kg * 2 + u;
                            p[4 * u + 0] = pack_bf16(ex2_mufu(s[4 * k]), ex2_mufu(s[4 * k + 1]));
                            p[4 * u + 1] = pack_bf16(ex2_mufu(s[4 * k + 2]), ex2_mufu(s[4 * k + 3]));
                            p[4 * u + 2] = ex2_pair_h16(h[2 * k]);
                            p[4 * u + 3] = ex2_pair_h16(h[2 * k + 1]);
                        }
                        wg_fence();
#pragma unroll
                        for (int u = 0; u < 2; u++)
                            wgmma_pv24(o, p[4 * u], p[4 * u + 1], p[4 * u + 2], p[4 * u + 3],
                                       descV0 + (uint64_t)(j * (KV_CHUNK >> 4) + (kg * 2 + u) * 16));
                        wg_commit();
                        wg_wait<2>();
                    }
                }
                wg_wait<0>();
                pin(o);
            } else {
                guarded_item(smem, ms, r, t, cta, &tmWo, &tmG, &tmU);
#pragma unroll
                for (int i = 0; i < 8; i++) o[i] = st[i * 128];
                o[8] = st[8 * 128]; o[10] = st[9 * 128];
            }
            release_chunk(4 * r + 3);
            if (r < 3) {
#pragma unroll
                for (int i = 0; i < 8; i++) st[i * 128] = o[i];
                st[8 * 128] = o[8]; st[9 * 128] = o[10];
            } else {
                const float l0 = __shfl_sync(0xffffffffu, o[8], lane & ~3), l1 = __shfl_sync(0xffffffffu, o[10], lane & ~3);
                const float r0 = __fdividef(1.f, l0), r1 = __fdividef(1.f, l1);
                uint32_t* Op = reinterpret_cast<uint32_t*>(gO + (size_t)(quarter * 512 + t * 64 + w4 * 16) * DM + head * DH);
                Op[g * 256 + t4] = pack_bf16(o[0] * r0, o[1] * r0);
                Op[(g + 8) * 256 + t4] = pack_bf16(o[2] * r1, o[3] * r1);
                Op[g * 256 + 4 + t4] = pack_bf16(o[4] * r0, o[5] * r0);
                Op[(g + 8) * 256 + 4 + t4] = pack_bf16(o[6] * r1, o[7] * r1);
            }
            bar_sync(3 + wg, 128);
            if (t128 == 0) asm volatile("st.release.cta.shared.u32 [%0], %1;" ::"r"(smem_u32(&ms.seq[t])), "r"(r + 1) : "memory");
            if (item == 8 + wg && tid == 511) {
                bulk_prefetch_l2(reinterpret_cast<const char*>(w_down) + cta * 14336, 14336);
            }
            item = ms.nxt[wg];
            bar_sync(3 + wg, 128);
        }
        };
        if (fast) run_items(std::true_type{}); else run_items(std::false_type{});
    }
    __syncthreads();
    if (warp == 0 && lane < 8) { fence_gpu(); asm volatile("st.relaxed.gpu.global.u32 [%0], %1;" ::"l"(&gFlagO[(quarter * 8 + lane) * 32 + head]), "r"(tag) : "memory"); }
    if (tid == 0) TS(4);

    const int rb3 = cta >> 2, cb = cta & 3;
    if (wg < 2) {
        const int r0 = rb3 * 64 + w4 * 16 + g, r1 = r0 + 8;
        const int col0 = cb * 128 + wg * 64 + 2 * t4;
        uint32_t xa[8], xb[8], wr[8];
#pragma unroll
        for (int j = 0; j < 8; j++) {
            xa[j] = __ldg(reinterpret_cast<const uint32_t*>(x + (size_t)r0 * DM + col0 + j * 8));
            xb[j] = __ldg(reinterpret_cast<const uint32_t*>(x + (size_t)r1 * DM + col0 + j * 8));
            wr[j] = __ldg(reinterpret_cast<const uint32_t*>(w_r + col0 + j * 8));
        }
        const float p0 = __bfloat162float(x[(size_t)r0 * DM]), p1 = __bfloat162float(x[(size_t)r1 * DM]);
        const float pivot = __bfloat162float(x[(size_t)(rb3 * 64 + (tid >> 2)) * DM]);
        float wsum = 0.f;
        {
            const uint4 a = __ldg(reinterpret_cast<const uint4*>(w_r) + lane), b = __ldg(reinterpret_cast<const uint4*>(w_r) + 32 + lane);
            const uint32_t w[8] = {a.x, a.y, a.z, a.w, b.x, b.y, b.z, b.w};
#pragma unroll
            for (int e = 0; e < 8; e++) wsum += bf_lo(w[e]) + bf_hi(w[e]);
#pragma unroll
            for (int m = 16; m; m >>= 1) wsum += __shfl_xor_sync(0xffffffffu, wsum, m);
        }
        float acc[32];
#pragma unroll
        for (int i = 0; i < 32; i++) acc[i] = 0.f;
#pragma unroll 1
        for (int kc = 0; kc < 8; kc++) {
            mbar_wait(smem_u32(&ms.wo[kc]), 0);
            mbar_wait(smem_u32(&ms.a3[kc]), 0);
            const uint64_t da = make_desc(smem_u32(smem + SM_A3 + kc * 8192), 16, 1024, 1);
            const uint64_t db = make_desc(smem_u32(smem + (kc * 2 + wg) * KV_CHUNK), 8192, 1024, 1);
            wg_fence();
#pragma unroll
            for (int ks = 0; ks < 4; ks++) wgmma_n64(acc, da + ks * 2, db + ks * 128);
            wg_commit();
        }
        wg_wait<0>();
        pin(acc);
        if (tid == 0) TS(6);
        float s1a = 0.f, s2a = 0.f, s3a = 0.f, s1b = 0.f, s2b = 0.f, s3b = 0.f;
#pragma unroll
        for (int j = 0; j < 8; j++) {
            const uint32_t ha = pack_bf16(bf_lo(xa[j]) + acc[4 * j], bf_hi(xa[j]) + acc[4 * j + 1]);
            const uint32_t hb = pack_bf16(bf_lo(xb[j]) + acc[4 * j + 2], bf_hi(xb[j]) + acc[4 * j + 3]);
            xa[j] = ha; xb[j] = hb;
            const float w0 = bf_lo(wr[j]), w1 = bf_hi(wr[j]);
            const float da0 = bf_lo(ha) - p0, da1 = bf_hi(ha) - p0, db0 = bf_lo(hb) - p1, db1 = bf_hi(hb) - p1;
            s1a += da0 + da1; s2a = fmaf(da0, da0, fmaf(da1, da1, s2a)); s3a = fmaf(da0, w0, fmaf(da1, w1, s3a));
            s1b += db0 + db1; s2b = fmaf(db0, db0, fmaf(db1, db1, s2b)); s3b = fmaf(db0, w0, fmaf(db1, w1, s3b));
        }
#pragma unroll
        for (int m = 1; m <= 2; m <<= 1) {
            s1a += __shfl_xor_sync(0xffffffffu, s1a, m); s2a += __shfl_xor_sync(0xffffffffu, s2a, m); s3a += __shfl_xor_sync(0xffffffffu, s3a, m);
            s1b += __shfl_xor_sync(0xffffffffu, s1b, m); s2b += __shfl_xor_sync(0xffffffffu, s2b, m); s3b += __shfl_xor_sync(0xffffffffu, s3b, m);
        }
        if (t4 == 0) {
            const int lr = w4 * 16 + g;
            ms.p3.part[wg][lr][0] = s1a; ms.p3.part[wg][lr][1] = s2a; ms.p3.part[wg][lr][2] = s3a;
            ms.p3.part[wg][lr + 8][0] = s1b; ms.p3.part[wg][lr + 8][1] = s2b; ms.p3.part[wg][lr + 8][2] = s3b;
        }
        if (tid == 0) TS(11);
        bar_sync(1, 256);
        if (tid == 0) TS(12);
        if (tid < 64) {
            st_pkt(&gPart[(rb3 * 64 + tid) * 4 + cb],
                   make_uint4(__float_as_uint(ms.p3.part[0][tid][0] + ms.p3.part[1][tid][0]), __float_as_uint(ms.p3.part[0][tid][1] + ms.p3.part[1][tid][1]),
                              __float_as_uint(ms.p3.part[0][tid][2] + ms.p3.part[1][tid][2]), tag));
        }
        {
            const int lr = tid >> 2, sl = tid & 3;
            uint4 pv[1];
            wait_pkts<1, 0xffffffffu>(&gPart[rb3 * 256 + tid], 0, tag, pv);
            float s1 = __uint_as_float(pv[0].x), s2 = __uint_as_float(pv[0].y), s3 = __uint_as_float(pv[0].z);
            if (tid == 0) TS(14);
#pragma unroll
            for (int m = 1; m <= 2; m <<= 1) {
                s1 += __shfl_xor_sync(0xffffffffu, s1, m); s2 += __shfl_xor_sync(0xffffffffu, s2, m); s3 += __shfl_xor_sync(0xffffffffu, s3, m);
            }
            if (sl == 0) {
                const float md = s1 * (1.f / DM);
                const float var = fmaxf(s2 * (1.f / DM) - md * md, 0.f);
                const float rs = rsqrtf(var + LN_EPS);
                ms.p3.mu[lr] = pivot + md;
                ms.p3.rs[lr] = rs;
                ms.p3.r[lr] = (s3 - md * wsum) * rs;
            }
        }
        bar_sync(1, 256);
        if (tid == 0) TS(7);
        {
            unsigned int i1, i2;
            warp_top2(f2ord(ms.p3.r[lane]), lane, f2ord(ms.p3.r[lane + 32]), lane + 32, i1, i2);
            if (cb == 0) {
                const int c = tid & 1, li = c ? i2 : i1;
                st_pkt(&gCand[(tid >> 1) * 64 + rb3 * 2 + c],
                       make_uint4(__float_as_uint(ms.p3.r[li]), __float_as_uint(ms.p3.mu[li]), __float_as_uint(ms.p3.rs[li]),
                                  (tag << 11) | (unsigned int)(rb3 * 64 + li)));
            }
#pragma unroll
            for (int c = 0; c < 2; c++) {
                const unsigned int li = c ? i2 : i1;
                if ((int)(li >> 4) == w4 && (int)(li & 7) == g) {
                    const bool hi = (li & 8) != 0;
                    uint4* dst = &gCandRow[(rb3 * 2 + c) * 128 + (cb * 2 + wg) * 16 + t4];
#pragma unroll
                    for (int q = 0; q < 4; q++)
                        st_pkt(dst + q * 4, make_uint4(hi ? xb[2 * q] : xa[2 * q], hi ? xb[2 * q + 1] : xa[2 * q + 1], 0u, tag));
                }
            }
            if (tid == 0) TS(15);
        }
        {
            const int lr0 = w4 * 16 + g;
            const float mu0 = ms.p3.mu[lr0], rs0 = ms.p3.rs[lr0], mu1 = ms.p3.mu[lr0 + 8], rs1 = ms.p3.rs[lr0 + 8];
            char* so = smem + wg * KV_CHUNK;
#pragma unroll
            for (int j = 0; j < 8; j++) {
                const float a0 = bf_lo(xa[j]), a1 = bf_hi(xa[j]), b0 = bf_lo(xb[j]), b1 = bf_hi(xb[j]);
                const uint32_t la = pack_bf16((a0 - mu0) * rs0, (a1 - mu0) * rs0);
                const uint32_t lb = pack_bf16((b0 - mu1) * rs1, (b1 - mu1) * rs1);
                const int o = ((j ^ g) << 4) + t4 * 4;
                *reinterpret_cast<uint32_t*>(so + lr0 * 128 + o) = pack_bf16(a0 + bf_lo(la), a1 + bf_hi(la));
                *reinterpret_cast<uint32_t*>(so + (lr0 + 8) * 128 + o) = pack_bf16(b0 + bf_lo(lb), b1 + bf_hi(lb));
            }
            asm volatile("fence.proxy.async.shared::cta;" ::: "memory");
            bar_sync(3 + wg, 128);
            if ((tid & 127) == 0) {
                tma_store_2d(&tmOut, smem_u32(so), cb * 128 + wg * 64, rb3 * 64);
                asm volatile("cp.async.bulk.wait_group 0;" ::: "memory");
                st_flag(&gFlagOut[cta * 8 + wg], tag);
            }
        }
    } else {
        const int t = tid - 256;
        {
            const int kc = warp - 8;
            if (lane == 0) {
                int it = 0;
                while (true) {
                    const uint4 f = ld_pkt(reinterpret_cast<const uint4*>(&gFlagO[rb3 * 32 + kc * 4]));
                    if (f.x == tag && f.y == tag && f.z == tag && f.w == tag) break;
                    if (++it > SPIN_LIMIT) __trap();
                    BACKOFF();
                }
                if (kc == 7) TS(5);
                fence_proxy_async_global();
                const uint32_t bar = smem_u32(&ms.a3[kc]);
                mbar_expect_tx(bar, 8192);
                tma_2d(smem_u32(smem + SM_A3 + kc * 8192), &tmO, kc * 64, rb3 * 64, bar);
            }
            __syncwarp();
        }
        uint32_t wd[16];
        if (cta < NFFN) {
#pragma unroll
            for (int k = 0; k < 16; k++) wd[k] = __ldg(reinterpret_cast<const uint32_t*>(w_down + (size_t)(cta * 16 + k) * DM + 2 * t));
        }
        if (warp == 8) {
            if (lane == 0) TS(56);
            uint4 cv[2];
            wait_pkts<2, 0xfffff800u>(&gCand[cta * 64 + lane * 2], 1, tag << 11, cv);
            if (lane == 0) TS(54);
            unsigned int i1, i2;
            warp_top2(f2ord(__uint_as_float(cv[0].x)), cv[0].w & 0x7ffu, f2ord(__uint_as_float(cv[1].x)), cv[1].w & 0x7ffu, i1, i2);
#pragma unroll
            for (int c = 0; c < 2; c++) {
                const unsigned int ci = cv[c].w & 0x7ffu;
                if (ci == i1 || ci == i2) {
                    const int o = ci == i1 ? 0 : 1;
                    ms.idx[o] = (int)ci;
                    ms.cslot[o] = lane * 2 + c;
                    *reinterpret_cast<float4*>(&ms.sel[o * 4]) =
                        make_float4(__uint_as_float(cv[c].y), __uint_as_float(cv[c].z), __fdividef(1.f, 1.f + __expf(-__uint_as_float(cv[c].x))), 0.f);
                }
            }
            if (lane == 0) TS(8);
        }
        bar_sync(2, 256);
        const int idx0 = ms.idx[0], idx1 = ms.idx[1];
        if (t == 0 && idx0 >= 0) TS(61);
        float* sX = reinterpret_cast<float*>(smem + SM_A3);
        float* sH = sX + 1024;
        float* sPart = sX + 2048;
        float* sAct = sPart + 512;
        if (cta < NFFN) {
            {
                const int tk = t >> 7, P = t & 127;
                uint4 hv[1];
                wait_pkts<1, 0xffffffffu>(&gCandRow[ms.cslot[tk] * 128 + P], 0, tag, hv);
                if (t == 0) TS(57);
                const float mu = ms.sel[tk * 4], rs = ms.sel[tk * 4 + 1];
                const int col = (P >> 4) * 64 + ((P >> 2) & 3) * 16 + (P & 3) * 2;
                const uint32_t l0 = pack_bf16((bf_lo(hv[0].x) - mu) * rs, (bf_hi(hv[0].x) - mu) * rs);
                const uint32_t l1 = pack_bf16((bf_lo(hv[0].y) - mu) * rs, (bf_hi(hv[0].y) - mu) * rs);
                *reinterpret_cast<float2*>(&sX[tk * 512 + col]) = make_float2(bf_lo(l0), bf_hi(l0));
                *reinterpret_cast<float2*>(&sX[tk * 512 + col + 8]) = make_float2(bf_lo(l1), bf_hi(l1));
                *reinterpret_cast<float2*>(&sH[tk * 512 + col]) = make_float2(bf_lo(hv[0].x), bf_hi(hv[0].x));
                *reinterpret_cast<float2*>(&sH[tk * 512 + col + 8]) = make_float2(bf_lo(hv[0].y), bf_hi(hv[0].y));
            }
            mbar_wait(smem_u32(&ms.moe), 0);
            bar_sync(1 + 8, 256);
            if (t == 0) { asm volatile("" ::: "memory"); sAct[40] = sX[0]; TS(58); }
            {
                const int wv = warp - 8, kk = lane >> 3, cp = lane & 7;
                float a[2][2][2] = {};
#pragma unroll
                for (int i = 0; i < 16; i++) {
                    const int k = wv * 64 + i * 4 + kk;
                    const float x0 = sX[k], x1 = sX[512 + k];
#pragma unroll
                    for (int mat = 0; mat < 2; mat++) {
                        const uint32_t w = *reinterpret_cast<const uint32_t*>(smem + (mat * 8 + wv) * KV_CHUNK + 8192 + (i * 4 + kk) * 32 + cp * 4);
                        a[mat][0][0] = fmaf(x0, bf_lo(w), a[mat][0][0]); a[mat][0][1] = fmaf(x0, bf_hi(w), a[mat][0][1]);
                        a[mat][1][0] = fmaf(x1, bf_lo(w), a[mat][1][0]); a[mat][1][1] = fmaf(x1, bf_hi(w), a[mat][1][1]);
                    }
                }
#pragma unroll
                for (int mat = 0; mat < 2; mat++)
#pragma unroll
                    for (int tk = 0; tk < 2; tk++)
#pragma unroll
                        for (int e = 0; e < 2; e++) {
                            float v = a[mat][tk][e];
                            v += __shfl_xor_sync(0xffffffffu, v, 8);
                            v += __shfl_xor_sync(0xffffffffu, v, 16);
                            if (kk == 0) sPart[(wv * 2 + tk) * 32 + mat * 16 + 2 * cp + e] = v;
                        }
            }
            bar_sync(1 + 8, 256);
            if (t == 0) { sAct[41] = sPart[0]; TS(59); }
            if (t < 32) {
                const int tk = t >> 4, c = t & 15;
                float gs = 0.f, us = 0.f;
#pragma unroll
                for (int w = 0; w < 8; w++) { gs += sPart[(w * 2 + tk) * 32 + c]; us += sPart[(w * 2 + tk) * 32 + 16 + c]; }
                const float gb = bf_round(gs), ub = bf_round(us);
                const float sl = bf_round(__fdividef(gb, 1.f + __expf(-gb)));
                sAct[tk * 16 + c] = bf_round(sl * ub);
            }
            bar_sync(1 + 8, 256);
            {
                float y00 = 0.f, y01 = 0.f, y10 = 0.f, y11 = 0.f;
#pragma unroll
                for (int k = 0; k < 16; k++) {
                    const float a0 = sAct[k], a1 = sAct[16 + k];
                    y00 = fmaf(a0, bf_lo(wd[k]), y00); y01 = fmaf(a0, bf_hi(wd[k]), y01);
                    y10 = fmaf(a1, bf_lo(wd[k]), y10); y11 = fmaf(a1, bf_hi(wd[k]), y11);
                }
                st_pkt(&gYPart[((t >> 2) * NFFN + cta) * 4 + (t & 3)], embed_tag(y00, y01, y10, y11, tag));
            }
            if (t == 0) TS(9);
        }
        if (cta < 64) {
            const int pc = t & 3, part = t >> 2;
            const int opc = (t >> 2) & 3, oe = t & 3, otk = oe >> 1, ocol = (cta * 4 + opc) * 2 + (oe & 1);
            float y[4] = {0.f, 0.f, 0.f, 0.f};
            if (part < 56) {
                uint4 yv[2];
                wait_pkts4<2>(&gYPart[(cta * NFFN + part) * 4 + pc], 56 * 4, tag, yv);
                if (t == 0) TS(60);
                y[0] = __uint_as_float(yv[0].x) + __uint_as_float(yv[1].x); y[1] = __uint_as_float(yv[0].y) + __uint_as_float(yv[1].y);
                y[2] = __uint_as_float(yv[0].z) + __uint_as_float(yv[1].z); y[3] = __uint_as_float(yv[0].w) + __uint_as_float(yv[1].w);
            }
            if (t >= 224 && t < 226) {
                const int orow = (t & 1) ? idx1 : idx0, oc = cta * 8;
                wait_flag(&gFlagOut[((orow >> 6) * 4 + (oc >> 7)) * 8 + ((oc >> 6) & 1)], tag);
            }
            __syncwarp();
#pragma unroll
            for (int e = 0; e < 4; e++) {
                y[e] += __shfl_xor_sync(0xffffffffu, y[e], 4); y[e] += __shfl_xor_sync(0xffffffffu, y[e], 8); y[e] += __shfl_xor_sync(0xffffffffu, y[e], 16);
            }
            float* sR = sAct + 32;
            if (lane < 4) *reinterpret_cast<float4*>(&sR[(warp - 8) * 16 + lane * 4]) = make_float4(y[0], y[1], y[2], y[3]);
            bar_sync(1 + 8, 256);
            if (t < 16) {
                float s = 0.f;
#pragma unroll
                for (int w = 0; w < 8; w++) s += sR[w * 16 + t];
                const float yb = bf_round(bf_round(s) * ms.sel[otk * 4 + 2]);
                out[(size_t)(otk ? idx1 : idx0) * DM + ocol] = __float2bfloat16(sH[otk * 512 + ocol] + bf_round(sX[otk * 512 + ocol] + yb));
            }
            if (cta == 0 && t == 0) {
                *reinterpret_cast<volatile unsigned int*>(&gEpoch) = tag;
            }
            if (t == 0) TS(10);
        }
    }
}

typedef CUresult (*EncodeFn)(CUtensorMap*, CUtensorMapDataType, cuuint32_t, void*, const cuuint64_t*, const cuuint64_t*,
                             const cuuint32_t*, const cuuint32_t*, CUtensorMapInterleave, CUtensorMapSwizzle,
                             CUtensorMapL2promotion, CUtensorMapFloatOOBfill);

void make_map(EncodeFn enc, CUtensorMap* tm, const void* base, uint64_t cols, uint64_t rows, uint32_t box_c, uint32_t box_r, bool swz) {
    cuuint64_t dims[2] = {cols, rows};
    cuuint64_t strides[1] = {cols * 2};
    cuuint32_t box[2] = {box_c, box_r};
    cuuint32_t es[2] = {1, 1};
    enc(tm, CU_TENSOR_MAP_DATA_TYPE_BFLOAT16, 2, const_cast<void*>(base), dims, strides, box, es, CU_TENSOR_MAP_INTERLEAVE_NONE,
        swz ? CU_TENSOR_MAP_SWIZZLE_128B : CU_TENSOR_MAP_SWIZZLE_NONE, CU_TENSOR_MAP_L2_PROMOTION_L2_256B,
        CU_TENSOR_MAP_FLOAT_OOB_FILL_NONE);
}

}

extern "C" void kernel_launch(void* const* d_in, const int* in_sizes, int n_in, void* d_out, int out_size) {
    const __nv_bfloat16* x = (const __nv_bfloat16*)d_in[0];
    const __nv_bfloat16* wqkv = (const __nv_bfloat16*)d_in[1];
    const __nv_bfloat16* wo = (const __nv_bfloat16*)d_in[2];
    const __nv_bfloat16* w_r = (const __nv_bfloat16*)d_in[4];
    const __nv_bfloat16* w_gate = (const __nv_bfloat16*)d_in[5];
    const __nv_bfloat16* w_up = (const __nv_bfloat16*)d_in[6];
    const __nv_bfloat16* w_down = (const __nv_bfloat16*)d_in[7];
    __nv_bfloat16* out = (__nv_bfloat16*)d_out;

    static EncodeFn enc = nullptr;
    static void* pO = nullptr;
    if (!enc) {
        void* fn = nullptr;
        cudaDriverEntryPointQueryResult qr;
        cudaGetDriverEntryPoint("cuTensorMapEncodeTiled", &fn, cudaEnableDefault, &qr);
        enc = (EncodeFn)fn;
        cudaGetSymbolAddress(&pO, gO);
        cudaFuncSetAttribute(mega_kernel, cudaFuncAttributeMaxDynamicSharedMemorySize, SMEM_TOTAL);
    }
    CUtensorMap tmX, tmW, tmO, tmWo, tmG, tmU, tmOut;
    make_map(enc, &tmX, x, DM, S_LEN, 64, 128, true);
    make_map(enc, &tmW, wqkv, 3 * DM, DM, 64, 64, true);
    make_map(enc, &tmO, pO, DM, S_LEN, 64, 64, true);
    make_map(enc, &tmWo, wo, DM, DM, 64, 64, true);
    make_map(enc, &tmG, w_gate, FF, DM, 16, 64, false);
    make_map(enc, &tmU, w_up, FF, DM, 16, 64, false);
    make_map(enc, &tmOut, out, DM, S_LEN, 64, 64, true);

    mega_kernel<<<128, 512, SMEM_TOTAL, cudaStreamPerThread>>>(tmX, tmW, tmO, tmWo, tmG, tmU, tmOut, x, wqkv, wo, w_r, w_gate, w_up, w_down, out);
}
```

```cpp
#include <cuda_runtime.h>
#include <cuda_bf16.h>
#include <cuda.h>
#include <stdint.h>
#include <type_traits>

namespace {

constexpr int S_LEN = 2048, DM = 512, NH = 32, DH = 16, FF = 1792;
constexpr int NFFN = FF / 16;
constexpr float LN_EPS = 1e-5f;
constexpr float QSCALE = 0.25f * 1.4426950408889634f;

__device__ __align__(1024) __nv_bfloat16 gQ[NH * S_LEN * DH];
__device__ __align__(1024) __nv_bfloat16 gKV[NH * S_LEN * DH * 2];
__device__ __align__(1024) __nv_bfloat16 gO[S_LEN * DM];
__device__ unsigned int gEpoch;
__device__ uint4 gFlagQKV[128 * 4];
__device__ __align__(32) unsigned int gFlagO[32 * 32];
__device__ uint4 gStat1[S_LEN];
__device__ uint4 gCsPart[8 * 16 * 48];
__device__ uint4 gPart[32 * 64 * 4];
__device__ uint4 gCand[128 * 64];
__device__ __align__(32) unsigned int gFlagOut[128 * 8];
__device__ uint4 gCandRow[64 * 128];
__device__ uint4 gYPart[NFFN * 256];

#define TS(slot) do {} while (0)

__device__ __forceinline__ uint32_t smem_u32(const void* p) { return (uint32_t)__cvta_generic_to_shared(p); }
__device__ __forceinline__ void mbar_init(uint32_t bar, uint32_t cnt) {
    asm volatile("mbarrier.init.shared::cta.b64 [%0], %1;" ::"r"(bar), "r"(cnt));
}
__device__ __forceinline__ void mbar_expect_tx(uint32_t bar, uint32_t bytes) {
    asm volatile("mbarrier.arrive.expect_tx.shared::cta.b64 _, [%0], %1;" ::"r"(bar), "r"(bytes) : "memory");
}
__device__ __forceinline__ void mbar_arrive(uint32_t bar) {
    asm volatile("mbarrier.arrive.shared::cta.b64 _, [%0];" ::"r"(bar) : "memory");
}
constexpr int SPIN_LIMIT = 1 << 22;
#define ITEMMODE 0
#define PVG 2
#define PVWAIT 2
#define CPI 16
#define NR (16 / CPI)
#define BACKOFF() __nanosleep(32)
__device__ __forceinline__ void mbar_wait(uint32_t bar, uint32_t parity) {
    uint32_t done = 0;
    int it = 0;
    while (true) {
        asm volatile("{.reg .pred p; mbarrier.try_wait.parity.shared::cta.b64 p, [%1], %2; selp.u32 %0, 1, 0, p;}"
                     : "=r"(done) : "r"(bar), "r"(parity) : "memory");
        if (done) break;
        if (++it > SPIN_LIMIT) __trap();
    }
}
__device__ __forceinline__ void bulk_g2s(uint32_t dst, const void* src, uint32_t bytes, uint32_t bar) {
    asm volatile("cp.async.bulk.shared::cluster.global.mbarrier::complete_tx::bytes [%0], [%1], %2, [%3];"
                 ::"r"(dst), "l"(src), "r"(bytes), "r"(bar) : "memory");
}
__device__ __forceinline__ void bulk_prefetch_l2(const void* src, uint32_t bytes) {
    asm volatile("cp.async.bulk.prefetch.L2.global [%0], %1;" ::"l"(src), "r"(bytes) : "memory");
}
__device__ __forceinline__ void tma_2d(uint32_t dst, const CUtensorMap* tm, int c0, int c1, uint32_t bar) {
    asm volatile("cp.async.bulk.tensor.2d.shared::cluster.global.mbarrier::complete_tx::bytes [%0], [%1, {%3, %4}], [%2];"
                 ::"r"(dst), "l"(tm), "r"(bar), "r"(c0), "r"(c1) : "memory");
}
__device__ __forceinline__ void tma_store_2d(const CUtensorMap* tm, uint32_t src, int c0, int c1) {
    asm volatile("cp.async.bulk.tensor.2d.global.shared::cta.bulk_group [%0, {%2, %3}], [%1];" ::"l"(tm), "r"(src), "r"(c0), "r"(c1) : "memory");
    asm volatile("cp.async.bulk.commit_group;" ::: "memory");
}
__device__ __forceinline__ void fence_proxy_async_global() { asm volatile("fence.proxy.async.global;" ::: "memory"); }
__device__ __forceinline__ void fence_gpu() { asm volatile("fence.acq_rel.gpu;" ::: "memory"); }
__device__ __forceinline__ void bar_sync(int id, int n) { asm volatile("bar.sync %0, %1;" ::"r"(id), "r"(n) : "memory"); }
__device__ __forceinline__ void bar_arrive(int id, int n) { asm volatile("bar.arrive %0, %1;" ::"r"(id), "r"(n) : "memory"); }
__device__ __forceinline__ void st_flag(unsigned int* p, unsigned int v) {
    asm volatile("st.release.gpu.global.u32 [%0], %1;" ::"l"(p), "r"(v) : "memory");
}
__device__ __forceinline__ unsigned int ld_flag(const unsigned int* p) {
    unsigned int v;
    asm volatile("ld.relaxed.gpu.global.u32 %0, [%1];" : "=r"(v) : "l"(p) : "memory");
    return v;
}
__device__ __forceinline__ void wait_flag(const unsigned int* p, unsigned int tag) {
    int it = 0;
    while (ld_flag(p) != tag) {
        if (++it > SPIN_LIMIT) __trap();
        BACKOFF();
    }
}
__device__ __forceinline__ void st_pkt(uint4* p, uint4 v) {
    asm volatile("st.relaxed.gpu.global.v4.u32 [%0], {%1,%2,%3,%4};" ::"l"(p), "r"(v.x), "r"(v.y), "r"(v.z), "r"(v.w) : "memory");
}
__device__ __forceinline__ uint4 ld_pkt(const uint4* p) {
    uint4 v;
    asm volatile("ld.relaxed.gpu.global.v4.u32 {%0,%1,%2,%3}, [%4];" : "=r"(v.x), "=r"(v.y), "=r"(v.z), "=r"(v.w) : "l"(p) : "memory");
    return v;
}
template <int N, unsigned int MASK>
__device__ __forceinline__ void wait_pkts(const uint4* p, int stride, unsigned int tag, uint4 (&v)[N]) {
    int it = 0;
    while (true) {
        bool ok = true;
#pragma unroll
        for (int i = 0; i < N; i++) v[i] = ld_pkt(p + (size_t)i * stride);
#pragma unroll
        for (int i = 0; i < N; i++) ok = ok && ((v[i].w & MASK) == tag);
        if (ok) break;
        if (++it > SPIN_LIMIT) __trap();
        BACKOFF();
    }
}
__device__ __forceinline__ uint4 embed_tag(float a, float b, float c, float d, unsigned int tag) {
    return make_uint4((__float_as_uint(a) & ~15u) | (tag & 15u), (__float_as_uint(b) & ~15u) | ((tag >> 4) & 15u),
                      (__float_as_uint(c) & ~15u) | ((tag >> 8) & 15u), (__float_as_uint(d) & ~15u) | ((tag >> 12) & 15u));
}
template <int N>
__device__ __forceinline__ void wait_pkts4(const uint4* p, int stride, unsigned int tag, uint4 (&v)[N]) {
    const unsigned int t16 = tag & 0xffffu;
    int it = 0;
    while (true) {
        bool ok = true;
#pragma unroll
        for (int i = 0; i < N; i++) v[i] = ld_pkt(p + (size_t)i * stride);
#pragma unroll
        for (int i = 0; i < N; i++)
            ok = ok && (((v[i].x & 15u) | ((v[i].y & 15u) << 4) | ((v[i].z & 15u) << 8) | ((v[i].w & 15u) << 12)) == t16);
        if (ok) break;
        if (++it > SPIN_LIMIT) __trap();
        BACKOFF();
    }
}
__device__ __forceinline__ uint64_t make_desc(uint32_t addr, uint32_t lbo, uint32_t sbo, uint32_t mode) {
    return (uint64_t)((addr & 0x3FFFF) >> 4) | ((uint64_t)((lbo & 0x3FFFF) >> 4) << 16) |
           ((uint64_t)((sbo & 0x3FFFF) >> 4) << 32) | ((uint64_t)mode << 62);
}
__device__ __forceinline__ void wg_fence() { asm volatile("wgmma.fence.sync.aligned;" ::: "memory"); }
__device__ __forceinline__ void wg_commit() { asm volatile("wgmma.commit_group.sync.aligned;" ::: "memory"); }
template <int N> __device__ __forceinline__ void wg_wait() { asm volatile("wgmma.wait_group.sync.aligned %0;" ::"n"(N) : "memory"); }
template <int N> __device__ __forceinline__ void pin(uint32_t (&d)[N]) {
#pragma unroll
    for (int i = 0; i < N; i++) asm volatile("" : "+r"(d[i])::"memory");
}
template <int N> __device__ __forceinline__ void pin(float (&d)[N]) {
#pragma unroll
    for (int i = 0; i < N; i++) asm volatile("" : "+f"(d[i])::"memory");
}
__device__ __forceinline__ uint32_t pack_bf16(float lo, float hi) {
    uint32_t r;
    asm("cvt.rn.bf16x2.f32 %0, %1, %2;" : "=r"(r) : "f"(hi), "f"(lo));
    return r;
}
__device__ __forceinline__ float bf_lo(uint32_t v) { return __uint_as_float(v << 16); }
__device__ __forceinline__ float bf_hi(uint32_t v) { return __uint_as_float(v & 0xFFFF0000u); }
__device__ __forceinline__ float bf_round(float v) { return __bfloat162float(__float2bfloat16(v)); }
__device__ __forceinline__ float ex2_mufu(float x) {
    float y;
    asm("ex2.approx.ftz.f32 %0, %1;" : "=f"(y) : "f"(x));
    return y;
}

#define ACC8(d, o) "+f"(d[o + 0]), "+f"(d[o + 1]), "+f"(d[o + 2]), "+f"(d[o + 3]), "+f"(d[o + 4]), "+f"(d[o + 5]), "+f"(d[o + 6]), "+f"(d[o + 7])
#define OUT8(d, o) "=f"(d[o + 0]), "=f"(d[o + 1]), "=f"(d[o + 2]), "=f"(d[o + 3]), "=f"(d[o + 4]), "=f"(d[o + 5]), "=f"(d[o + 6]), "=f"(d[o + 7])

__device__ __forceinline__ void wgmma_n192(float (&d)[96], uint64_t da, uint64_t db) {
    asm volatile(
        "wgmma.mma_async.sync.aligned.m64n192k16.f32.bf16.bf16 "
        "{%0,%1,%2,%3,%4,%5,%6,%7,%8,%9,%10,%11,%12,%13,%14,%15,%16,%17,%18,%19,%20,%21,%22,%23,%24,%25,%26,%27,%28,%29,%30,%31,"
        "%32,%33,%34,%35,%36,%37,%38,%39,%40,%41,%42,%43,%44,%45,%46,%47,%48,%49,%50,%51,%52,%53,%54,%55,%56,%57,%58,%59,%60,%61,%62,%63,"
        "%64,%65,%66,%67,%68,%69,%70,%71,%72,%73,%74,%75,%76,%77,%78,%79,%80,%81,%82,%83,%84,%85,%86,%87,%88,%89,%90,%91,%92,%93,%94,%95},"
        "%96, %97, 1, 1, 1, 0, 1;"
        : ACC8(d, 0), ACC8(d, 8), ACC8(d, 16), ACC8(d, 24), ACC8(d, 32), ACC8(d, 40), ACC8(d, 48), ACC8(d, 56),
          ACC8(d, 64), ACC8(d, 72), ACC8(d, 80), ACC8(d, 88)
        : "l"(da), "l"(db));
}
__device__ __forceinline__ void wgmma_n192_rs(float (&d)[96], const uint32_t* a, uint64_t db) {
    asm volatile(
        "wgmma.mma_async.sync.aligned.m64n192k16.f32.bf16.bf16 "
        "{%0,%1,%2,%3,%4,%5,%6,%7,%8,%9,%10,%11,%12,%13,%14,%15,%16,%17,%18,%19,%20,%21,%22,%23,%24,%25,%26,%27,%28,%29,%30,%31,"
        "%32,%33,%34,%35,%36,%37,%38,%39,%40,%41,%42,%43,%44,%45,%46,%47,%48,%49,%50,%51,%52,%53,%54,%55,%56,%57,%58,%59,%60,%61,%62,%63,"
        "%64,%65,%66,%67,%68,%69,%70,%71,%72,%73,%74,%75,%76,%77,%78,%79,%80,%81,%82,%83,%84,%85,%86,%87,%88,%89,%90,%91,%92,%93,%94,%95},"
        "{%96,%97,%98,%99}, %100, 1, 1, 1, 1;"
        : ACC8(d, 0), ACC8(d, 8), ACC8(d, 16), ACC8(d, 24), ACC8(d, 32), ACC8(d, 40), ACC8(d, 48), ACC8(d, 56),
          ACC8(d, 64), ACC8(d, 72), ACC8(d, 80), ACC8(d, 88)
        : "r"(a[0]), "r"(a[1]), "r"(a[2]), "r"(a[3]), "l"(db));
}
__device__ __forceinline__ void ldsm_x4(uint32_t* r, uint32_t addr) {
    asm volatile("ldmatrix.sync.aligned.m8n8.x4.shared.b16 {%0,%1,%2,%3}, [%4];"
                 : "=r"(r[0]), "=r"(r[1]), "=r"(r[2]), "=r"(r[3]) : "r"(addr) : "memory");
}
__device__ __forceinline__ void wgmma_n64(float (&d)[32], uint64_t da, uint64_t db) {
    asm volatile(
        "wgmma.mma_async.sync.aligned.m64n64k16.f32.bf16.bf16 "
        "{%0,%1,%2,%3,%4,%5,%6,%7,%8,%9,%10,%11,%12,%13,%14,%15,%16,%17,%18,%19,%20,%21,%22,%23,%24,%25,%26,%27,%28,%29,%30,%31},"
        "%32, %33, 1, 1, 1, 0, 1;"
        : ACC8(d, 0), ACC8(d, 8), ACC8(d, 16), ACC8(d, 24)
        : "l"(da), "l"(db));
}
__device__ __forceinline__ void wgmma_qk128(float (&d)[64], const uint32_t (&a)[4], uint64_t db) {
    asm volatile("wgmma.mma_async.sync.aligned.m64n128k16.f32.f16.f16 "
        "{%0,%1,%2,%3,%4,%5,%6,%7,%8,%9,%10,%11,%12,%13,%14,%15,%16,%17,%18,%19,%20,%21,%22,%23,%24,%25,%26,%27,%28,%29,%30,%31,%32,%33,%34,%35,%36,%37,%38,%39,%40,%41,%42,%43,%44,%45,%46,%47,%48,%49,%50,%51,%52,%53,%54,%55,%56,%57,%58,%59,%60,%61,%62,%63}, {%64,%65,%66,%67}, %68, 0, 1, 1, 0;"
        : "=f"(d[0]), "=f"(d[1]), "=f"(d[2]), "=f"(d[3]), "=f"(d[4]), "=f"(d[5]), "=f"(d[6]), "=f"(d[7]), "=f"(d[8]), "=f"(d[9]), "=f"(d[10]), "=f"(d[11]), "=f"(d[12]), "=f"(d[13]), "=f"(d[14]), "=f"(d[15]), "=f"(d[16]), "=f"(d[17]), "=f"(d[18]), "=f"(d[19]), "=f"(d[20]), "=f"(d[21]), "=f"(d[22]), "=f"(d[23]), "=f"(d[24]), "=f"(d[25]), "=f"(d[26]), "=f"(d[27]), "=f"(d[28]), "=f"(d[29]), "=f"(d[30]), "=f"(d[31]), "=f"(d[32]), "=f"(d[33]), "=f"(d[34]), "=f"(d[35]), "=f"(d[36]), "=f"(d[37]), "=f"(d[38]), "=f"(d[39]), "=f"(d[40]), "=f"(d[41]), "=f"(d[42]), "=f"(d[43]), "=f"(d[44]), "=f"(d[45]), "=f"(d[46]), "=f"(d[47]), "=f"(d[48]), "=f"(d[49]), "=f"(d[50]), "=f"(d[51]), "=f"(d[52]), "=f"(d[53]), "=f"(d[54]), "=f"(d[55]), "=f"(d[56]), "=f"(d[57]), "=f"(d[58]), "=f"(d[59]), "=f"(d[60]), "=f"(d[61]), "=f"(d[62]), "=f"(d[63])
        : "r"(a[0]), "r"(a[1]), "r"(a[2]), "r"(a[3]), "l"(db));
}
__device__ __forceinline__ void wgmma_qk64_f32(float (&d)[32], const uint32_t (&a)[4], uint64_t db) {
    asm volatile("wgmma.mma_async.sync.aligned.m64n64k16.f32.f16.f16 "
        "{%0,%1,%2,%3,%4,%5,%6,%7,%8,%9,%10,%11,%12,%13,%14,%15,%16,%17,%18,%19,%20,%21,%22,%23,%24,%25,%26,%27,%28,%29,%30,%31}, {%32,%33,%34,%35}, %36, 0, 1, 1, 0;"
        : "=f"(d[0]), "=f"(d[1]), "=f"(d[2]), "=f"(d[3]), "=f"(d[4]), "=f"(d[5]), "=f"(d[6]), "=f"(d[7]), "=f"(d[8]), "=f"(d[9]), "=f"(d[10]), "=f"(d[11]), "=f"(d[12]), "=f"(d[13]), "=f"(d[14]), "=f"(d[15]), "=f"(d[16]), "=f"(d[17]), "=f"(d[18]), "=f"(d[19]), "=f"(d[20]), "=f"(d[21]), "=f"(d[22]), "=f"(d[23]), "=f"(d[24]), "=f"(d[25]), "=f"(d[26]), "=f"(d[27]), "=f"(d[28]), "=f"(d[29]), "=f"(d[30]), "=f"(d[31])
        : "r"(a[0]), "r"(a[1]), "r"(a[2]), "r"(a[3]), "l"(db));
}
__device__ __forceinline__ void wgmma_qk64_f16(uint32_t (&d)[16], const uint32_t (&a)[4], uint64_t db) {
    asm volatile("wgmma.mma_async.sync.aligned.m64n64k16.f16.f16.f16 "
        "{%0,%1,%2,%3,%4,%5,%6,%7,%8,%9,%10,%11,%12,%13,%14,%15}, {%16,%17,%18,%19}, %20, 0, 1, 1, 0;"
        : "=r"(d[0]), "=r"(d[1]), "=r"(d[2]), "=r"(d[3]), "=r"(d[4]), "=r"(d[5]), "=r"(d[6]), "=r"(d[7]), "=r"(d[8]), "=r"(d[9]), "=r"(d[10]), "=r"(d[11]), "=r"(d[12]), "=r"(d[13]), "=r"(d[14]), "=r"(d[15])
        : "r"(a[0]), "r"(a[1]), "r"(a[2]), "r"(a[3]), "l"(db));
}
__device__ __forceinline__ void wgmma_pv24(float (&o)[12], uint32_t a0, uint32_t a1, uint32_t a2, uint32_t a3, uint64_t desc) {
    asm volatile(
        "wgmma.mma_async.sync.aligned.m64n24k16.f32.bf16.bf16 "
        "{%0,%1,%2,%3,%4,%5,%6,%7,%8,%9,%10,%11}, {%12,%13,%14,%15}, %16, 1, 1, 1, 1;"
        : ACC8(o, 0), "+f"(o[8]), "+f"(o[9]), "+f"(o[10]), "+f"(o[11])
        : "r"(a0), "r"(a1), "r"(a2), "r"(a3), "l"(desc));
}

__device__ __forceinline__ uint32_t ex2_pair_h16(uint32_t x2) {
    uint32_t t, r, f, q;
    asm("add.rn.f16x2 %0, %1, %2;" : "=r"(t) : "r"(x2), "r"(0x661E661Fu));
    asm("sub.rn.f16x2 %0, %1, %2;" : "=r"(r) : "r"(t), "r"(0x661E661Fu));
    asm("sub.rn.f16x2 %0, %1, %2;" : "=r"(f) : "r"(x2), "r"(r));
    asm("fma.rn.f16x2 %0, %1, %2, %3;" : "=r"(q) : "r"(0x15101510u), "r"(f), "r"(0x1d7e1d7eu));
    asm("fma.rn.f16x2 %0, %1, %2, %3;" : "=r"(q) : "r"(q), "r"(f), "r"(0x23d823d8u));
    asm("fma.rn.f16x2 %0, %1, %2, %3;" : "=r"(q) : "r"(q), "r"(f), "r"(0x30823035u));
    return t * 128u + q;
}
constexpr float VSCALE_ODD = 0.70703125f;
constexpr float LOG2C_ODD = 0.50015402f;
__device__ __forceinline__ uint32_t pack_f16_sat(float lo, float hi) {
    uint32_t r;
    asm("cvt.rn.satfinite.f16x2.f32 %0, %1, %2;" : "=r"(r) : "f"(hi), "f"(lo));
    return r;
}
__device__ __forceinline__ unsigned int f2ord(float v) {
    const unsigned int u = __float_as_uint(v);
    const unsigned int o = u ^ ((unsigned int)((int)u >> 31) | 0x80000000u);
    return (v == v) ? o : 0u;
}
__device__ __forceinline__ void warp_top2(unsigned int ka, unsigned int ia, unsigned int kb, unsigned int ib, unsigned int& i1, unsigned int& i2) {
    const unsigned int m1 = __reduce_max_sync(0xffffffffu, max(ka, kb));
    i1 = __reduce_min_sync(0xffffffffu, min(ka == m1 ? ia : 0xffffffffu, kb == m1 ? ib : 0xffffffffu));
    const bool ra = (ia == i1), rb = (ib == i1);
    const unsigned int ka2 = ra ? 0u : ka, kb2 = rb ? 0u : kb, ia2 = ra ? 0xffffffffu : ia, ib2 = rb ? 0xffffffffu : ib;
    const unsigned int m2 = __reduce_max_sync(0xffffffffu, max(ka2, kb2));
    i2 = __reduce_min_sync(0xffffffffu, min(ka2 == m2 ? ia2 : 0xffffffffu, kb2 == m2 ? ib2 : 0xffffffffu));
}

constexpr int P1_STAGES = 5;
constexpr int P1_STAGE_BYTES = 16384 + 24576;
constexpr int KV_CHUNK = 10240;
constexpr int SM_Q = 163840 + 49152;
constexpr int SM_A3 = 163840;
constexpr int SM_MISC = 229376;
constexpr int SMEM_TOTAL = 232448;
struct Misc {
    uint64_t p1_full[P1_STAGES], p1_empty[P1_STAGES];
    uint64_t kv[16];
    uint64_t wo[8], a3[8], moe;
    unsigned int tag;
    int fast;
    int idx[2], cslot[2];
    alignas(16) float sel[8];
    unsigned int norm[12];
    uint64_t qbar;
    int item, nxt[4];
    unsigned int seq[8];
    unsigned int freed[16];
    union alignas(16) {
        struct { float mu[128], rs[128], cs[192]; } p1;
        struct { float part[2][64][3]; float mu[64], rs[64], r[64]; } p3;
    };
};
static_assert(sizeof(Misc) <= SMEM_TOTAL - SM_MISC, "misc smem");

__device__ __forceinline__ void release_kv_chunk(Misc& ms, int j, int lane) {
    asm volatile("{.reg .pred p; setp.eq.s32 p, %1, 0; @p red.relaxed.cta.shared.add.u32 [%0], 1;}" ::"r"(smem_u32(&ms.freed[j])), "r"(lane) : "memory");
}
__device__ __forceinline__ bool refill_kv_chunk(char* smem, Misc& ms, int j, int cta, int lane, const CUtensorMap* tmWo,
                                                const CUtensorMap* tmG, const CUtensorMap* tmU) {
    unsigned int cnt;
    asm volatile("ld.relaxed.cta.shared.u32 %0, [%1];" : "=r"(cnt) : "r"(smem_u32(&ms.freed[j])) : "memory");
    if (cnt < 32u) return false;
    if (lane == 0) {
        const uint32_t dst = smem_u32(smem + j * KV_CHUNK);
        const uint32_t wb = smem_u32(&ms.wo[j >> 1]);
        mbar_expect_tx(wb, 8192);
        tma_2d(dst, tmWo, (cta & 3) * 128 + (j & 1) * 64, (j >> 1) * 64, wb);
        const uint32_t mb = smem_u32(&ms.moe);
        if (cta < NFFN) {
            mbar_expect_tx(mb, 2048);
            tma_2d(dst + 8192, (j & 8) ? tmU : tmG, cta * 16, (j & 7) * 64, mb);
        }
    }
    __syncwarp();
    return true;
}

__device__ __forceinline__ void guarded_item(char* smem, Misc& ms, int r, int t) {
    const int tid = threadIdx.x, lane = tid & 31, w4 = (tid >> 5) & 3;
    const uint64_t descK0 = make_desc(smem_u32(smem), 128, 256, 0);
    const uint64_t descV0 = make_desc(smem_u32(smem + 4096), 128, 2048, 0);
    uint32_t q[4];
    {
        const uint32_t* Qs = reinterpret_cast<const uint32_t*>(smem + SM_Q + t * 2048 + w4 * 512);
        q[0] = Qs[lane]; q[2] = Qs[32 + lane]; q[1] = Qs[64 + lane]; q[3] = Qs[96 + lane];
    }
    float* st = reinterpret_cast<float*>(smem + SM_A3) + t * (12 * 128) + (tid & 127);
    float o[12];
#pragma unroll
    for (int i = 0; i < 8; i++) o[i] = r > 0 ? st[i * 128] : 0.f;
    o[8] = r > 0 ? st[8 * 128] : 0.f; o[10] = r > 0 ? st[9 * 128] : 0.f; o[9] = 0.f; o[11] = 0.f;
    float m0 = r > 0 ? st[10 * 128] : -INFINITY, m1 = r > 0 ? st[11 * 128] : -INFINITY;
#pragma unroll 1
    for (int jh = 2 * CPI * r; jh < 2 * CPI * (r + 1); jh++) {
        const int j = jh >> 1;
        mbar_wait(smem_u32(&ms.kv[j]), 0);
        float s[32];
        const uint32_t off = j * (KV_CHUNK >> 4);
        wg_fence();
        wgmma_qk64_f32(s, q, descK0 + (uint64_t)(off + (jh & 1) * 128));
        wg_commit();
        wg_wait<0>();
        pin(s);
        pin(o);
        if ((jh & 1) == 0 && j > CPI * r) release_kv_chunk(ms, j - 1, lane);
        float n0 = m0, n1 = m1;
#pragma unroll
        for (int i = 0; i < 8; i++) {
            n0 = fmaxf(n0, fmaxf(s[4 * i], s[4 * i + 1]));
            n1 = fmaxf(n1, fmaxf(s[4 * i + 2], s[4 * i + 3]));
        }
        n0 = fmaxf(n0, __shfl_xor_sync(0xffffffffu, n0, 1)); n0 = fmaxf(n0, __shfl_xor_sync(0xffffffffu, n0, 2));
        n1 = fmaxf(n1, __shfl_xor_sync(0xffffffffu, n1, 1)); n1 = fmaxf(n1, __shfl_xor_sync(0xffffffffu, n1, 2));
        const float a0 = ex2_mufu(m0 - n0), a1 = ex2_mufu(m1 - n1);
        m0 = n0; m1 = n1;
#pragma unroll
        for (int i = 0; i < 3; i++) { o[4 * i] *= a0; o[4 * i + 1] *= a0; o[4 * i + 2] *= a1; o[4 * i + 3] *= a1; }
        const float e0 = n0 - LOG2C_ODD, e1 = n1 - LOG2C_ODD;
#pragma unroll
        for (int k = 0; k < 4; k++) {
            const uint32_t p0 = pack_bf16(ex2_mufu(s[8 * k] - n0), ex2_mufu(s[8 * k + 1] - n0));
            const uint32_t p1 = pack_bf16(ex2_mufu(s[8 * k + 2] - n1), ex2_mufu(s[8 * k + 3] - n1));
            const uint32_t p2 = pack_bf16(ex2_mufu(s[8 * k + 4] - e0), ex2_mufu(s[8 * k + 5] - e0));
            const uint32_t p3 = pack_bf16(ex2_mufu(s[8 * k + 6] - e1), ex2_mufu(s[8 * k + 7] - e1));
            wg_fence();
            wgmma_pv24(o, p0, p1, p2, p3, descV0 + (uint64_t)(off + ((jh & 1) * 4 + k) * 16));
            wg_commit();
            wg_wait<0>();
            pin(o);
        }
    }
#pragma unroll
    for (int i = 0; i < 8; i++) st[i * 128] = o[i];
    st[8 * 128] = o[8]; st[9 * 128] = o[10]; st[10 * 128] = m0; st[11 * 128] = m1;
}

__global__ void __launch_bounds__(512, 1)
mega_kernel(const __grid_constant__ CUtensorMap tmX, const __grid_constant__ CUtensorMap tmW,
            const __grid_constant__ CUtensorMap tmO, const __grid_constant__ CUtensorMap tmWo,
            const __grid_constant__ CUtensorMap tmG, const __grid_constant__ CUtensorMap tmU, const __grid_constant__ CUtensorMap tmOut,
            const __nv_bfloat16* __restrict__ x, const __nv_bfloat16* __restrict__ wqkv, const __nv_bfloat16* __restrict__ wo,
            const __nv_bfloat16* __restrict__ w_r, const __nv_bfloat16* __restrict__ w_gate,
            const __nv_bfloat16* __restrict__ w_up, const __nv_bfloat16* __restrict__ w_down,
            __nv_bfloat16* __restrict__ out) {
    extern __shared__ __align__(1024) char smem[];
    Misc& ms = *reinterpret_cast<Misc*>(smem + SM_MISC);
    const int tid = threadIdx.x, lane = tid & 31;
    const int warp = __shfl_sync(0xffffffffu, tid >> 5, 0);
    const int wg = warp >> 2, w4 = warp & 3, g = lane >> 2, t4 = lane & 3;
    const int cta = blockIdx.x;
    const int rb = cta >> 3, hg = cta & 7;

    if (warp == 12) {
        if (lane == 0) {
            TS(0);
            if (smem_u32(smem) & 1023) __trap();
            for (int i = 0; i < P1_STAGES; i++) { mbar_init(smem_u32(&ms.p1_full[i]), 1); mbar_init(smem_u32(&ms.p1_empty[i]), 8); }
            asm volatile("fence.mbarrier_init.release.cluster;" ::: "memory");
        }
        __syncwarp();
        bar_arrive(13, 288);
        bar_arrive(14, 256);
    } else {
        if (tid == 32) {
            for (int i = 0; i < 16; i++) mbar_init(smem_u32(&ms.kv[i]), 1);
            for (int i = 0; i < 8; i++) { mbar_init(smem_u32(&ms.wo[i]), 2); mbar_init(smem_u32(&ms.a3[i]), 1); }
            mbar_init(smem_u32(&ms.moe), 16);
            for (int i = 0; i < 16; i++) ms.freed[i] = 0;
            for (int i = 0; i < 8; i++) ms.seq[i] = 0;
            ms.item = 4;
            mbar_init(smem_u32(&ms.qbar), 1);
            asm volatile("fence.mbarrier_init.release.cluster;" ::: "memory");
        }
        if (tid >= 64 && tid < 76) ms.norm[tid - 64] = 0;
        if (tid >= 96 && tid < 101) {
            const CUtensorMap* tm = tid == 96 ? &tmO : tid == 97 ? &tmWo : tid == 98 ? &tmG : tid == 99 ? &tmU : &tmOut;
            asm volatile("prefetch.tensormap [%0];" ::"l"(tm) : "memory");
        }
        if (tid == 416) ms.tag = __ldcg(&gEpoch) + 1u;
    }

    if (wg < 2) {
        asm volatile("setmaxnreg.inc.sync.aligned.u32 160;");
        float acc[96];
#pragma unroll
        for (int i = 0; i < 96; i++) acc[i] = 0.f;
        bar_sync(13, 288);
#pragma unroll 1
        for (int kc = 0; kc < 8; kc++) {
            const int s = kc % P1_STAGES;
            mbar_wait(smem_u32(&ms.p1_full[s]), (kc / P1_STAGES) & 1);
            if (tid == 0) TS(24 + kc);
            const uint32_t sa = smem_u32(smem + s * P1_STAGE_BYTES), sb = sa + 16384;
            const uint64_t da = make_desc(sa + wg * 8192, 16, 1024, 1);
            const uint64_t db = make_desc(sb, 8192, 1024, 1);
            wg_fence();
#pragma unroll
            for (int ks = 0; ks < 4; ks++) wgmma_n192(acc, da + ks * 2, db + ks * 128);
            wg_commit();
            wg_wait<0>();
            if (lane == 0) mbar_arrive(smem_u32(&ms.p1_empty[s]));
        }
        pin(acc);
        if (tid == 0) TS(1);
        bar_sync(1, 480);
        const unsigned int tag = ms.tag;
        if (tid == 0) TS(16);
        const int lr0 = wg * 64 + w4 * 16 + g, lr1 = lr0 + 8;
        const float mu0 = ms.p1.mu[lr0], mu1 = ms.p1.mu[lr1], rs0 = ms.p1.rs[lr0], rs1 = ms.p1.rs[lr1];
        const int lg0 = wg * 8 + w4 * 2;
        const int rg0 = rb * 16 + lg0;
#pragma unroll
        for (int hh = 0; hh < 4; hh++) {
            const int head = hg * 4 + hh;
            float nrm[3];
#pragma unroll
            for (int sec = 0; sec < 3; sec++) {
                float sq0 = 0.f, sq1 = 0.f, vm = 0.f;
#pragma unroll
                for (int db = 0; db < 2; db++) {
                    const int j = sec * 8 + hh * 2 + db;
                    const float2 c = *reinterpret_cast<const float2*>(&ms.p1.cs[j * 8 + 2 * t4]);
                    const float f0 = sec == 0 ? rs0 * QSCALE : rs0, f1 = sec == 0 ? rs1 * QSCALE : rs1;
                    const float a0 = (acc[4 * j + 0] - mu0 * c.x) * f0, a1 = (acc[4 * j + 1] - mu0 * c.y) * f0;
                    const float b0 = (acc[4 * j + 2] - mu1 * c.x) * f1, b1 = (acc[4 * j + 3] - mu1 * c.y) * f1;
                    const uint32_t pa = sec < 2 ? pack_f16_sat(a0, a1) : pack_bf16(a0, a1);
                    const uint32_t pb = sec < 2 ? pack_f16_sat(b0, b1) : pack_bf16(b0 * VSCALE_ODD, b1 * VSCALE_ODD);
                    if (sec < 2) {
                        uint32_t* dst = sec == 0 ? reinterpret_cast<uint32_t*>(gQ) + ((size_t)head * S_LEN * DH + rg0 * 128) / 2
                                                 : reinterpret_cast<uint32_t*>(gKV) + (size_t)(head * 16 + rb) * 2048 + lg0 * 64;
                        dst[db * 32 + lane] = pa;
                        dst[64 + db * 32 + lane] = pb;
                        sq0 = fmaf(a0, a0, fmaf(a1, a1, sq0));
                        sq1 = fmaf(b0, b0, fmaf(b1, b1, sq1));
                    } else {
                        uint32_t* dst = reinterpret_cast<uint32_t*>(gKV) + (size_t)(head * 16 + rb) * 2048 + 1024 + db * 512 + lg0 * 32;
                        dst[lane] = pa;
                        dst[32 + lane] = pb;
                        vm = fmaxf(vm, fmaxf(fmaxf(fabsf(a0), fabsf(a1)), fmaxf(fabsf(b0), fabsf(b1))));
                        if (!(a0 + a1 + b0 + b1 == a0 + a1 + b0 + b1)) vm = __int_as_float(0x7f800000);
                    }
                }
                if (sec < 2) {
                    sq0 += __shfl_xor_sync(0xffffffffu, sq0, 1); sq0 += __shfl_xor_sync(0xffffffffu, sq0, 2);
                    sq1 += __shfl_xor_sync(0xffffffffu, sq1, 1); sq1 += __shfl_xor_sync(0xffffffffu, sq1, 2);
                    vm = fmaxf(sq0, sq1);
                    if (!(sq0 + sq1 < 3.0e38f)) vm = __int_as_float(0x7f800000);
                }
                nrm[sec] = vm;
            }
            const unsigned int a = __reduce_max_sync(0xffffffffu, __float_as_uint(nrm[0]));
            const unsigned int b = __reduce_max_sync(0xffffffffu, __float_as_uint(nrm[1]));
            const unsigned int c = __reduce_max_sync(0xffffffffu, __float_as_uint(nrm[2]));
            if (lane == 0) { atomicMax(&ms.norm[hh * 3 + 0], a); atomicMax(&ms.norm[hh * 3 + 1], b); atomicMax(&ms.norm[hh * 3 + 2], c); }
        }
        if (tid == 0) TS(17);
        bar_sync(2, 256);
        if (tid == 0) TS(18);
        if (tid < 4) {
            fence_gpu();
            st_pkt(&gFlagQKV[(hg * 16 + rb) * 4 + tid], make_uint4(ms.norm[tid * 3], ms.norm[tid * 3 + 1], ms.norm[tid * 3 + 2], tag));
            if (tid == 0) TS(2);
        }
        asm volatile("setmaxnreg.dec.sync.aligned.u32 128;");
        bar_sync(15, 512);
    } else {
      asm volatile("setmaxnreg.dec.sync.aligned.u32 96;");
      if (wg == 2) {
        const int t = tid - 256;
        if (t < 4) gFlagQKV[(hg * 16 + rb) * 4 + t] = make_uint4(0u, 0u, 0u, 0u);
        bar_sync(14, 256);
        mbar_wait(smem_u32(&ms.p1_full[0]), 0);
        {
            const int row = rb * 128 + hg * 16 + (t >> 3), j = t & 7;
            const uint4* xp = reinterpret_cast<const uint4*>(x + (size_t)row * DM);
            uint4 v[8];
#pragma unroll
            for (int i = 0; i < 8; i++) v[i] = __ldg(xp + i * 8 + j);
            float s1 = 0.f;
#pragma unroll
            for (int i = 0; i < 8; i++) {
                const uint32_t w[4] = {v[i].x, v[i].y, v[i].z, v[i].w};
#pragma unroll
                for (int e = 0; e < 4; e++) s1 += bf_lo(w[e]) + bf_hi(w[e]);
            }
            s1 += __shfl_xor_sync(0xffffffffu, s1, 1); s1 += __shfl_xor_sync(0xffffffffu, s1, 2); s1 += __shfl_xor_sync(0xffffffffu, s1, 4);
            const float mu = s1 * (1.f / DM);
            float s2 = 0.f;
#pragma unroll
            for (int i = 0; i < 8; i++) {
                const uint32_t w[4] = {v[i].x, v[i].y, v[i].z, v[i].w};
#pragma unroll
                for (int e = 0; e < 4; e++) {
                    const float a = bf_lo(w[e]) - mu, b = bf_hi(w[e]) - mu;
                    s2 = fmaf(a, a, fmaf(b, b, s2));
                }
            }
            s2 += __shfl_xor_sync(0xffffffffu, s2, 1); s2 += __shfl_xor_sync(0xffffffffu, s2, 2); s2 += __shfl_xor_sync(0xffffffffu, s2, 4);
            bar_sync(11, 224);
            if (j == 0) st_pkt(&gStat1[row], make_uint4(__float_as_uint(mu), __float_as_uint(rsqrtf(s2 * (1.f / DM) + LN_EPS)), 0u, ms.tag));
        }
        const unsigned int tag = ms.tag;
        if (t == 0) TS(32);
        uint4 st[1];
        if (t < 8) wait_pkts<1, 0xffffffffu>(&gStat1[rb * 128 + t * 16 + 15], 0, tag, st);
        bar_sync(12, 128);
        wait_pkts<1, 0xffffffffu>(&gStat1[rb * 128 + t], 0, tag, st);
        if (t == 0) TS(34);
        ms.p1.mu[t] = __uint_as_float(st[0].x);
        ms.p1.rs[t] = __uint_as_float(st[0].y);
        bar_arrive(1, 480);
        {
            const uint4 z = make_uint4(0u, 0u, 0u, 0u);
            if (t < 64) { gCand[cta * 64 + t] = z; gPart[cta * 64 + t] = z; gCandRow[cta * 64 + t] = z; }
            gYPart[cta * 224 + t] = z;
            if (t < 96) gYPart[cta * 224 + 128 + t] = z;
            if (t < 2) {
                reinterpret_cast<uint4*>(gFlagO)[cta * 2 + t] = z;
                reinterpret_cast<uint4*>(gFlagOut)[cta * 2 + t] = z;
            }
        }
      } else if (warp == 12) {
        if (lane == 0) {
#pragma unroll 1
            for (int kc = 0; kc < 8; kc++) {
                const int s = kc % P1_STAGES;
                if (kc >= P1_STAGES) mbar_wait(smem_u32(&ms.p1_empty[s]), 0);
                const uint32_t bar = smem_u32(&ms.p1_full[s]);
                const uint32_t sa = smem_u32(smem + s * P1_STAGE_BYTES), sb = sa + 16384;
                mbar_expect_tx(bar, P1_STAGE_BYTES);
                tma_2d(sa, &tmX, kc * 64, rb * 128, bar);
#pragma unroll
                for (int p = 0; p < 3; p++) tma_2d(sb + p * 8192, &tmW, p * 512 + hg * 64, kc * 64, bar);
            }
        }
      } else {
        const int t = tid - 416;
        bar_sync(14, 256);
        mbar_wait(smem_u32(&ms.p1_full[0]), 0);
        const int c16 = t >> 2, rs = t & 3;
        const __nv_bfloat16* wp = wqkv + (size_t)(rb * 32 + rs) * (3 * DM) + (c16 >> 3) * 512 + hg * 64 + (c16 & 7) * 8;
        uint4 v[8];
#pragma unroll
        for (int i = 0; i < 8; i++) v[i] = __ldg(reinterpret_cast<const uint4*>(wp + (size_t)i * 4 * (3 * DM)));
        float a[8] = {};
#pragma unroll
        for (int i = 0; i < 8; i++) {
            a[0] += bf_lo(v[i].x); a[1] += bf_hi(v[i].x); a[2] += bf_lo(v[i].y); a[3] += bf_hi(v[i].y);
            a[4] += bf_lo(v[i].z); a[5] += bf_hi(v[i].z); a[6] += bf_lo(v[i].w); a[7] += bf_hi(v[i].w);
        }
#pragma unroll
        for (int e = 0; e < 8; e++) { a[e] += __shfl_xor_sync(0xffffffffu, a[e], 1); a[e] += __shfl_xor_sync(0xffffffffu, a[e], 2); }
        bar_sync(11, 224);
        const unsigned int tag = ms.tag;
        const int pk = c16 * 2 + rs;
        if (rs < 2) st_pkt(&gCsPart[(hg * 16 + rb) * 48 + pk], embed_tag(rs ? a[4] : a[0], rs ? a[5] : a[1], rs ? a[6] : a[2], rs ? a[7] : a[3], tag));
        if (t == 0) TS(35);
        if (t < 16) { uint4 gate[1]; wait_pkts4<1>(&gCsPart[(hg * 16 + t) * 48 + 47], 0, tag, gate); }
        bar_sync(8, 96);
        if (t == 0) TS(36);
        if (rs < 2) {
            uint4 p[16];
            wait_pkts4<16>(&gCsPart[hg * 16 * 48 + pk], 48, tag, p);
            float s0 = 0.f, s1 = 0.f, s2 = 0.f, s3 = 0.f;
#pragma unroll
            for (int i = 0; i < 16; i++) {
                s0 += __uint_as_float(p[i].x); s1 += __uint_as_float(p[i].y); s2 += __uint_as_float(p[i].z); s3 += __uint_as_float(p[i].w);
            }
            *reinterpret_cast<float4*>(&ms.p1.cs[pk * 4]) = make_float4(s0, s1, s2, s3);
            if (t == 0) TS(37);
        }
        __syncwarp();
        bar_arrive(1, 480);
      }
      __syncwarp();
      bar_sync(15, 512);
      asm volatile("setmaxnreg.inc.sync.aligned.u32 128;");
    }
    if (tid == 0) TS(20);
    const unsigned int tag = ms.tag;

    const int head = hg * 4 + (rb >> 2), quarter = rb & 3;
    {
#pragma unroll
        for (int i = 0; i < 4; i++) {
            const int e = tid + i * 512;
            *reinterpret_cast<uint4*>(smem + (e >> 7) * KV_CHUNK + 8192 + (e & 127) * 16) = make_uint4((e & 8) ? 0x00003F35u : 0x00003F80u, 0, 0, 0);
        }
        asm volatile("fence.proxy.async.shared::cta;" ::: "memory");
    }
    if (warp == 0) {
        uint4 n[1];
        wait_pkts<1, 0xffffffffu>(&gFlagQKV[(hg * 16 + (lane & 15)) * 4 + (rb >> 2)], 0, tag, n);
        __syncwarp();
        if (lane == 0) TS(21);
        const float q2 = __uint_as_float(__reduce_max_sync(0xffffffffu, n[0].x));
        const float k2 = __uint_as_float(__reduce_max_sync(0xffffffffu, n[0].y));
        const float vm = __uint_as_float(__reduce_max_sync(0xffffffffu, n[0].z));
        if (lane == 0) ms.fast = (q2 * k2 * 1.02f <= 812.f) && (q2 <= 1.0e6f) && (k2 <= 1.0e6f) && (vm <= 1.0e18f) && (vm >= 1.0e-18f || vm == 0.f);
    }
    __syncthreads();
    if (lane == 0) {
        fence_proxy_async_global();
        if (warp == 1) {
            mbar_expect_tx(smem_u32(&ms.qbar), 16384);
            bulk_g2s(smem_u32(smem + SM_Q), reinterpret_cast<const char*>(gQ) + (size_t)head * 65536 + quarter * 16384, 16384, smem_u32(&ms.qbar));
        }
        const uint32_t bar = smem_u32(&ms.kv[warp]);
        mbar_expect_tx(bar, 8192);
        bulk_g2s(smem_u32(smem + warp * KV_CHUNK), reinterpret_cast<const char*>(gKV) + (size_t)(head * 16 + warp) * 8192, 8192, bar);
    }
    if (tid == 0) TS(3);
    bool refilled = false;
    {
        const bool fast = ms.fast != 0;
        const uint64_t descKe = make_desc(smem_u32(smem), 128, 512, 0);
        const uint64_t descKo = make_desc(smem_u32(smem) + 256, 128, 512, 0);
        const uint64_t descV0 = make_desc(smem_u32(smem + 4096), 128, 2048, 0);
        auto release_chunk = [&](int j) { release_kv_chunk(ms, j, lane); };
        float* sAcc = reinterpret_cast<float*>(smem + SM_A3);
        const int t128 = tid & 127;
        mbar_wait(smem_u32(&ms.qbar), 0);
        auto run_items = [&](auto FAST) {
        int item = wg * NR;
#pragma unroll 1
        while (item < 8 * NR) {
            const int r = item % NR, t = item / NR;
            if (t128 == 0) ms.nxt[wg] = ((item % NR) == NR - 1) ? item + 3 * NR + 1 : item + 1;
            if (r > 0) {
                int it = 0;
                unsigned int sq;
                while (true) {
                    asm volatile("ld.acquire.cta.shared.u32 %0, [%1];" : "=r"(sq) : "r"(smem_u32(&ms.seq[t])) : "memory");
                    if (sq >= (unsigned int)r) break;
                    if (++it > SPIN_LIMIT) __trap();
                }
            }
            uint32_t q[4];
            {
                const uint32_t* Qs = reinterpret_cast<const uint32_t*>(smem + SM_Q + t * 2048 + w4 * 512);
                q[0] = Qs[lane]; q[2] = Qs[32 + lane]; q[1] = Qs[64 + lane]; q[3] = Qs[96 + lane];
            }
            float* st = sAcc + t * (12 * 128) + t128;
            float o[12];
#pragma unroll
            for (int i = 0; i < 8; i++) o[i] = r > 0 ? st[i * 128] : 0.f;
            o[8] = r > 0 ? st[8 * 128] : 0.f; o[10] = r > 0 ? st[9 * 128] : 0.f; o[9] = 0.f; o[11] = 0.f;
            if constexpr (decltype(FAST)::value) {
#pragma unroll 1
                for (int j = CPI * r; j < CPI * (r + 1); j++) {
                    mbar_wait(smem_u32(&ms.kv[j]), 0);
                    float s[32];
                    uint32_t h[16];
                    wg_fence();
                    wgmma_qk64_f32(s, q, descKe + (uint64_t)(j * (KV_CHUNK >> 4)));
                    wgmma_qk64_f16(h, q, descKo + (uint64_t)(j * (KV_CHUNK >> 4)));
                    wg_commit();
                    wg_wait<0>();
                    pin(s);
                    pin(h);
                    if (j > CPI * r) release_chunk(j - 1);
                    if (!refilled && j > warp) refilled = refill_kv_chunk(smem, ms, warp, cta, lane, &tmWo, &tmG, &tmU);
#pragma unroll
                    for (int kg = 0; kg < 8 / PVG; kg++) {
                        uint32_t p[4 * PVG];
#pragma unroll
                        for (int u = 0; u < PVG; u++) {
                            const int k = kg * PVG + u;
                            p[4 * u + 0] = pack_bf16(ex2_mufu(s[4 * k]), ex2_mufu(s[4 * k + 1]));
                            p[4 * u + 1] = pack_bf16(ex2_mufu(s[4 * k + 2]), ex2_mufu(s[4 * k + 3]));
                            p[4 * u + 2] = ex2_pair_h16(h[2 * k]);
                            p[4 * u + 3] = ex2_pair_h16(h[2 * k + 1]);
                        }
                        wg_fence();
#pragma unroll
                        for (int u = 0; u < PVG; u++)
                            wgmma_pv24(o, p[4 * u], p[4 * u + 1], p[4 * u + 2], p[4 * u + 3],
                                       descV0 + (uint64_t)(j * (KV_CHUNK >> 4) + (kg * PVG + u) * 16));
                        wg_commit();
                        wg_wait<PVWAIT>();
                    }
                }
                wg_wait<0>();
                pin(o);
            } else {
                guarded_item(smem, ms, r, t);
#pragma unroll
                for (int i = 0; i < 8; i++) o[i] = st[i * 128];
                o[8] = st[8 * 128]; o[10] = st[9 * 128];
            }
            release_chunk(CPI * r + CPI - 1);
            if (r < NR - 1) {
#pragma unroll
                for (int i = 0; i < 8; i++) st[i * 128] = o[i];
                st[8 * 128] = o[8]; st[9 * 128] = o[10];
            } else {
                const float l0 = __shfl_sync(0xffffffffu, o[8], lane & ~3), l1 = __shfl_sync(0xffffffffu, o[10], lane & ~3);
                const float r0 = __fdividef(1.f, l0), r1 = __fdividef(1.f, l1);
                uint32_t* Op = reinterpret_cast<uint32_t*>(gO + (size_t)(quarter * 512 + t * 64 + w4 * 16) * DM + head * DH);
                Op[g * 256 + t4] = pack_bf16(o[0] * r0, o[1] * r0);
                Op[(g + 8) * 256 + t4] = pack_bf16(o[2] * r1, o[3] * r1);
                Op[g * 256 + 4 + t4] = pack_bf16(o[4] * r0, o[5] * r0);
                Op[(g + 8) * 256 + 4 + t4] = pack_bf16(o[6] * r1, o[7] * r1);
            }
            bar_sync(3 + wg, 128);
            if (t128 == 0) asm volatile("st.release.cta.shared.u32 [%0], %1;" ::"r"(smem_u32(&ms.seq[t])), "r"(r + 1) : "memory");
            if (r == 0 && t == 3 && tid == 511) {
                bulk_prefetch_l2(reinterpret_cast<const char*>(w_down) + cta * 14336, 14336);
            }
            if (!refilled) refilled = refill_kv_chunk(smem, ms, warp, cta, lane, &tmWo, &tmG, &tmU);
            item = ms.nxt[wg];
            bar_sync(3 + wg, 128);
        }
        };
        if (fast) run_items(std::true_type{}); else run_items(std::false_type{});
    }
    __syncthreads();
    if (!refilled) refill_kv_chunk(smem, ms, warp, cta, lane, &tmWo, &tmG, &tmU);
    if (warp == 0 && lane < 8) { fence_gpu(); asm volatile("st.relaxed.gpu.global.u32 [%0], %1;" ::"l"(&gFlagO[(quarter * 8 + lane) * 32 + head]), "r"(tag) : "memory"); }
    if (tid == 0) TS(4);

    const int rb3 = cta >> 2, cb = cta & 3;
    if (wg < 2) {
        const int r0 = rb3 * 64 + w4 * 16 + g, r1 = r0 + 8;
        const int col0 = cb * 128 + wg * 64 + 2 * t4;
        uint32_t xa[8], xb[8], wr[8];
#pragma unroll
        for (int j = 0; j < 8; j++) {
            xa[j] = __ldg(reinterpret_cast<const uint32_t*>(x + (size_t)r0 * DM + col0 + j * 8));
            xb[j] = __ldg(reinterpret_cast<const uint32_t*>(x + (size_t)r1 * DM + col0 + j * 8));
            wr[j] = __ldg(reinterpret_cast<const uint32_t*>(w_r + col0 + j * 8));
        }
        const float p0 = __bfloat162float(x[(size_t)r0 * DM]), p1 = __bfloat162float(x[(size_t)r1 * DM]);
        const float pivot = __bfloat162float(x[(size_t)(rb3 * 64 + (tid >> 2)) * DM]);
        float wsum = 0.f;
        {
            const uint4 a = __ldg(reinterpret_cast<const uint4*>(w_r) + lane), b = __ldg(reinterpret_cast<const uint4*>(w_r) + 32 + lane);
            const uint32_t w[8] = {a.x, a.y, a.z, a.w, b.x, b.y, b.z, b.w};
#pragma unroll
            for (int e = 0; e < 8; e++) wsum += bf_lo(w[e]) + bf_hi(w[e]);
#pragma unroll
            for (int m = 16; m; m >>= 1) wsum += __shfl_xor_sync(0xffffffffu, wsum, m);
        }
        float acc[32];
#pragma unroll
        for (int i = 0; i < 32; i++) acc[i] = 0.f;
#pragma unroll 1
        for (int kc = 0; kc < 8; kc++) {
            mbar_wait(smem_u32(&ms.wo[kc]), 0);
            mbar_wait(smem_u32(&ms.a3[kc]), 0);
            const uint64_t da = make_desc(smem_u32(smem + SM_A3 + kc * 8192), 16, 1024, 1);
            const uint64_t db = make_desc(smem_u32(smem + (kc * 2 + wg) * KV_CHUNK), 8192, 1024, 1);
            wg_fence();
#pragma unroll
            for (int ks = 0; ks < 4; ks++) wgmma_n64(acc, da + ks * 2, db + ks * 128);
            wg_commit();
        }
        wg_wait<0>();
        pin(acc);
        if (tid == 0) TS(6);
        float s1a = 0.f, s2a = 0.f, s3a = 0.f, s1b = 0.f, s2b = 0.f, s3b = 0.f;
#pragma unroll
        for (int j = 0; j < 8; j++) {
            const uint32_t ha = pack_bf16(bf_lo(xa[j]) + acc[4 * j], bf_hi(xa[j]) + acc[4 * j + 1]);
            const uint32_t hb = pack_bf16(bf_lo(xb[j]) + acc[4 * j + 2], bf_hi(xb[j]) + acc[4 * j + 3]);
            xa[j] = ha; xb[j] = hb;
            const float w0 = bf_lo(wr[j]), w1 = bf_hi(wr[j]);
            const float da0 = bf_lo(ha) - p0, da1 = bf_hi(ha) - p0, db0 = bf_lo(hb) - p1, db1 = bf_hi(hb) - p1;
            s1a += da0 + da1; s2a = fmaf(da0, da0, fmaf(da1, da1, s2a)); s3a = fmaf(da0, w0, fmaf(da1, w1, s3a));
            s1b += db0 + db1; s2b = fmaf(db0, db0, fmaf(db1, db1, s2b)); s3b = fmaf(db0, w0, fmaf(db1, w1, s3b));
        }
#pragma unroll
        for (int m = 1; m <= 2; m <<= 1) {
            s1a += __shfl_xor_sync(0xffffffffu, s1a, m); s2a += __shfl_xor_sync(0xffffffffu, s2a, m); s3a += __shfl_xor_sync(0xffffffffu, s3a, m);
            s1b += __shfl_xor_sync(0xffffffffu, s1b, m); s2b += __shfl_xor_sync(0xffffffffu, s2b, m); s3b += __shfl_xor_sync(0xffffffffu, s3b, m);
        }
        if (t4 == 0) {
            const int lr = w4 * 16 + g;
            ms.p3.part[wg][lr][0] = s1a; ms.p3.part[wg][lr][1] = s2a; ms.p3.part[wg][lr][2] = s3a;
            ms.p3.part[wg][lr + 8][0] = s1b; ms.p3.part[wg][lr + 8][1] = s2b; ms.p3.part[wg][lr + 8][2] = s3b;
        }
        if (tid == 0) TS(11);
        bar_sync(1, 256);
        if (tid == 0) TS(12);
        if (tid < 64) {
            st_pkt(&gPart[(rb3 * 64 + tid) * 4 + cb],
                   make_uint4(__float_as_uint(ms.p3.part[0][tid][0] + ms.p3.part[1][tid][0]), __float_as_uint(ms.p3.part[0][tid][1] + ms.p3.part[1][tid][1]),
                              __float_as_uint(ms.p3.part[0][tid][2] + ms.p3.part[1][tid][2]), tag));
        }
        {
            const int lr = tid >> 2, sl = tid & 3;
            uint4 pv[1];
            wait_pkts<1, 0xffffffffu>(&gPart[rb3 * 256 + tid], 0, tag, pv);
            float s1 = __uint_as_float(pv[0].x), s2 = __uint_as_float(pv[0].y), s3 = __uint_as_float(pv[0].z);
            if (tid == 0) TS(14);
#pragma unroll
            for (int m = 1; m <= 2; m <<= 1) {
                s1 += __shfl_xor_sync(0xffffffffu, s1, m); s2 += __shfl_xor_sync(0xffffffffu, s2, m); s3 += __shfl_xor_sync(0xffffffffu, s3, m);
            }
            if (sl == 0) {
                const float md = s1 * (1.f / DM);
                const float var = fmaxf(s2 * (1.f / DM) - md * md, 0.f);
                const float rs = rsqrtf(var + LN_EPS);
                ms.p3.mu[lr] = pivot + md;
                ms.p3.rs[lr] = rs;
                ms.p3.r[lr] = (s3 - md * wsum) * rs;
            }
        }
        bar_sync(1, 256);
        if (tid == 0) TS(7);
        {
            unsigned int i1, i2;
            warp_top2(f2ord(ms.p3.r[lane]), lane, f2ord(ms.p3.r[lane + 32]), lane + 32, i1, i2);
            if (cb == 0) {
                const int c = tid & 1, li = c ? i2 : i1;
                st_pkt(&gCand[(tid >> 1) * 64 + rb3 * 2 + c],
                       make_uint4(__float_as_uint(ms.p3.r[li]), __float_as_uint(ms.p3.mu[li]), __float_as_uint(ms.p3.rs[li]),
                                  (tag << 11) | (unsigned int)(rb3 * 64 + li)));
            }
#pragma unroll
            for (int c = 0; c < 2; c++) {
                const unsigned int li = c ? i2 : i1;
                if ((int)(li >> 4) == w4 && (int)(li & 7) == g) {
                    const bool hi = (li & 8) != 0;
                    uint4* dst = &gCandRow[(rb3 * 2 + c) * 128 + (cb * 2 + wg) * 16 + t4];
#pragma unroll
                    for (int q = 0; q < 4; q++)
                        st_pkt(dst + q * 4, make_uint4(hi ? xb[2 * q] : xa[2 * q], hi ? xb[2 * q + 1] : xa[2 * q + 1], 0u, tag));
                }
            }
            if (tid == 0) TS(15);
        }
        {
            const int lr0 = w4 * 16 + g;
            const float mu0 = ms.p3.mu[lr0], rs0 = ms.p3.rs[lr0], mu1 = ms.p3.mu[lr0 + 8], rs1 = ms.p3.rs[lr0 + 8];
            char* so = smem + wg * KV_CHUNK;
#pragma unroll
            for (int j = 0; j < 8; j++) {
                const float a0 = bf_lo(xa[j]), a1 = bf_hi(xa[j]), b0 = bf_lo(xb[j]), b1 = bf_hi(xb[j]);
                const uint32_t la = pack_bf16((a0 - mu0) * rs0, (a1 - mu0) * rs0);
                const uint32_t lb = pack_bf16((b0 - mu1) * rs1, (b1 - mu1) * rs1);
                const int o = ((j ^ g) << 4) + t4 * 4;
                *reinterpret_cast<uint32_t*>(so + lr0 * 128 + o) = pack_bf16(a0 + bf_lo(la), a1 + bf_hi(la));
                *reinterpret_cast<uint32_t*>(so + (lr0 + 8) * 128 + o) = pack_bf16(b0 + bf_lo(lb), b1 + bf_hi(lb));
            }
            asm volatile("fence.proxy.async.shared::cta;" ::: "memory");
            bar_sync(3 + wg, 128);
            if ((tid & 127) == 0) {
                tma_store_2d(&tmOut, smem_u32(so), cb * 128 + wg * 64, rb3 * 64);
                asm volatile("cp.async.bulk.wait_group 0;" ::: "memory");
                st_flag(&gFlagOut[cta * 8 + wg], tag);
            }
        }
    } else {
        const int t = tid - 256;
        {
            const int kc = warp - 8;
            if (lane == 0) {
                int it = 0;
                while (true) {
                    const uint4 f = ld_pkt(reinterpret_cast<const uint4*>(&gFlagO[rb3 * 32 + kc * 4]));
                    if (f.x == tag && f.y == tag && f.z == tag && f.w == tag) break;
                    if (++it > SPIN_LIMIT) __trap();
                    BACKOFF();
                }
                if (kc == 7) TS(5);
                fence_proxy_async_global();
                const uint32_t bar = smem_u32(&ms.a3[kc]);
                mbar_expect_tx(bar, 8192);
                tma_2d(smem_u32(smem + SM_A3 + kc * 8192), &tmO, kc * 64, rb3 * 64, bar);
            }
            __syncwarp();
        }
        uint32_t wd[16];
        if (cta < NFFN) {
#pragma unroll
            for (int k = 0; k < 16; k++) wd[k] = __ldg(reinterpret_cast<const uint32_t*>(w_down + (size_t)(cta * 16 + k) * DM + 2 * t));
        }
        if (warp == 8) {
            if (lane == 0) TS(56);
            uint4 cv[2];
            wait_pkts<2, 0xfffff800u>(&gCand[cta * 64 + lane * 2], 1, tag << 11, cv);
            if (lane == 0) TS(54);
            unsigned int i1, i2;
            warp_top2(f2ord(__uint_as_float(cv[0].x)), cv[0].w & 0x7ffu, f2ord(__uint_as_float(cv[1].x)), cv[1].w & 0x7ffu, i1, i2);
#pragma unroll
            for (int c = 0; c < 2; c++) {
                const unsigned int ci = cv[c].w & 0x7ffu;
                if (ci == i1 || ci == i2) {
                    const int o = ci == i1 ? 0 : 1;
                    ms.idx[o] = (int)ci;
                    ms.cslot[o] = lane * 2 + c;
                    *reinterpret_cast<float4*>(&ms.sel[o * 4]) =
                        make_float4(__uint_as_float(cv[c].y), __uint_as_float(cv[c].z), __fdividef(1.f, 1.f + __expf(-__uint_as_float(cv[c].x))), 0.f);
                }
            }
            if (lane == 0) TS(8);
        }
        bar_sync(2, 256);
        const int idx0 = ms.idx[0], idx1 = ms.idx[1];
        if (t == 0 && idx0 >= 0) TS(61);
        float* sX = reinterpret_cast<float*>(smem + SM_A3);
        float* sH = sX + 1024;
        float* sPart = sX + 2048;
        float* sAct = sPart + 512;
        if (cta < NFFN) {
            {
                const int tk = t >> 7, P = t & 127;
                uint4 hv[1];
                wait_pkts<1, 0xffffffffu>(&gCandRow[ms.cslot[tk] * 128 + P], 0, tag, hv);
                if (t == 0) TS(57);
                const float mu = ms.sel[tk * 4], rs = ms.sel[tk * 4 + 1];
                const int col = (P >> 4) * 64 + ((P >> 2) & 3) * 16 + (P & 3) * 2;
                const uint32_t l0 = pack_bf16((bf_lo(hv[0].x) - mu) * rs, (bf_hi(hv[0].x) - mu) * rs);
                const uint32_t l1 = pack_bf16((bf_lo(hv[0].y) - mu) * rs, (bf_hi(hv[0].y) - mu) * rs);
                *reinterpret_cast<float2*>(&sX[tk * 512 + col]) = make_float2(bf_lo(l0), bf_hi(l0));
                *reinterpret_cast<float2*>(&sX[tk * 512 + col + 8]) = make_float2(bf_lo(l1), bf_hi(l1));
                *reinterpret_cast<float2*>(&sH[tk * 512 + col]) = make_float2(bf_lo(hv[0].x), bf_hi(hv[0].x));
                *reinterpret_cast<float2*>(&sH[tk * 512 + col + 8]) = make_float2(bf_lo(hv[0].y), bf_hi(hv[0].y));
            }
            mbar_wait(smem_u32(&ms.moe), 0);
            bar_sync(1 + 8, 256);
            if (t == 0) { asm volatile("" ::: "memory"); sAct[40] = sX[0]; TS(58); }
            {
                const int wv = warp - 8, kk = lane >> 3, cp = lane & 7;
                float a[2][2][2] = {};
#pragma unroll
                for (int i = 0; i < 16; i++) {
                    const int k = wv * 64 + i * 4 + kk;
                    const float x0 = sX[k], x1 = sX[512 + k];
#pragma unroll
                    for (int mat = 0; mat < 2; mat++) {
                        const uint32_t w = *reinterpret_cast<const uint32_t*>(smem + (mat * 8 + wv) * KV_CHUNK + 8192 + (i * 4 + kk) * 32 + cp * 4);
                        a[mat][0][0] = fmaf(x0, bf_lo(w), a[mat][0][0]); a[mat][0][1] = fmaf(x0, bf_hi(w), a[mat][0][1]);
                        a[mat][1][0] = fmaf(x1, bf_lo(w), a[mat][1][0]); a[mat][1][1] = fmaf(x1, bf_hi(w), a[mat][1][1]);
                    }
                }
#pragma unroll
                for (int mat = 0; mat < 2; mat++)
#pragma unroll
                    for (int tk = 0; tk < 2; tk++)
#pragma unroll
                        for (int e = 0; e < 2; e++) {
                            float v = a[mat][tk][e];
                            v += __shfl_xor_sync(0xffffffffu, v, 8);
                            v += __shfl_xor_sync(0xffffffffu, v, 16);
                            if (kk == 0) sPart[(wv * 2 + tk) * 32 + mat * 16 + 2 * cp + e] = v;
                        }
            }
            bar_sync(1 + 8, 256);
            if (t == 0) { sAct[41] = sPart[0]; TS(59); }
            if (t < 32) {
                const int tk = t >> 4, c = t & 15;
                float gs = 0.f, us = 0.f;
#pragma unroll
                for (int w = 0; w < 8; w++) { gs += sPart[(w * 2 + tk) * 32 + c]; us += sPart[(w * 2 + tk) * 32 + 16 + c]; }
                const float gb = bf_round(gs), ub = bf_round(us);
                const float sl = bf_round(__fdividef(gb, 1.f + __expf(-gb)));
                sAct[tk * 16 + c] = bf_round(sl * ub);
            }
            bar_sync(1 + 8, 256);
            {
                float y00 = 0.f, y01 = 0.f, y10 = 0.f, y11 = 0.f;
#pragma unroll
                for (int k = 0; k < 16; k++) {
                    const float a0 = sAct[k], a1 = sAct[16 + k];
                    y00 = fmaf(a0, bf_lo(wd[k]), y00); y01 = fmaf(a0, bf_hi(wd[k]), y01);
                    y10 = fmaf(a1, bf_lo(wd[k]), y10); y11 = fmaf(a1, bf_hi(wd[k]), y11);
                }
                st_pkt(&gYPart[((t >> 2) * NFFN + cta) * 4 + (t & 3)], embed_tag(y00, y01, y10, y11, tag));
            }
            if (t == 0) TS(9);
        }
        if (cta < 64) {
            const int pc = t & 3, part = t >> 2;
            const int opc = (t >> 2) & 3, oe = t & 3, otk = oe >> 1, ocol = (cta * 4 + opc) * 2 + (oe & 1);
            float y[4] = {0.f, 0.f, 0.f, 0.f};
            if (part < 56) {
                uint4 yv[2];
                wait_pkts4<2>(&gYPart[(cta * NFFN + part) * 4 + pc], 56 * 4, tag, yv);
                if (t == 0) TS(60);
                y[0] = __uint_as_float(yv[0].x) + __uint_as_float(yv[1].x); y[1] = __uint_as_float(yv[0].y) + __uint_as_float(yv[1].y);
                y[2] = __uint_as_float(yv[0].z) + __uint_as_float(yv[1].z); y[3] = __uint_as_float(yv[0].w) + __uint_as_float(yv[1].w);
            }
            if (t >= 224 && t < 226) {
                const int orow = (t & 1) ? idx1 : idx0, oc = cta * 8;
                wait_flag(&gFlagOut[((orow >> 6) * 4 + (oc >> 7)) * 8 + ((oc >> 6) & 1)], tag);
            }
            __syncwarp();
#pragma unroll
            for (int e = 0; e < 4; e++) {
                y[e] += __shfl_xor_sync(0xffffffffu, y[e], 4); y[e] += __shfl_xor_sync(0xffffffffu, y[e], 8); y[e] += __shfl_xor_sync(0xffffffffu, y[e], 16);
            }
            float* sR = sAct + 32;
            if (lane < 4) *reinterpret_cast<float4*>(&sR[(warp - 8) * 16 + lane * 4]) = make_float4(y[0], y[1], y[2], y[3]);
            bar_sync(1 + 8, 256);
            if (t < 16) {
                float s = 0.f;
#pragma unroll
                for (int w = 0; w < 8; w++) s += sR[w * 16 + t];
                const float yb = bf_round(bf_round(s) * ms.sel[otk * 4 + 2]);
                out[(size_t)(otk ? idx1 : idx0) * DM + ocol] = __float2bfloat16(sH[otk * 512 + ocol] + bf_round(sX[otk * 512 + ocol] + yb));
            }
            if (cta == 0 && t == 0) {
                *reinterpret_cast<volatile unsigned int*>(&gEpoch) = tag;
            }
            if (t == 0) TS(10);
        }
    }
}

typedef CUresult (*EncodeFn)(CUtensorMap*, CUtensorMapDataType, cuuint32_t, void*, const cuuint64_t*, const cuuint64_t*,
                             const cuuint32_t*, const cuuint32_t*, CUtensorMapInterleave, CUtensorMapSwizzle,
                             CUtensorMapL2promotion, CUtensorMapFloatOOBfill);

void make_map(EncodeFn enc, CUtensorMap* tm, const void* base, uint64_t cols, uint64_t rows, uint32_t box_c, uint32_t box_r, bool swz) {
    cuuint64_t dims[2] = {cols, rows};
    cuuint64_t strides[1] = {cols * 2};
    cuuint32_t box[2] = {box_c, box_r};
    cuuint32_t es[2] = {1, 1};
    enc(tm, CU_TENSOR_MAP_DATA_TYPE_BFLOAT16, 2, const_cast<void*>(base), dims, strides, box, es, CU_TENSOR_MAP_INTERLEAVE_NONE,
        swz ? CU_TENSOR_MAP_SWIZZLE_128B : CU_TENSOR_MAP_SWIZZLE_NONE, CU_TENSOR_MAP_L2_PROMOTION_L2_256B,
        CU_TENSOR_MAP_FLOAT_OOB_FILL_NONE);
}

}

extern "C" void kernel_launch(void* const* d_in, const int* in_sizes, int n_in, void* d_out, int out_size) {
    const __nv_bfloat16* x = (const __nv_bfloat16*)d_in[0];
    const __nv_bfloat16* wqkv = (const __nv_bfloat16*)d_in[1];
    const __nv_bfloat16* wo = (const __nv_bfloat16*)d_in[2];
    const __nv_bfloat16* w_r = (const __nv_bfloat16*)d_in[4];
    const __nv_bfloat16* w_gate = (const __nv_bfloat16*)d_in[5];
    const __nv_bfloat16* w_up = (const __nv_bfloat16*)d_in[6];
    const __nv_bfloat16* w_down = (const __nv_bfloat16*)d_in[7];
    __nv_bfloat16* out = (__nv_bfloat16*)d_out;

    static EncodeFn enc = nullptr;
    static void* pO = nullptr;
    if (!enc) {
        void* fn = nullptr;
        cudaDriverEntryPointQueryResult qr;
        cudaGetDriverEntryPoint("cuTensorMapEncodeTiled", &fn, cudaEnableDefault, &qr);
        enc = (EncodeFn)fn;
        cudaGetSymbolAddress(&pO, gO);
        cudaFuncSetAttribute(mega_kernel, cudaFuncAttributeMaxDynamicSharedMemorySize, SMEM_TOTAL);
    }
    CUtensorMap tmX, tmW, tmO, tmWo, tmG, tmU, tmOut;
    make_map(enc, &tmX, x, DM, S_LEN, 64, 128, true);
    make_map(enc, &tmW, wqkv, 3 * DM, DM, 64, 64, true);
    make_map(enc, &tmO, pO, DM, S_LEN, 64, 64, true);
    make_map(enc, &tmWo, wo, DM, DM, 64, 64, true);
    make_map(enc, &tmG, w_gate, FF, DM, 16, 64, false);
    make_map(enc, &tmU, w_up, FF, DM, 16, 64, false);
    make_map(enc, &tmOut, out, DM, S_LEN, 64, 64, true);

    mega_kernel<<<128, 512, SMEM_TOTAL, cudaStreamPerThread>>>(tmX, tmW, tmO, tmWo, tmG, tmU, tmOut, x, wqkv, wo, w_r, w_gate, w_up, w_down, out);
}
```

```cpp
#include <cuda_runtime.h>
#include <cuda_bf16.h>
#include <cuda.h>
#include <stdint.h>
#include <type_traits>

namespace {

constexpr int S_LEN = 2048, DM = 512, NH = 32, DH = 16, FF = 1792;
constexpr int NFFN = FF / 16;
constexpr float LN_EPS = 1e-5f;
constexpr float QSCALE = 0.25f * 1.4426950408889634f;

__device__ __align__(1024) __nv_bfloat16 gQ[NH * S_LEN * DH];
__device__ __align__(1024) __nv_bfloat16 gKV[NH * S_LEN * DH * 2];
__device__ __align__(1024) __nv_bfloat16 gO[S_LEN * DM];
__device__ unsigned int gEpoch;
__device__ uint4 gFlagQKV[128 * 4];
__device__ __align__(32) unsigned int gFlagO[32 * 32];
__device__ uint4 gStat1[S_LEN];
__device__ uint4 gCsPart[8 * 16 * 48];
__device__ uint4 gPart[32 * 64 * 4];
__device__ uint4 gCand[128 * 64];
__device__ __align__(32) unsigned int gFlagOut[128 * 8];
__device__ uint4 gCandRow[64 * 128];
__device__ uint4 gYPart[NFFN * 256];

#define TS(slot) do {} while (0)

__device__ __forceinline__ uint32_t smem_u32(const void* p) { return (uint32_t)__cvta_generic_to_shared(p); }
__device__ __forceinline__ void mbar_init(uint32_t bar, uint32_t cnt) {
    asm volatile("mbarrier.init.shared::cta.b64 [%0], %1;" ::"r"(bar), "r"(cnt));
}
__device__ __forceinline__ void mbar_expect_tx(uint32_t bar, uint32_t bytes) {
    asm volatile("mbarrier.arrive.expect_tx.shared::cta.b64 _, [%0], %1;" ::"r"(bar), "r"(bytes) : "memory");
}
__device__ __forceinline__ void mbar_arrive(uint32_t bar) {
    asm volatile("mbarrier.arrive.shared::cta.b64 _, [%0];" ::"r"(bar) : "memory");
}
constexpr int SPIN_LIMIT = 1 << 22;
#define ITEMMODE 0
#define PVG 2
#define PVWAIT 2
#define CPI 16
#define NR (16 / CPI)
#define BACKOFF() __nanosleep(32)
__device__ __forceinline__ void mbar_wait(uint32_t bar, uint32_t parity) {
    uint32_t done = 0;
    int it = 0;
    while (true) {
        asm volatile("{.reg .pred p; mbarrier.try_wait.parity.shared::cta.b64 p, [%1], %2; selp.u32 %0, 1, 0, p;}"
                     : "=r"(done) : "r"(bar), "r"(parity) : "memory");
        if (done) break;
        if (++it > SPIN_LIMIT) __trap();
    }
}
__device__ __forceinline__ void bulk_g2s(uint32_t dst, const void* src, uint32_t bytes, uint32_t bar) {
    asm volatile("cp.async.bulk.shared::cluster.global.mbarrier::complete_tx::bytes [%0], [%1], %2, [%3];"
                 ::"r"(dst), "l"(src), "r"(bytes), "r"(bar) : "memory");
}
__device__ __forceinline__ void bulk_prefetch_l2(const void* src, uint32_t bytes) {
    asm volatile("cp.async.bulk.prefetch.L2.global [%0], %1;" ::"l"(src), "r"(bytes) : "memory");
}
__device__ __forceinline__ void tma_2d(uint32_t dst, const CUtensorMap* tm, int c0, int c1, uint32_t bar) {
    asm volatile("cp.async.bulk.tensor.2d.shared::cluster.global.mbarrier::complete_tx::bytes [%0], [%1, {%3, %4}], [%2];"
                 ::"r"(dst), "l"(tm), "r"(bar), "r"(c0), "r"(c1) : "memory");
}
__device__ __forceinline__ void tma_store_2d(const CUtensorMap* tm, uint32_t src, int c0, int c1) {
    asm volatile("cp.async.bulk.tensor.2d.global.shared::cta.bulk_group [%0, {%2, %3}], [%1];" ::"l"(tm), "r"(src), "r"(c0), "r"(c1) : "memory");
    asm volatile("cp.async.bulk.commit_group;" ::: "memory");
}
__device__ __forceinline__ void fence_proxy_async_global() { asm volatile("fence.proxy.async.global;" ::: "memory"); }
__device__ __forceinline__ void fence_gpu() { asm volatile("fence.acq_rel.gpu;" ::: "memory"); }
__device__ __forceinline__ void bar_sync(int id, int n) { asm volatile("bar.sync %0, %1;" ::"r"(id), "r"(n) : "memory"); }
__device__ __forceinline__ void bar_arrive(int id, int n) { asm volatile("bar.arrive %0, %1;" ::"r"(id), "r"(n) : "memory"); }
__device__ __forceinline__ void st_flag(unsigned int* p, unsigned int v) {
    asm volatile("st.release.gpu.global.u32 [%0], %1;" ::"l"(p), "r"(v) : "memory");
}
__device__ __forceinline__ unsigned int ld_flag(const unsigned int* p) {
    unsigned int v;
    asm volatile("ld.relaxed.gpu.global.u32 %0, [%1];" : "=r"(v) : "l"(p) : "memory");
    return v;
}
__device__ __forceinline__ void wait_flag(const unsigned int* p, unsigned int tag) {
    int it = 0;
    while (ld_flag(p) != tag) {
        if (++it > SPIN_LIMIT) __trap();
        BACKOFF();
    }
}
__device__ __forceinline__ void st_pkt(uint4* p, uint4 v) {
    asm volatile("st.relaxed.gpu.global.v4.u32 [%0], {%1,%2,%3,%4};" ::"l"(p), "r"(v.x), "r"(v.y), "r"(v.z), "r"(v.w) : "memory");
}
__device__ __forceinline__ uint4 ld_pkt(const uint4* p) {
    uint4 v;
    asm volatile("ld.relaxed.gpu.global.v4.u32 {%0,%1,%2,%3}, [%4];" : "=r"(v.x), "=r"(v.y), "=r"(v.z), "=r"(v.w) : "l"(p) : "memory");
    return v;
}
template <int N, unsigned int MASK>
__device__ __forceinline__ void wait_pkts(const uint4* p, int stride, unsigned int tag, uint4 (&v)[N]) {
    int it = 0;
    while (true) {
        bool ok = true;
#pragma unroll
        for (int i = 0; i < N; i++) v[i] = ld_pkt(p + (size_t)i * stride);
#pragma unroll
        for (int i = 0; i < N; i++) ok = ok && ((v[i].w & MASK) == tag);
        if (ok) break;
        if (++it > SPIN_LIMIT) __trap();
        BACKOFF();
    }
}
__device__ __forceinline__ uint4 embed_tag(float a, float b, float c, float d, unsigned int tag) {
    return make_uint4((__float_as_uint(a) & ~15u) | (tag & 15u), (__float_as_uint(b) & ~15u) | ((tag >> 4) & 15u),
                      (__float_as_uint(c) & ~15u) | ((tag >> 8) & 15u), (__float_as_uint(d) & ~15u) | ((tag >> 12) & 15u));
}
template <int N>
__device__ __forceinline__ void wait_pkts4(const uint4* p, int stride, unsigned int tag, uint4 (&v)[N]) {
    const unsigned int t16 = tag & 0xffffu;
    int it = 0;
    while (true) {
        bool ok = true;
#pragma unroll
        for (int i = 0; i < N; i++) v[i] = ld_pkt(p + (size_t)i * stride);
#pragma unroll
        for (int i = 0; i < N; i++)
            ok = ok && (((v[i].x & 15u) | ((v[i].y & 15u) << 4) | ((v[i].z & 15u) << 8) | ((v[i].w & 15u) << 12)) == t16);
        if (ok) break;
        if (++it > SPIN_LIMIT) __trap();
        BACKOFF();
    }
}
__device__ __forceinline__ uint64_t make_desc(uint32_t addr, uint32_t lbo, uint32_t sbo, uint32_t mode) {
    return (uint64_t)((addr & 0x3FFFF) >> 4) | ((uint64_t)((lbo & 0x3FFFF) >> 4) << 16) |
           ((uint64_t)((sbo & 0x3FFFF) >> 4) << 32) | ((uint64_t)mode << 62);
}
__device__ __forceinline__ void wg_fence() { asm volatile("wgmma.fence.sync.aligned;" ::: "memory"); }
__device__ __forceinline__ void wg_commit() { asm volatile("wgmma.commit_group.sync.aligned;" ::: "memory"); }
template <int N> __device__ __forceinline__ void wg_wait() { asm volatile("wgmma.wait_group.sync.aligned %0;" ::"n"(N) : "memory"); }
template <int N> __device__ __forceinline__ void pin(uint32_t (&d)[N]) {
#pragma unroll
    for (int i = 0; i < N; i++) asm volatile("" : "+r"(d[i])::"memory");
}
template <int N> __device__ __forceinline__ void pin(float (&d)[N]) {
#pragma unroll
    for (int i = 0; i < N; i++) asm volatile("" : "+f"(d[i])::"memory");
}
__device__ __forceinline__ uint32_t pack_bf16(float lo, float hi) {
    uint32_t r;
    asm("cvt.rn.bf16x2.f32 %0, %1, %2;" : "=r"(r) : "f"(hi), "f"(lo));
    return r;
}
__device__ __forceinline__ float bf_lo(uint32_t v) { return __uint_as_float(v << 16); }
__device__ __forceinline__ float bf_hi(uint32_t v) { return __uint_as_float(v & 0xFFFF0000u); }
__device__ __forceinline__ float bf_round(float v) { return __bfloat162float(__float2bfloat16(v)); }
__device__ __forceinline__ float ex2_mufu(float x) {
    float y;
    asm("ex2.approx.ftz.f32 %0, %1;" : "=f"(y) : "f"(x));
    return y;
}

#define ACC8(d, o) "+f"(d[o + 0]), "+f"(d[o + 1]), "+f"(d[o + 2]), "+f"(d[o + 3]), "+f"(d[o + 4]), "+f"(d[o + 5]), "+f"(d[o + 6]), "+f"(d[o + 7])
#define OUT8(d, o) "=f"(d[o + 0]), "=f"(d[o + 1]), "=f"(d[o + 2]), "=f"(d[o + 3]), "=f"(d[o + 4]), "=f"(d[o + 5]), "=f"(d[o + 6]), "=f"(d[o + 7])

__device__ __forceinline__ void wgmma_n192(float (&d)[96], uint64_t da, uint64_t db) {
    asm volatile(
        "wgmma.mma_async.sync.aligned.m64n192k16.f32.bf16.bf16 "
        "{%0,%1,%2,%3,%4,%5,%6,%7,%8,%9,%10,%11,%12,%13,%14,%15,%16,%17,%18,%19,%20,%21,%22,%23,%24,%25,%26,%27,%28,%29,%30,%31,"
        "%32,%33,%34,%35,%36,%37,%38,%39,%40,%41,%42,%43,%44,%45,%46,%47,%48,%49,%50,%51,%52,%53,%54,%55,%56,%57,%58,%59,%60,%61,%62,%63,"
        "%64,%65,%66,%67,%68,%69,%70,%71,%72,%73,%74,%75,%76,%77,%78,%79,%80,%81,%82,%83,%84,%85,%86,%87,%88,%89,%90,%91,%92,%93,%94,%95},"
        "%96, %97, 1, 1, 1, 0, 1;"
        : ACC8(d, 0), ACC8(d, 8), ACC8(d, 16), ACC8(d, 24), ACC8(d, 32), ACC8(d, 40), ACC8(d, 48), ACC8(d, 56),
          ACC8(d, 64), ACC8(d, 72), ACC8(d, 80), ACC8(d, 88)
        : "l"(da), "l"(db));
}
__device__ __forceinline__ void wgmma_n192_rs(float (&d)[96], const uint32_t* a, uint64_t db) {
    asm volatile(
        "wgmma.mma_async.sync.aligned.m64n192k16.f32.bf16.bf16 "
        "{%0,%1,%2,%3,%4,%5,%6,%7,%8,%9,%10,%11,%12,%13,%14,%15,%16,%17,%18,%19,%20,%21,%22,%23,%24,%25,%26,%27,%28,%29,%30,%31,"
        "%32,%33,%34,%35,%36,%37,%38,%39,%40,%41,%42,%43,%44,%45,%46,%47,%48,%49,%50,%51,%52,%53,%54,%55,%56,%57,%58,%59,%60,%61,%62,%63,"
        "%64,%65,%66,%67,%68,%69,%70,%71,%72,%73,%74,%75,%76,%77,%78,%79,%80,%81,%82,%83,%84,%85,%86,%87,%88,%89,%90,%91,%92,%93,%94,%95},"
        "{%96,%97,%98,%99}, %100, 1, 1, 1, 1;"
        : ACC8(d, 0), ACC8(d, 8), ACC8(d, 16), ACC8(d, 24), ACC8(d, 32), ACC8(d, 40), ACC8(d, 48), ACC8(d, 56),
          ACC8(d, 64), ACC8(d, 72), ACC8(d, 80), ACC8(d, 88)
        : "r"(a[0]), "r"(a[1]), "r"(a[2]), "r"(a[3]), "l"(db));
}
__device__ __forceinline__ void ldsm_x4(uint32_t* r, uint32_t addr) {
    asm volatile("ldmatrix.sync.aligned.m8n8.x4.shared.b16 {%0,%1,%2,%3}, [%4];"
                 : "=r"(r[0]), "=r"(r[1]), "=r"(r[2]), "=r"(r[3]) : "r"(addr) : "memory");
}
__device__ __forceinline__ void wgmma_n64(float (&d)[32], uint64_t da, uint64_t db) {
    asm volatile(
        "wgmma.mma_async.sync.aligned.m64n64k16.f32.bf16.bf16 "
        "{%0,%1,%2,%3,%4,%5,%6,%7,%8,%9,%10,%11,%12,%13,%14,%15,%16,%17,%18,%19,%20,%21,%22,%23,%24,%25,%26,%27,%28,%29,%30,%31},"
        "%32, %33, 1, 1, 1, 0, 1;"
        : ACC8(d, 0), ACC8(d, 8), ACC8(d, 16), ACC8(d, 24)
        : "l"(da), "l"(db));
}
__device__ __forceinline__ void wgmma_qk128(float (&d)[64], const uint32_t (&a)[4], uint64_t db) {
    asm volatile("wgmma.mma_async.sync.aligned.m64n128k16.f32.f16.f16 "
        "{%0,%1,%2,%3,%4,%5,%6,%7,%8,%9,%10,%11,%12,%13,%14,%15,%16,%17,%18,%19,%20,%21,%22,%23,%24,%25,%26,%27,%28,%29,%30,%31,%32,%33,%34,%35,%36,%37,%38,%39,%40,%41,%42,%43,%44,%45,%46,%47,%48,%49,%50,%51,%52,%53,%54,%55,%56,%57,%58,%59,%60,%61,%62,%63}, {%64,%65,%66,%67}, %68, 0, 1, 1, 0;"
        : "=f"(d[0]), "=f"(d[1]), "=f"(d[2]), "=f"(d[3]), "=f"(d[4]), "=f"(d[5]), "=f"(d[6]), "=f"(d[7]), "=f"(d[8]), "=f"(d[9]), "=f"(d[10]), "=f"(d[11]), "=f"(d[12]), "=f"(d[13]), "=f"(d[14]), "=f"(d[15]), "=f"(d[16]), "=f"(d[17]), "=f"(d[18]), "=f"(d[19]), "=f"(d[20]), "=f"(d[21]), "=f"(d[22]), "=f"(d[23]), "=f"(d[24]), "=f"(d[25]), "=f"(d[26]), "=f"(d[27]), "=f"(d[28]), "=f"(d[29]), "=f"(d[30]), "=f"(d[31]), "=f"(d[32]), "=f"(d[33]), "=f"(d[34]), "=f"(d[35]), "=f"(d[36]), "=f"(d[37]), "=f"(d[38]), "=f"(d[39]), "=f"(d[40]), "=f"(d[41]), "=f"(d[42]), "=f"(d[43]), "=f"(d[44]), "=f"(d[45]), "=f"(d[46]), "=f"(d[47]), "=f"(d[48]), "=f"(d[49]), "=f"(d[50]), "=f"(d[51]), "=f"(d[52]), "=f"(d[53]), "=f"(d[54]), "=f"(d[55]), "=f"(d[56]), "=f"(d[57]), "=f"(d[58]), "=f"(d[59]), "=f"(d[60]), "=f"(d[61]), "=f"(d[62]), "=f"(d[63])
        : "r"(a[0]), "r"(a[1]), "r"(a[2]), "r"(a[3]), "l"(db));
}
__device__ __forceinline__ void wgmma_qk64_f32(float (&d)[32], const uint32_t (&a)[4], uint64_t db) {
    asm volatile("wgmma.mma_async.sync.aligned.m64n64k16.f32.f16.f16 "
        "{%0,%1,%2,%3,%4,%5,%6,%7,%8,%9,%10,%11,%12,%13,%14,%15,%16,%17,%18,%19,%20,%21,%22,%23,%24,%25,%26,%27,%28,%29,%30,%31}, {%32,%33,%34,%35}, %36, 0, 1, 1, 0;"
        : "=f"(d[0]), "=f"(d[1]), "=f"(d[2]), "=f"(d[3]), "=f"(d[4]), "=f"(d[5]), "=f"(d[6]), "=f"(d[7]), "=f"(d[8]), "=f"(d[9]), "=f"(d[10]), "=f"(d[11]), "=f"(d[12]), "=f"(d[13]), "=f"(d[14]), "=f"(d[15]), "=f"(d[16]), "=f"(d[17]), "=f"(d[18]), "=f"(d[19]), "=f"(d[20]), "=f"(d[21]), "=f"(d[22]), "=f"(d[23]), "=f"(d[24]), "=f"(d[25]), "=f"(d[26]), "=f"(d[27]), "=f"(d[28]), "=f"(d[29]), "=f"(d[30]), "=f"(d[31])
        : "r"(a[0]), "r"(a[1]), "r"(a[2]), "r"(a[3]), "l"(db));
}
__device__ __forceinline__ void wgmma_qk64_f16(uint32_t (&d)[16], const uint32_t (&a)[4], uint64_t db) {
    asm volatile("wgmma.mma_async.sync.aligned.m64n64k16.f16.f16.f16 "
        "{%0,%1,%2,%3,%4,%5,%6,%7,%8,%9,%10,%11,%12,%13,%14,%15}, {%16,%17,%18,%19}, %20, 0, 1, 1, 0;"
        : "=r"(d[0]), "=r"(d[1]), "=r"(d[2]), "=r"(d[3]), "=r"(d[4]), "=r"(d[5]), "=r"(d[6]), "=r"(d[7]), "=r"(d[8]), "=r"(d[9]), "=r"(d[10]), "=r"(d[11]), "=r"(d[12]), "=r"(d[13]), "=r"(d[14]), "=r"(d[15])
        : "r"(a[0]), "r"(a[1]), "r"(a[2]), "r"(a[3]), "l"(db));
}
__device__ __forceinline__ void wgmma_pv24(float (&o)[12], uint32_t a0, uint32_t a1, uint32_t a2, uint32_t a3, uint64_t desc) {
    asm volatile(
        "wgmma.mma_async.sync.aligned.m64n24k16.f32.bf16.bf16 "
        "{%0,%1,%2,%3,%4,%5,%6,%7,%8,%9,%10,%11}, {%12,%13,%14,%15}, %16, 1, 1, 1, 1;"
        : ACC8(o, 0), "+f"(o[8]), "+f"(o[9]), "+f"(o[10]), "+f"(o[11])
        : "r"(a0), "r"(a1), "r"(a2), "r"(a3), "l"(desc));
}

__device__ __forceinline__ uint32_t ex2_pair_h16(uint32_t x2) {
    uint32_t t, r, f, q;
    asm("add.rn.f16x2 %0, %1, %2;" : "=r"(t) : "r"(x2), "r"(0x661E661Fu));
    asm("sub.rn.f16x2 %0, %1, %2;" : "=r"(r) : "r"(t), "r"(0x661E661Fu));
    asm("sub.rn.f16x2 %0, %1, %2;" : "=r"(f) : "r"(x2), "r"(r));
    asm("fma.rn.f16x2 %0, %1, %2, %3;" : "=r"(q) : "r"(0x15101510u), "r"(f), "r"(0x1d7e1d7eu));
    asm("fma.rn.f16x2 %0, %1, %2, %3;" : "=r"(q) : "r"(q), "r"(f), "r"(0x23d823d8u));
    asm("fma.rn.f16x2 %0, %1, %2, %3;" : "=r"(q) : "r"(q), "r"(f), "r"(0x30823035u));
    return t * 128u + q;
}
constexpr float VSCALE_ODD = 0.70703125f;
constexpr float LOG2C_ODD = 0.50015402f;
__device__ __forceinline__ uint32_t pack_f16_sat(float lo, float hi) {
    uint32_t r;
    asm("cvt.rn.satfinite.f16x2.f32 %0, %1, %2;" : "=r"(r) : "f"(hi), "f"(lo));
    return r;
}
__device__ __forceinline__ unsigned int f2ord(float v) {
    const unsigned int u = __float_as_uint(v);
    const unsigned int o = u ^ ((unsigned int)((int)u >> 31) | 0x80000000u);
    return (v == v) ? o : 0u;
}
__device__ __forceinline__ void warp_top2(unsigned int ka, unsigned int ia, unsigned int kb, unsigned int ib, unsigned int& i1, unsigned int& i2) {
    const unsigned int m1 = __reduce_max_sync(0xffffffffu, max(ka, kb));
    i1 = __reduce_min_sync(0xffffffffu, min(ka == m1 ? ia : 0xffffffffu, kb == m1 ? ib : 0xffffffffu));
    const bool ra = (ia == i1), rb = (ib == i1);
    const unsigned int ka2 = ra ? 0u : ka, kb2 = rb ? 0u : kb, ia2 = ra ? 0xffffffffu : ia, ib2 = rb ? 0xffffffffu : ib;
    const unsigned int m2 = __reduce_max_sync(0xffffffffu, max(ka2, kb2));
    i2 = __reduce_min_sync(0xffffffffu, min(ka2 == m2 ? ia2 : 0xffffffffu, kb2 == m2 ? ib2 : 0xffffffffu));
}

constexpr int P1_STAGES = 5;
constexpr int P1_STAGE_BYTES = 16384 + 24576;
constexpr int KV_CHUNK = 10240;
constexpr int SM_Q = 163840 + 49152;
constexpr int SM_A3 = 163840;
constexpr int SM_MISC = 229376;
constexpr int SMEM_TOTAL = 232448;
struct Misc {
    uint64_t p1_full[P1_STAGES], p1_empty[P1_STAGES];
    uint64_t kv[16];
    uint64_t wo[8], a3[8], moe;
    unsigned int tag;
    int fast;
    int idx[2], cslot[2];
    alignas(16) float sel[8];
    unsigned int norm[12];
    uint64_t qbar;
    int item, nxt[4];
    unsigned int seq[8];
    unsigned int freed[16];
    union alignas(16) {
        struct { float mu[128], rs[128], cs[192]; } p1;
        struct { float part[2][64][3]; float mu[64], rs[64], r[64]; } p3;
    };
};
static_assert(sizeof(Misc) <= SMEM_TOTAL - SM_MISC, "misc smem");

__device__ __forceinline__ void release_kv_chunk(Misc& ms, int j, int lane) {
    asm volatile("{.reg .pred p; setp.eq.s32 p, %1, 0; @p red.relaxed.cta.shared.add.u32 [%0], 1;}" ::"r"(smem_u32(&ms.freed[j])), "r"(lane) : "memory");
}
__device__ __forceinline__ bool refill_kv_chunk(char* smem, Misc& ms, int j, int cta, int lane, const CUtensorMap* tmWo,
                                                const CUtensorMap* tmG, const CUtensorMap* tmU) {
    unsigned int cnt;
    asm volatile("ld.relaxed.cta.shared.u32 %0, [%1];" : "=r"(cnt) : "r"(smem_u32(&ms.freed[j])) : "memory");
    if (cnt < 32u) return false;
    if (lane == 0) {
        const uint32_t dst = smem_u32(smem + j * KV_CHUNK);
        const uint32_t wb = smem_u32(&ms.wo[j >> 1]);
        mbar_expect_tx(wb, 8192);
        tma_2d(dst, tmWo, (cta & 3) * 128 + (j & 1) * 64, (j >> 1) * 64, wb);
        const uint32_t mb = smem_u32(&ms.moe);
        if (cta < NFFN) {
            mbar_expect_tx(mb, 2048);
            tma_2d(dst + 8192, (j & 8) ? tmU : tmG, cta * 16, (j & 7) * 64, mb);
        }
    }
    __syncwarp();
    return true;
}

template <typename LoadFn>
__device__ __forceinline__ void guarded_item(char* smem, Misc& ms, int r, int t, int warp, LoadFn load_chunk) {
    const int tid = threadIdx.x, lane = tid & 31, w4 = (tid >> 5) & 3;
    const uint64_t descK0 = make_desc(smem_u32(smem), 128, 256, 0);
    const uint64_t descV0 = make_desc(smem_u32(smem + 4096), 128, 2048, 0);
    uint32_t q[4];
    {
        const uint32_t* Qs = reinterpret_cast<const uint32_t*>(smem + SM_Q + t * 2048 + w4 * 512);
        q[0] = Qs[lane]; q[2] = Qs[32 + lane]; q[1] = Qs[64 + lane]; q[3] = Qs[96 + lane];
    }
    float* st = reinterpret_cast<float*>(smem + SM_A3) + t * (12 * 128) + (tid & 127);
    float o[12];
#pragma unroll
    for (int i = 0; i < 8; i++) o[i] = r > 0 ? st[i * 128] : 0.f;
    o[8] = r > 0 ? st[8 * 128] : 0.f; o[10] = r > 0 ? st[9 * 128] : 0.f; o[9] = 0.f; o[11] = 0.f;
    float m0 = r > 0 ? st[10 * 128] : -INFINITY, m1 = r > 0 ? st[11 * 128] : -INFINITY;
#pragma unroll 1
    for (int jh = 2 * CPI * r; jh < 2 * CPI * (r + 1); jh++) {
        const int j = jh >> 1;
        if (t < 4 && (jh & 1) == 0 && warp == j + 5 && lane == 0) load_chunk(warp);
        __syncwarp();
        mbar_wait(smem_u32(&ms.kv[j]), 0);
        float s[32];
        const uint32_t off = j * (KV_CHUNK >> 4);
        wg_fence();
        wgmma_qk64_f32(s, q, descK0 + (uint64_t)(off + (jh & 1) * 128));
        wg_commit();
        wg_wait<0>();
        pin(s);
        pin(o);
        if ((jh & 1) == 0 && j > CPI * r) release_kv_chunk(ms, j - 1, lane);
        float n0 = m0, n1 = m1;
#pragma unroll
        for (int i = 0; i < 8; i++) {
            n0 = fmaxf(n0, fmaxf(s[4 * i], s[4 * i + 1]));
            n1 = fmaxf(n1, fmaxf(s[4 * i + 2], s[4 * i + 3]));
        }
        n0 = fmaxf(n0, __shfl_xor_sync(0xffffffffu, n0, 1)); n0 = fmaxf(n0, __shfl_xor_sync(0xffffffffu, n0, 2));
        n1 = fmaxf(n1, __shfl_xor_sync(0xffffffffu, n1, 1)); n1 = fmaxf(n1, __shfl_xor_sync(0xffffffffu, n1, 2));
        const float a0 = ex2_mufu(m0 - n0), a1 = ex2_mufu(m1 - n1);
        m0 = n0; m1 = n1;
#pragma unroll
        for (int i = 0; i < 3; i++) { o[4 * i] *= a0; o[4 * i + 1] *= a0; o[4 * i + 2] *= a1; o[4 * i + 3] *= a1; }
        const float e0 = n0 - LOG2C_ODD, e1 = n1 - LOG2C_ODD;
#pragma unroll
        for (int k = 0; k < 4; k++) {
            const uint32_t p0 = pack_bf16(ex2_mufu(s[8 * k] - n0), ex2_mufu(s[8 * k + 1] - n0));
            const uint32_t p1 = pack_bf16(ex2_mufu(s[8 * k + 2] - n1), ex2_mufu(s[8 * k + 3] - n1));
            const uint32_t p2 = pack_bf16(ex2_mufu(s[8 * k + 4] - e0), ex2_mufu(s[8 * k + 5] - e0));
            const uint32_t p3 = pack_bf16(ex2_mufu(s[8 * k + 6] - e1), ex2_mufu(s[8 * k + 7] - e1));
            wg_fence();
            wgmma_pv24(o, p0, p1, p2, p3, descV0 + (uint64_t)(off + ((jh & 1) * 4 + k) * 16));
            wg_commit();
            wg_wait<0>();
            pin(o);
        }
    }
#pragma unroll
    for (int i = 0; i < 8; i++) st[i * 128] = o[i];
    st[8 * 128] = o[8]; st[9 * 128] = o[10]; st[10 * 128] = m0; st[11 * 128] = m1;
}

__global__ void __launch_bounds__(512, 1)
mega_kernel(const __grid_constant__ CUtensorMap tmX, const __grid_constant__ CUtensorMap tmW,
            const __grid_constant__ CUtensorMap tmO, const __grid_constant__ CUtensorMap tmWo,
            const __grid_constant__ CUtensorMap tmG, const __grid_constant__ CUtensorMap tmU, const __grid_constant__ CUtensorMap tmOut,
            const __nv_bfloat16* __restrict__ x, const __nv_bfloat16* __restrict__ wqkv, const __nv_bfloat16* __restrict__ wo,
            const __nv_bfloat16* __restrict__ w_r, const __nv_bfloat16* __restrict__ w_gate,
            const __nv_bfloat16* __restrict__ w_up, const __nv_bfloat16* __restrict__ w_down,
            __nv_bfloat16* __restrict__ out) {
    extern __shared__ __align__(1024) char smem[];
    Misc& ms = *reinterpret_cast<Misc*>(smem + SM_MISC);
    const int tid = threadIdx.x, lane = tid & 31;
    const int warp = __shfl_sync(0xffffffffu, tid >> 5, 0);
    const int wg = warp >> 2, w4 = warp & 3, g = lane >> 2, t4 = lane & 3;
    const int cta = blockIdx.x;
    const int rb = cta >> 3, hg = cta & 7;

    if (warp == 12) {
        if (lane == 0) {
            TS(0);
            if (smem_u32(smem) & 1023) __trap();
            for (int i = 0; i < P1_STAGES; i++) { mbar_init(smem_u32(&ms.p1_full[i]), 1); mbar_init(smem_u32(&ms.p1_empty[i]), 8); }
            asm volatile("fence.mbarrier_init.release.cluster;" ::: "memory");
        }
        __syncwarp();
        bar_arrive(13, 288);
        bar_arrive(14, 256);
    } else {
        if (tid == 32) {
            for (int i = 0; i < 16; i++) mbar_init(smem_u32(&ms.kv[i]), 1);
            for (int i = 0; i < 8; i++) { mbar_init(smem_u32(&ms.wo[i]), 2); mbar_init(smem_u32(&ms.a3[i]), 1); }
            mbar_init(smem_u32(&ms.moe), 16);
            for (int i = 0; i < 16; i++) ms.freed[i] = 0;
            for (int i = 0; i < 8; i++) ms.seq[i] = 0;
            ms.item = 4;
            mbar_init(smem_u32(&ms.qbar), 1);
            asm volatile("fence.mbarrier_init.release.cluster;" ::: "memory");
        }
        if (tid >= 64 && tid < 76) ms.norm[tid - 64] = 0;
        if (tid >= 96 && tid < 101) {
            const CUtensorMap* tm = tid == 96 ? &tmO : tid == 97 ? &tmWo : tid == 98 ? &tmG : tid == 99 ? &tmU : &tmOut;
            asm volatile("prefetch.tensormap [%0];" ::"l"(tm) : "memory");
        }
        if (tid == 416) ms.tag = __ldcg(&gEpoch) + 1u;
    }

    if (wg < 2) {
        asm volatile("setmaxnreg.inc.sync.aligned.u32 160;");
        float acc[96];
#pragma unroll
        for (int i = 0; i < 96; i++) acc[i] = 0.f;
        bar_sync(13, 288);
#pragma unroll 1
        for (int kc = 0; kc < 8; kc++) {
            const int s = kc % P1_STAGES;
            mbar_wait(smem_u32(&ms.p1_full[s]), (kc / P1_STAGES) & 1);
            if (tid == 0) TS(24 + kc);
            const uint32_t sa = smem_u32(smem + s * P1_STAGE_BYTES), sb = sa + 16384;
            const uint64_t da = make_desc(sa + wg * 8192, 16, 1024, 1);
            const uint64_t db = make_desc(sb, 8192, 1024, 1);
            wg_fence();
#pragma unroll
            for (int ks = 0; ks < 4; ks++) wgmma_n192(acc, da + ks * 2, db + ks * 128);
            wg_commit();
            wg_wait<0>();
            if (lane == 0) mbar_arrive(smem_u32(&ms.p1_empty[s]));
        }
        pin(acc);
        if (tid == 0) TS(1);
        bar_sync(1, 480);
        const unsigned int tag = ms.tag;
        if (tid == 0) TS(16);
        const int lr0 = wg * 64 + w4 * 16 + g, lr1 = lr0 + 8;
        const float mu0 = ms.p1.mu[lr0], mu1 = ms.p1.mu[lr1], rs0 = ms.p1.rs[lr0], rs1 = ms.p1.rs[lr1];
        const int lg0 = wg * 8 + w4 * 2;
        const int rg0 = rb * 16 + lg0;
#pragma unroll
        for (int hh = 0; hh < 4; hh++) {
            const int head = hg * 4 + hh;
            float nrm[3];
#pragma unroll
            for (int sec = 0; sec < 3; sec++) {
                float sq0 = 0.f, sq1 = 0.f, vm = 0.f;
#pragma unroll
                for (int db = 0; db < 2; db++) {
                    const int j = sec * 8 + hh * 2 + db;
                    const float2 c = *reinterpret_cast<const float2*>(&ms.p1.cs[j * 8 + 2 * t4]);
                    const float f0 = sec == 0 ? rs0 * QSCALE : rs0, f1 = sec == 0 ? rs1 * QSCALE : rs1;
                    const float a0 = (acc[4 * j + 0] - mu0 * c.x) * f0, a1 = (acc[4 * j + 1] - mu0 * c.y) * f0;
                    const float b0 = (acc[4 * j + 2] - mu1 * c.x) * f1, b1 = (acc[4 * j + 3] - mu1 * c.y) * f1;
                    const uint32_t pa = sec < 2 ? pack_f16_sat(a0, a1) : pack_bf16(a0, a1);
                    const uint32_t pb = sec < 2 ? pack_f16_sat(b0, b1) : pack_bf16(b0 * VSCALE_ODD, b1 * VSCALE_ODD);
                    if (sec < 2) {
                        uint32_t* dst = sec == 0 ? reinterpret_cast<uint32_t*>(gQ) + ((size_t)head * S_LEN * DH + rg0 * 128) / 2
                                                 : reinterpret_cast<uint32_t*>(gKV) + (size_t)(head * 16 + rb) * 2048 + lg0 * 64;
                        dst[db * 32 + lane] = pa;
                        dst[64 + db * 32 + lane] = pb;
                        sq0 = fmaf(a0, a0, fmaf(a1, a1, sq0));
                        sq1 = fmaf(b0, b0, fmaf(b1, b1, sq1));
                    } else {
                        uint32_t* dst = reinterpret_cast<uint32_t*>(gKV) + (size_t)(head * 16 + rb) * 2048 + 1024 + db * 512 + lg0 * 32;
                        dst[lane] = pa;
                        dst[32 + lane] = pb;
                        vm = fmaxf(vm, fmaxf(fmaxf(fabsf(a0), fabsf(a1)), fmaxf(fabsf(b0), fabsf(b1))));
                        if (!(a0 + a1 + b0 + b1 == a0 + a1 + b0 + b1)) vm = __int_as_float(0x7f800000);
                    }
                }
                if (sec < 2) {
                    sq0 += __shfl_xor_sync(0xffffffffu, sq0, 1); sq0 += __shfl_xor_sync(0xffffffffu, sq0, 2);
                    sq1 += __shfl_xor_sync(0xffffffffu, sq1, 1); sq1 += __shfl_xor_sync(0xffffffffu, sq1, 2);
                    vm = fmaxf(sq0, sq1);
                    if (!(sq0 + sq1 < 3.0e38f)) vm = __int_as_float(0x7f800000);
                }
                nrm[sec] = vm;
            }
            const unsigned int a = __reduce_max_sync(0xffffffffu, __float_as_uint(nrm[0]));
            const unsigned int b = __reduce_max_sync(0xffffffffu, __float_as_uint(nrm[1]));
            const unsigned int c = __reduce_max_sync(0xffffffffu, __float_as_uint(nrm[2]));
            if (lane == 0) { atomicMax(&ms.norm[hh * 3 + 0], a); atomicMax(&ms.norm[hh * 3 + 1], b); atomicMax(&ms.norm[hh * 3 + 2], c); }
        }
        if (tid == 0) TS(17);
        bar_sync(2, 256);
        if (tid == 0) TS(18);
        if (tid < 4) {
            fence_gpu();
            st_pkt(&gFlagQKV[(hg * 16 + rb) * 4 + tid], make_uint4(ms.norm[tid * 3], ms.norm[tid * 3 + 1], ms.norm[tid * 3 + 2], tag));
            if (tid == 0) TS(2);
        }
        asm volatile("setmaxnreg.dec.sync.aligned.u32 128;");
        bar_sync(15, 512);
    } else {
      asm volatile("setmaxnreg.dec.sync.aligned.u32 96;");
      if (wg == 2) {
        const int t = tid - 256;
        if (t < 4) gFlagQKV[(hg * 16 + rb) * 4 + t] = make_uint4(0u, 0u, 0u, 0u);
        bar_sync(14, 256);
        mbar_wait(smem_u32(&ms.p1_full[0]), 0);
        {
            const int row = rb * 128 + hg * 16 + (t >> 3), j = t & 7;
            const uint4* xp = reinterpret_cast<const uint4*>(x + (size_t)row * DM);
            uint4 v[8];
#pragma unroll
            for (int i = 0; i < 8; i++) v[i] = __ldg(xp + i * 8 + j);
            float s1 = 0.f;
#pragma unroll
            for (int i = 0; i < 8; i++) {
                const uint32_t w[4] = {v[i].x, v[i].y, v[i].z, v[i].w};
#pragma unroll
                for (int e = 0; e < 4; e++) s1 += bf_lo(w[e]) + bf_hi(w[e]);
            }
            s1 += __shfl_xor_sync(0xffffffffu, s1, 1); s1 += __shfl_xor_sync(0xffffffffu, s1, 2); s1 += __shfl_xor_sync(0xffffffffu, s1, 4);
            const float mu = s1 * (1.f / DM);
            float s2 = 0.f;
#pragma unroll
            for (int i = 0; i < 8; i++) {
                const uint32_t w[4] = {v[i].x, v[i].y, v[i].z, v[i].w};
#pragma unroll
                for (int e = 0; e < 4; e++) {
                    const float a = bf_lo(w[e]) - mu, b = bf_hi(w[e]) - mu;
                    s2 = fmaf(a, a, fmaf(b, b, s2));
                }
            }
            s2 += __shfl_xor_sync(0xffffffffu, s2, 1); s2 += __shfl_xor_sync(0xffffffffu, s2, 2); s2 += __shfl_xor_sync(0xffffffffu, s2, 4);
            bar_sync(11, 224);
            if (j == 0) st_pkt(&gStat1[row], make_uint4(__float_as_uint(mu), __float_as_uint(rsqrtf(s2 * (1.f / DM) + LN_EPS)), 0u, ms.tag));
        }
        const unsigned int tag = ms.tag;
        if (t == 0) TS(32);
        uint4 st[1];
        if (t < 8) wait_pkts<1, 0xffffffffu>(&gStat1[rb * 128 + t * 16 + 15], 0, tag, st);
        bar_sync(12, 128);
        wait_pkts<1, 0xffffffffu>(&gStat1[rb * 128 + t], 0, tag, st);
        if (t == 0) TS(34);
        ms.p1.mu[t] = __uint_as_float(st[0].x);
        ms.p1.rs[t] = __uint_as_float(st[0].y);
        bar_arrive(1, 480);
        {
            const uint4 z = make_uint4(0u, 0u, 0u, 0u);
            if (t < 64) { gCand[cta * 64 + t] = z; gPart[cta * 64 + t] = z; gCandRow[cta * 64 + t] = z; }
            gYPart[cta * 224 + t] = z;
            if (t < 96) gYPart[cta * 224 + 128 + t] = z;
            if (t < 2) {
                reinterpret_cast<uint4*>(gFlagO)[cta * 2 + t] = z;
                reinterpret_cast<uint4*>(gFlagOut)[cta * 2 + t] = z;
            }
        }
      } else if (warp == 12) {
        if (lane == 0) {
#pragma unroll 1
            for (int kc = 0; kc < 8; kc++) {
                const int s = kc % P1_STAGES;
                if (kc >= P1_STAGES) mbar_wait(smem_u32(&ms.p1_empty[s]), 0);
                const uint32_t bar = smem_u32(&ms.p1_full[s]);
                const uint32_t sa = smem_u32(smem + s * P1_STAGE_BYTES), sb = sa + 16384;
                mbar_expect_tx(bar, P1_STAGE_BYTES);
                tma_2d(sa, &tmX, kc * 64, rb * 128, bar);
#pragma unroll
                for (int p = 0; p < 3; p++) tma_2d(sb + p * 8192, &tmW, p * 512 + hg * 64, kc * 64, bar);
            }
        }
      } else {
        const int t = tid - 416;
        bar_sync(14, 256);
        mbar_wait(smem_u32(&ms.p1_full[0]), 0);
        const int c16 = t >> 2, rs = t & 3;
        const __nv_bfloat16* wp = wqkv + (size_t)(rb * 32 + rs) * (3 * DM) + (c16 >> 3) * 512 + hg * 64 + (c16 & 7) * 8;
        uint4 v[8];
#pragma unroll
        for (int i = 0; i < 8; i++) v[i] = __ldg(reinterpret_cast<const uint4*>(wp + (size_t)i * 4 * (3 * DM)));
        float a[8] = {};
#pragma unroll
        for (int i = 0; i < 8; i++) {
            a[0] += bf_lo(v[i].x); a[1] += bf_hi(v[i].x); a[2] += bf_lo(v[i].y); a[3] += bf_hi(v[i].y);
            a[4] += bf_lo(v[i].z); a[5] += bf_hi(v[i].z); a[6] += bf_lo(v[i].w); a[7] += bf_hi(v[i].w);
        }
#pragma unroll
        for (int e = 0; e < 8; e++) { a[e] += __shfl_xor_sync(0xffffffffu, a[e], 1); a[e] += __shfl_xor_sync(0xffffffffu, a[e], 2); }
        bar_sync(11, 224);
        const unsigned int tag = ms.tag;
        const int pk = c16 * 2 + rs;
        if (rs < 2) st_pkt(&gCsPart[(hg * 16 + rb) * 48 + pk], embed_tag(rs ? a[4] : a[0], rs ? a[5] : a[1], rs ? a[6] : a[2], rs ? a[7] : a[3], tag));
        if (t == 0) TS(35);
        if (t < 16) { uint4 gate[1]; wait_pkts4<1>(&gCsPart[(hg * 16 + t) * 48 + 47], 0, tag, gate); }
        bar_sync(8, 96);
        if (t == 0) TS(36);
        if (rs < 2) {
            uint4 p[16];
            wait_pkts4<16>(&gCsPart[hg * 16 * 48 + pk], 48, tag, p);
            float s0 = 0.f, s1 = 0.f, s2 = 0.f, s3 = 0.f;
#pragma unroll
            for (int i = 0; i < 16; i++) {
                s0 += __uint_as_float(p[i].x); s1 += __uint_as_float(p[i].y); s2 += __uint_as_float(p[i].z); s3 += __uint_as_float(p[i].w);
            }
            *reinterpret_cast<float4*>(&ms.p1.cs[pk * 4]) = make_float4(s0, s1, s2, s3);
            if (t == 0) TS(37);
        }
        __syncwarp();
        bar_arrive(1, 480);
      }
      __syncwarp();
      bar_sync(15, 512);
      asm volatile("setmaxnreg.inc.sync.aligned.u32 128;");
    }
    if (tid == 0) TS(20);
    const unsigned int tag = ms.tag;

    const int head = hg * 4 + (rb >> 2), quarter = rb & 3;
    {
#pragma unroll
        for (int i = 0; i < 4; i++) {
            const int e = tid + i * 512;
            *reinterpret_cast<uint4*>(smem + (e >> 7) * KV_CHUNK + 8192 + (e & 127) * 16) = make_uint4((e & 8) ? 0x00003F35u : 0x00003F80u, 0, 0, 0);
        }
        asm volatile("fence.proxy.async.shared::cta;" ::: "memory");
    }
    if (warp == 0) {
        uint4 n[1];
        wait_pkts<1, 0xffffffffu>(&gFlagQKV[(hg * 16 + (lane & 15)) * 4 + (rb >> 2)], 0, tag, n);
        __syncwarp();
        if (lane == 0) TS(21);
        const float q2 = __uint_as_float(__reduce_max_sync(0xffffffffu, n[0].x));
        const float k2 = __uint_as_float(__reduce_max_sync(0xffffffffu, n[0].y));
        const float vm = __uint_as_float(__reduce_max_sync(0xffffffffu, n[0].z));
        if (lane == 0) ms.fast = (q2 * k2 * 1.02f <= 812.f) && (q2 <= 1.0e6f) && (k2 <= 1.0e6f) && (vm <= 1.0e18f) && (vm >= 1.0e-18f || vm == 0.f);
    }
    __syncthreads();
    auto load_kv_chunk = [&](int j) {
        fence_proxy_async_global();
        const uint32_t bar = smem_u32(&ms.kv[j]);
        mbar_expect_tx(bar, 8192);
        bulk_g2s(smem_u32(smem + j * KV_CHUNK), reinterpret_cast<const char*>(gKV) + (size_t)(head * 16 + j) * 8192, 8192, bar);
    };
    if (lane == 0) {
        if (warp == 5) {
            fence_proxy_async_global();
            mbar_expect_tx(smem_u32(&ms.qbar), 16384);
            bulk_g2s(smem_u32(smem + SM_Q), reinterpret_cast<const char*>(gQ) + (size_t)head * 65536 + quarter * 16384, 16384, smem_u32(&ms.qbar));
        }
        if (warp < 5) load_kv_chunk(warp);
    }
    __syncwarp();
    if (tid == 0) TS(3);
    bool refilled = false;
    {
        const bool fast = ms.fast != 0;
        const uint64_t descKe = make_desc(smem_u32(smem), 128, 512, 0);
        const uint64_t descKo = make_desc(smem_u32(smem) + 256, 128, 512, 0);
        const uint64_t descV0 = make_desc(smem_u32(smem + 4096), 128, 2048, 0);
        auto release_chunk = [&](int j) { release_kv_chunk(ms, j, lane); };
        float* sAcc = reinterpret_cast<float*>(smem + SM_A3);
        const int t128 = tid & 127;
        mbar_wait(smem_u32(&ms.qbar), 0);
        auto run_items = [&](auto FAST) {
        int item = wg * NR;
#pragma unroll 1
        while (item < 8 * NR) {
            const int r = item % NR, t = item / NR;
            if (t128 == 0) ms.nxt[wg] = ((item % NR) == NR - 1) ? item + 3 * NR + 1 : item + 1;
            if (r > 0) {
                int it = 0;
                unsigned int sq;
                while (true) {
                    asm volatile("ld.acquire.cta.shared.u32 %0, [%1];" : "=r"(sq) : "r"(smem_u32(&ms.seq[t])) : "memory");
                    if (sq >= (unsigned int)r) break;
                    if (++it > SPIN_LIMIT) __trap();
                }
            }
            uint32_t q[4];
            {
                const uint32_t* Qs = reinterpret_cast<const uint32_t*>(smem + SM_Q + t * 2048 + w4 * 512);
                q[0] = Qs[lane]; q[2] = Qs[32 + lane]; q[1] = Qs[64 + lane]; q[3] = Qs[96 + lane];
            }
            float* st = sAcc + t * (12 * 128) + t128;
            float o[12];
#pragma unroll
            for (int i = 0; i < 8; i++) o[i] = r > 0 ? st[i * 128] : 0.f;
            o[8] = r > 0 ? st[8 * 128] : 0.f; o[10] = r > 0 ? st[9 * 128] : 0.f; o[9] = 0.f; o[11] = 0.f;
            if constexpr (decltype(FAST)::value) {
#pragma unroll 1
                for (int j = CPI * r; j < CPI * (r + 1); j++) {
                    if (t < 4 && warp == j + 5 && lane == 0) load_kv_chunk(warp);
                    __syncwarp();
                    mbar_wait(smem_u32(&ms.kv[j]), 0);
                    float s[32];
                    uint32_t h[16];
                    wg_fence();
                    wgmma_qk64_f32(s, q, descKe + (uint64_t)(j * (KV_CHUNK >> 4)));
                    wgmma_qk64_f16(h, q, descKo + (uint64_t)(j * (KV_CHUNK >> 4)));
                    wg_commit();
                    wg_wait<0>();
                    pin(s);
                    pin(h);
                    if (j > CPI * r) release_chunk(j - 1);
                    if (!refilled && j > warp) refilled = refill_kv_chunk(smem, ms, warp, cta, lane, &tmWo, &tmG, &tmU);
#pragma unroll
                    for (int kg = 0; kg < 8 / PVG; kg++) {
                        uint32_t p[4 * PVG];
#pragma unroll
                        for (int u = 0; u < PVG; u++) {
                            const int k = kg * PVG + u;
                            p[4 * u + 0] = pack_bf16(ex2_mufu(s[4 * k]), ex2_mufu(s[4 * k + 1]));
                            p[4 * u + 1] = pack_bf16(ex2_mufu(s[4 * k + 2]), ex2_mufu(s[4 * k + 3]));
                            p[4 * u + 2] = ex2_pair_h16(h[2 * k]);
                            p[4 * u + 3] = ex2_pair_h16(h[2 * k + 1]);
                        }
                        wg_fence();
#pragma unroll
                        for (int u = 0; u < PVG; u++)
                            wgmma_pv24(o, p[4 * u], p[4 * u + 1], p[4 * u + 2], p[4 * u + 3],
                                       descV0 + (uint64_t)(j * (KV_CHUNK >> 4) + (kg * PVG + u) * 16));
                        wg_commit();
                        wg_wait<PVWAIT>();
                    }
                }
                wg_wait<0>();
                pin(o);
            } else {
                guarded_item(smem, ms, r, t, warp, load_kv_chunk);
#pragma unroll
                for (int i = 0; i < 8; i++) o[i] = st[i * 128];
                o[8] = st[8 * 128]; o[10] = st[9 * 128];
            }
            release_chunk(CPI * r + CPI - 1);
            if (r < NR - 1) {
#pragma unroll
                for (int i = 0; i < 8; i++) st[i * 128] = o[i];
                st[8 * 128] = o[8]; st[9 * 128] = o[10];
            } else {
                const float l0 = __shfl_sync(0xffffffffu, o[8], lane & ~3), l1 = __shfl_sync(0xffffffffu, o[10], lane & ~3);
                const float r0 = __fdividef(1.f, l0), r1 = __fdividef(1.f, l1);
                uint32_t* Op = reinterpret_cast<uint32_t*>(gO + (size_t)(quarter * 512 + t * 64 + w4 * 16) * DM + head * DH);
                Op[g * 256 + t4] = pack_bf16(o[0] * r0, o[1] * r0);
                Op[(g + 8) * 256 + t4] = pack_bf16(o[2] * r1, o[3] * r1);
                Op[g * 256 + 4 + t4] = pack_bf16(o[4] * r0, o[5] * r0);
                Op[(g + 8) * 256 + 4 + t4] = pack_bf16(o[6] * r1, o[7] * r1);
            }
            bar_sync(3 + wg, 128);
            if (t128 == 0) asm volatile("st.release.cta.shared.u32 [%0], %1;" ::"r"(smem_u32(&ms.seq[t])), "r"(r + 1) : "memory");
            if (r == 0 && t == 3 && tid == 511) {
                bulk_prefetch_l2(reinterpret_cast<const char*>(w_down) + cta * 14336, 14336);
            }
            if (!refilled) refilled = refill_kv_chunk(smem, ms, warp, cta, lane, &tmWo, &tmG, &tmU);
            item = ms.nxt[wg];
            bar_sync(3 + wg, 128);
        }
        };
        if (fast) run_items(std::true_type{}); else run_items(std::false_type{});
    }
    __syncthreads();
    if (!refilled) refill_kv_chunk(smem, ms, warp, cta, lane, &tmWo, &tmG, &tmU);
    if (warp == 0 && lane < 8) { fence_gpu(); asm volatile("st.relaxed.gpu.global.u32 [%0], %1;" ::"l"(&gFlagO[(quarter * 8 + lane) * 32 + head]), "r"(tag) : "memory"); }
    if (tid == 0) TS(4);

    const int rb3 = cta >> 2, cb = cta & 3;
    if (wg < 2) {
        const int r0 = rb3 * 64 + w4 * 16 + g, r1 = r0 + 8;
        const int col0 = cb * 128 + wg * 64 + 2 * t4;
        uint32_t xa[8], xb[8], wr[8];
#pragma unroll
        for (int j = 0; j < 8; j++) {
            xa[j] = __ldg(reinterpret_cast<const uint32_t*>(x + (size_t)r0 * DM + col0 + j * 8));
            xb[j] = __ldg(reinterpret_cast<const uint32_t*>(x + (size_t)r1 * DM + col0 + j * 8));
            wr[j] = __ldg(reinterpret_cast<const uint32_t*>(w_r + col0 + j * 8));
        }
        const float p0 = __bfloat162float(x[(size_t)r0 * DM]), p1 = __bfloat162float(x[(size_t)r1 * DM]);
        const float pivot = __bfloat162float(x[(size_t)(rb3 * 64 + (tid >> 2)) * DM]);
        float wsum = 0.f;
        {
            const uint4 a = __ldg(reinterpret_cast<const uint4*>(w_r) + lane), b = __ldg(reinterpret_cast<const uint4*>(w_r) + 32 + lane);
            const uint32_t w[8] = {a.x, a.y, a.z, a.w, b.x, b.y, b.z, b.w};
#pragma unroll
            for (int e = 0; e < 8; e++) wsum += bf_lo(w[e]) + bf_hi(w[e]);
#pragma unroll
            for (int m = 16; m; m >>= 1) wsum += __shfl_xor_sync(0xffffffffu, wsum, m);
        }
        float acc[32];
#pragma unroll
        for (int i = 0; i < 32; i++) acc[i] = 0.f;
#pragma unroll 1
        for (int kc = 0; kc < 8; kc++) {
            mbar_wait(smem_u32(&ms.wo[kc]), 0);
            mbar_wait(smem_u32(&ms.a3[kc]), 0);
            const uint64_t da = make_desc(smem_u32(smem + SM_A3 + kc * 8192), 16, 1024, 1);
            const uint64_t db = make_desc(smem_u32(smem + (kc * 2 + wg) * KV_CHUNK), 8192, 1024, 1);
            wg_fence();
#pragma unroll
            for (int ks = 0; ks < 4; ks++) wgmma_n64(acc, da + ks * 2, db + ks * 128);
            wg_commit();
        }
        wg_wait<0>();
        pin(acc);
        if (tid == 0) TS(6);
        float s1a = 0.f, s2a = 0.f, s3a = 0.f, s1b = 0.f, s2b = 0.f, s3b = 0.f;
#pragma unroll
        for (int j = 0; j < 8; j++) {
            const uint32_t ha = pack_bf16(bf_lo(xa[j]) + acc[4 * j], bf_hi(xa[j]) + acc[4 * j + 1]);
            const uint32_t hb = pack_bf16(bf_lo(xb[j]) + acc[4 * j + 2], bf_hi(xb[j]) + acc[4 * j + 3]);
            xa[j] = ha; xb[j] = hb;
            const float w0 = bf_lo(wr[j]), w1 = bf_hi(wr[j]);
            const float da0 = bf_lo(ha) - p0, da1 = bf_hi(ha) - p0, db0 = bf_lo(hb) - p1, db1 = bf_hi(hb) - p1;
            s1a += da0 + da1; s2a = fmaf(da0, da0, fmaf(da1, da1, s2a)); s3a = fmaf(da0, w0, fmaf(da1, w1, s3a));
            s1b += db0 + db1; s2b = fmaf(db0, db0, fmaf(db1, db1, s2b)); s3b = fmaf(db0, w0, fmaf(db1, w1, s3b));
        }
#pragma unroll
        for (int m = 1; m <= 2; m <<= 1) {
            s1a += __shfl_xor_sync(0xffffffffu, s1a, m); s2a += __shfl_xor_sync(0xffffffffu, s2a, m); s3a += __shfl_xor_sync(0xffffffffu, s3a, m);
            s1b += __shfl_xor_sync(0xffffffffu, s1b, m); s2b += __shfl_xor_sync(0xffffffffu, s2b, m); s3b += __shfl_xor_sync(0xffffffffu, s3b, m);
        }
        if (t4 == 0) {
            const int lr = w4 * 16 + g;
            ms.p3.part[wg][lr][0] = s1a; ms.p3.part[wg][lr][1] = s2a; ms.p3.part[wg][lr][2] = s3a;
            ms.p3.part[wg][lr + 8][0] = s1b; ms.p3.part[wg][lr + 8][1] = s2b; ms.p3.part[wg][lr + 8][2] = s3b;
        }
        if (tid == 0) TS(11);
        bar_sync(1, 256);
        if (tid == 0) TS(12);
        if (tid < 64) {
            st_pkt(&gPart[(rb3 * 64 + tid) * 4 + cb],
                   make_uint4(__float_as_uint(ms.p3.part[0][tid][0] + ms.p3.part[1][tid][0]), __float_as_uint(ms.p3.part[0][tid][1] + ms.p3.part[1][tid][1]),
                              __float_as_uint(ms.p3.part[0][tid][2] + ms.p3.part[1][tid][2]), tag));
        }
        {
            const int lr = tid >> 2, sl = tid & 3;
            uint4 pv[1];
            wait_pkts<1, 0xffffffffu>(&gPart[rb3 * 256 + tid], 0, tag, pv);
            float s1 = __uint_as_float(pv[0].x), s2 = __uint_as_float(pv[0].y), s3 = __uint_as_float(pv[0].z);
            if (tid == 0) TS(14);
#pragma unroll
            for (int m = 1; m <= 2; m <<= 1) {
                s1 += __shfl_xor_sync(0xffffffffu, s1, m); s2 += __shfl_xor_sync(0xffffffffu, s2, m); s3 += __shfl_xor_sync(0xffffffffu, s3, m);
            }
            if (sl == 0) {
                const float md = s1 * (1.f / DM);
                const float var = fmaxf(s2 * (1.f / DM) - md * md, 0.f);
                const float rs = rsqrtf(var + LN_EPS);
                ms.p3.mu[lr] = pivot + md;
                ms.p3.rs[lr] = rs;
                ms.p3.r[lr] = (s3 - md * wsum) * rs;
            }
        }
        bar_sync(1, 256);
        if (tid == 0) TS(7);
        {
            unsigned int i1, i2;
            warp_top2(f2ord(ms.p3.r[lane]), lane, f2ord(ms.p3.r[lane + 32]), lane + 32, i1, i2);
            if (cb == 0) {
                const int c = tid & 1, li = c ? i2 : i1;
                st_pkt(&gCand[(tid >> 1) * 64 + rb3 * 2 + c],
                       make_uint4(__float_as_uint(ms.p3.r[li]), __float_as_uint(ms.p3.mu[li]), __float_as_uint(ms.p3.rs[li]),
                                  (tag << 11) | (unsigned int)(rb3 * 64 + li)));
            }
#pragma unroll
            for (int c = 0; c < 2; c++) {
                const unsigned int li = c ? i2 : i1;
                if ((int)(li >> 4) == w4 && (int)(li & 7) == g) {
                    const bool hi = (li & 8) != 0;
                    uint4* dst = &gCandRow[(rb3 * 2 + c) * 128 + (cb * 2 + wg) * 16 + t4];
#pragma unroll
                    for (int q = 0; q < 4; q++)
                        st_pkt(dst + q * 4, make_uint4(hi ? xb[2 * q] : xa[2 * q], hi ? xb[2 * q + 1] : xa[2 * q + 1], 0u, tag));
                }
            }
            if (tid == 0) TS(15);
        }
        {
            const int lr0 = w4 * 16 + g;
            const float mu0 = ms.p3.mu[lr0], rs0 = ms.p3.rs[lr0], mu1 = ms.p3.mu[lr0 + 8], rs1 = ms.p3.rs[lr0 + 8];
            char* so = smem + wg * KV_CHUNK;
#pragma unroll
            for (int j = 0; j < 8; j++) {
                const float a0 = bf_lo(xa[j]), a1 = bf_hi(xa[j]), b0 = bf_lo(xb[j]), b1 = bf_hi(xb[j]);
                const uint32_t la = pack_bf16((a0 - mu0) * rs0, (a1 - mu0) * rs0);
                const uint32_t lb = pack_bf16((b0 - mu1) * rs1, (b1 - mu1) * rs1);
                const int o = ((j ^ g) << 4) + t4 * 4;
                *reinterpret_cast<uint32_t*>(so + lr0 * 128 + o) = pack_bf16(a0 + bf_lo(la), a1 + bf_hi(la));
                *reinterpret_cast<uint32_t*>(so + (lr0 + 8) * 128 + o) = pack_bf16(b0 + bf_lo(lb), b1 + bf_hi(lb));
            }
            asm volatile("fence.proxy.async.shared::cta;" ::: "memory");
            bar_sync(3 + wg, 128);
            if ((tid & 127) == 0) {
                tma_store_2d(&tmOut, smem_u32(so), cb * 128 + wg * 64, rb3 * 64);
                asm volatile("cp.async.bulk.wait_group 0;" ::: "memory");
                st_flag(&gFlagOut[cta * 8 + wg], tag);
            }
        }
    } else {
        const int t = tid - 256;
        {
            const int kc = warp - 8;
            if (lane == 0) {
                int it = 0;
                while (true) {
                    const uint4 f = ld_pkt(reinterpret_cast<const uint4*>(&gFlagO[rb3 * 32 + kc * 4]));
                    if (f.x == tag && f.y == tag && f.z == tag && f.w == tag) break;
                    if (++it > SPIN_LIMIT) __trap();
                    BACKOFF();
                }
                if (kc == 7) TS(5);
                fence_proxy_async_global();
                const uint32_t bar = smem_u32(&ms.a3[kc]);
                mbar_expect_tx(bar, 8192);
                tma_2d(smem_u32(smem + SM_A3 + kc * 8192), &tmO, kc * 64, rb3 * 64, bar);
            }
            __syncwarp();
        }
        uint32_t wd[16];
        if (cta < NFFN) {
#pragma unroll
            for (int k = 0; k < 16; k++) wd[k] = __ldg(reinterpret_cast<const uint32_t*>(w_down + (size_t)(cta * 16 + k) * DM + 2 * t));
        }
        if (warp == 8) {
            if (lane == 0) TS(56);
            uint4 cv[2];
            wait_pkts<2, 0xfffff800u>(&gCand[cta * 64 + lane * 2], 1, tag << 11, cv);
            if (lane == 0) TS(54);
            unsigned int i1, i2;
            warp_top2(f2ord(__uint_as_float(cv[0].x)), cv[0].w & 0x7ffu, f2ord(__uint_as_float(cv[1].x)), cv[1].w & 0x7ffu, i1, i2);
#pragma unroll
            for (int c = 0; c < 2; c++) {
                const unsigned int ci = cv[c].w & 0x7ffu;
                if (ci == i1 || ci == i2) {
                    const int o = ci == i1 ? 0 : 1;
                    ms.idx[o] = (int)ci;
                    ms.cslot[o] = lane * 2 + c;
                    *reinterpret_cast<float4*>(&ms.sel[o * 4]) =
                        make_float4(__uint_as_float(cv[c].y), __uint_as_float(cv[c].z), __fdividef(1.f, 1.f + __expf(-__uint_as_float(cv[c].x))), 0.f);
                }
            }
            if (lane == 0) TS(8);
        }
        bar_sync(2, 256);
        const int idx0 = ms.idx[0], idx1 = ms.idx[1];
        if (t == 0 && idx0 >= 0) TS(61);
        float* sX = reinterpret_cast<float*>(smem + SM_A3);
        float* sH = sX + 1024;
        float* sPart = sX + 2048;
        float* sAct = sPart + 512;
        if (cta < NFFN) {
            {
                const int tk = t >> 7, P = t & 127;
                uint4 hv[1];
                wait_pkts<1, 0xffffffffu>(&gCandRow[ms.cslot[tk] * 128 + P], 0, tag, hv);
                if (t == 0) TS(57);
                const float mu = ms.sel[tk * 4], rs = ms.sel[tk * 4 + 1];
                const int col = (P >> 4) * 64 + ((P >> 2) & 3) * 16 + (P & 3) * 2;
                const uint32_t l0 = pack_bf16((bf_lo(hv[0].x) - mu) * rs, (bf_hi(hv[0].x) - mu) * rs);
                const uint32_t l1 = pack_bf16((bf_lo(hv[0].y) - mu) * rs, (bf_hi(hv[0].y) - mu) * rs);
                *reinterpret_cast<float2*>(&sX[tk * 512 + col]) = make_float2(bf_lo(l0), bf_hi(l0));
                *reinterpret_cast<float2*>(&sX[tk * 512 + col + 8]) = make_float2(bf_lo(l1), bf_hi(l1));
                *reinterpret_cast<float2*>(&sH[tk * 512 + col]) = make_float2(bf_lo(hv[0].x), bf_hi(hv[0].x));
                *reinterpret_cast<float2*>(&sH[tk * 512 + col + 8]) = make_float2(bf_lo(hv[0].y), bf_hi(hv[0].y));
            }
            mbar_wait(smem_u32(&ms.moe), 0);
            bar_sync(1 + 8, 256);
            if (t == 0) { asm volatile("" ::: "memory"); sAct[40] = sX[0]; TS(58); }
            {
                const int wv = warp - 8, kk = lane >> 3, cp = lane & 7;
                float a[2][2][2] = {};
#pragma unroll
                for (int i = 0; i < 16; i++) {
                    const int k = wv * 64 + i * 4 + kk;
                    const float x0 = sX[k], x1 = sX[512 + k];
#pragma unroll
                    for (int mat = 0; mat < 2; mat++) {
                        const uint32_t w = *reinterpret_cast<const uint32_t*>(smem + (mat * 8 + wv) * KV_CHUNK + 8192 + (i * 4 + kk) * 32 + cp * 4);
                        a[mat][0][0] = fmaf(x0, bf_lo(w), a[mat][0][0]); a[mat][0][1] = fmaf(x0, bf_hi(w), a[mat][0][1]);
                        a[mat][1][0] = fmaf(x1, bf_lo(w), a[mat][1][0]); a[mat][1][1] = fmaf(x1, bf_hi(w), a[mat][1][1]);
                    }
                }
#pragma unroll
                for (int mat = 0; mat < 2; mat++)
#pragma unroll
                    for (int tk = 0; tk < 2; tk++)
#pragma unroll
                        for (int e = 0; e < 2; e++) {
                            float v = a[mat][tk][e];
                            v += __shfl_xor_sync(0xffffffffu, v, 8);
                            v += __shfl_xor_sync(0xffffffffu, v, 16);
                            if (kk == 0) sPart[(wv * 2 + tk) * 32 + mat * 16 + 2 * cp + e] = v;
                        }
            }
            bar_sync(1 + 8, 256);
            if (t == 0) { sAct[41] = sPart[0]; TS(59); }
            if (t < 32) {
                const int tk = t >> 4, c = t & 15;
                float gs = 0.f, us = 0.f;
#pragma unroll
                for (int w = 0; w < 8; w++) { gs += sPart[(w * 2 + tk) * 32 + c]; us += sPart[(w * 2 + tk) * 32 + 16 + c]; }
                const float gb = bf_round(gs), ub = bf_round(us);
                const float sl = bf_round(__fdividef(gb, 1.f + __expf(-gb)));
                sAct[tk * 16 + c] = bf_round(sl * ub);
            }
            bar_sync(1 + 8, 256);
            {
                float y00 = 0.f, y01 = 0.f, y10 = 0.f, y11 = 0.f;
#pragma unroll
                for (int k = 0; k < 16; k++) {
                    const float a0 = sAct[k], a1 = sAct[16 + k];
                    y00 = fmaf(a0, bf_lo(wd[k]), y00); y01 = fmaf(a0, bf_hi(wd[k]), y01);
                    y10 = fmaf(a1, bf_lo(wd[k]), y10); y11 = fmaf(a1, bf_hi(wd[k]), y11);
                }
                st_pkt(&gYPart[((t >> 2) * NFFN + cta) * 4 + (t & 3)], embed_tag(y00, y01, y10, y11, tag));
            }
            if (t == 0) TS(9);
        }
        if (cta < 64) {
            const int pc = t & 3, part = t >> 2;
            const int opc = (t >> 2) & 3, oe = t & 3, otk = oe >> 1, ocol = (cta * 4 + opc) * 2 + (oe & 1);
            float y[4] = {0.f, 0.f, 0.f, 0.f};
            if (part < 56) {
                uint4 yv[2];
                wait_pkts4<2>(&gYPart[(cta * NFFN + part) * 4 + pc], 56 * 4, tag, yv);
                if (t == 0) TS(60);
                y[0] = __uint_as_float(yv[0].x) + __uint_as_float(yv[1].x); y[1] = __uint_as_float(yv[0].y) + __uint_as_float(yv[1].y);
                y[2] = __uint_as_float(yv[0].z) + __uint_as_float(yv[1].z); y[3] = __uint_as_float(yv[0].w) + __uint_as_float(yv[1].w);
            }
            if (t >= 224 && t < 226) {
                const int orow = (t & 1) ? idx1 : idx0, oc = cta * 8;
                wait_flag(&gFlagOut[((orow >> 6) * 4 + (oc >> 7)) * 8 + ((oc >> 6) & 1)], tag);
            }
            __syncwarp();
#pragma unroll
            for (int e = 0; e < 4; e++) {
                y[e] += __shfl_xor_sync(0xffffffffu, y[e], 4); y[e] += __shfl_xor_sync(0xffffffffu, y[e], 8); y[e] += __shfl_xor_sync(0xffffffffu, y[e], 16);
            }
            float* sR = sAct + 32;
            if (lane < 4) *reinterpret_cast<float4*>(&sR[(warp - 8) * 16 + lane * 4]) = make_float4(y[0], y[1], y[2], y[3]);
            bar_sync(1 + 8, 256);
            if (t < 16) {
                float s = 0.f;
#pragma unroll
                for (int w = 0; w < 8; w++) s += sR[w * 16 + t];
                const float yb = bf_round(bf_round(s) * ms.sel[otk * 4 + 2]);
                out[(size_t)(otk ? idx1 : idx0) * DM + ocol] = __float2bfloat16(sH[otk * 512 + ocol] + bf_round(sX[otk * 512 + ocol] + yb));
            }
            if (cta == 0 && t == 0) {
                *reinterpret_cast<volatile unsigned int*>(&gEpoch) = tag;
            }
            if (t == 0) TS(10);
        }
    }
}

typedef CUresult (*EncodeFn)(CUtensorMap*, CUtensorMapDataType, cuuint32_t, void*, const cuuint64_t*, const cuuint64_t*,
                             const cuuint32_t*, const cuuint32_t*, CUtensorMapInterleave, CUtensorMapSwizzle,
                             CUtensorMapL2promotion, CUtensorMapFloatOOBfill);

void make_map(EncodeFn enc, CUtensorMap* tm, const void* base, uint64_t cols, uint64_t rows, uint32_t box_c, uint32_t box_r, bool swz) {
    cuuint64_t dims[2] = {cols, rows};
    cuuint64_t strides[1] = {cols * 2};
    cuuint32_t box[2] = {box_c, box_r};
    cuuint32_t es[2] = {1, 1};
    enc(tm, CU_TENSOR_MAP_DATA_TYPE_BFLOAT16, 2, const_cast<void*>(base), dims, strides, box, es, CU_TENSOR_MAP_INTERLEAVE_NONE,
        swz ? CU_TENSOR_MAP_SWIZZLE_128B : CU_TENSOR_MAP_SWIZZLE_NONE, CU_TENSOR_MAP_L2_PROMOTION_L2_256B,
        CU_TENSOR_MAP_FLOAT_OOB_FILL_NONE);
}

}

extern "C" void kernel_launch(void* const* d_in, const int* in_sizes, int n_in, void* d_out, int out_size) {
    const __nv_bfloat16* x = (const __nv_bfloat16*)d_in[0];
    const __nv_bfloat16* wqkv = (const __nv_bfloat16*)d_in[1];
    const __nv_bfloat16* wo = (const __nv_bfloat16*)d_in[2];
    const __nv_bfloat16* w_r = (const __nv_bfloat16*)d_in[4];
    const __nv_bfloat16* w_gate = (const __nv_bfloat16*)d_in[5];
    const __nv_bfloat16* w_up = (const __nv_bfloat16*)d_in[6];
    const __nv_bfloat16* w_down = (const __nv_bfloat16*)d_in[7];
    __nv_bfloat16* out = (__nv_bfloat16*)d_out;

    static EncodeFn enc = nullptr;
    static void* pO = nullptr;
    if (!enc) {
        void* fn = nullptr;
        cudaDriverEntryPointQueryResult qr;
        cudaGetDriverEntryPoint("cuTensorMapEncodeTiled", &fn, cudaEnableDefault, &qr);
        enc = (EncodeFn)fn;
        cudaGetSymbolAddress(&pO, gO);
        cudaFuncSetAttribute(mega_kernel, cudaFuncAttributeMaxDynamicSharedMemorySize, SMEM_TOTAL);
    }
    CUtensorMap tmX, tmW, tmO, tmWo, tmG, tmU, tmOut;
    make_map(enc, &tmX, x, DM, S_LEN, 64, 128, true);
    make_map(enc, &tmW, wqkv, 3 * DM, DM, 64, 64, true);
    make_map(enc, &tmO, pO, DM, S_LEN, 64, 64, true);
    make_map(enc, &tmWo, wo, DM, DM, 64, 64, true);
    make_map(enc, &tmG, w_gate, FF, DM, 16, 64, false);
    make_map(enc, &tmU, w_up, FF, DM, 16, 64, false);
    make_map(enc, &tmOut, out, DM, S_LEN, 64, 64, true);

    mega_kernel<<<128, 512, SMEM_TOTAL, cudaStreamPerThread>>>(tmX, tmW, tmO, tmWo, tmG, tmU, tmOut, x, wqkv, wo, w_r, w_gate, w_up, w_down, out);
}
```

```cpp
#include <cuda_runtime.h>
#include <cuda_bf16.h>
#include <cuda.h>
#include <stdint.h>
#include <type_traits>

namespace {

constexpr int S_LEN = 2048, DM = 512, NH = 32, DH = 16, FF = 1792;
constexpr int NFFN = FF / 16;
constexpr float LN_EPS = 1e-5f;
constexpr float QSCALE = 0.25f * 1.4426950408889634f;

__device__ __align__(1024) __nv_bfloat16 gQ[NH * S_LEN * DH];
__device__ __align__(1024) __nv_bfloat16 gKV[NH * S_LEN * DH * 2];
__device__ __align__(1024) __nv_bfloat16 gO[S_LEN * DM];
__device__ unsigned int gEpoch;
__device__ uint4 gFlagQKV[128 * 4];
__device__ __align__(32) unsigned int gFlagO[32 * 32];
__device__ uint4 gStat1[S_LEN];
__device__ uint4 gCsPart[8 * 16 * 48];
__device__ uint4 gPart[32 * 64 * 8];
__device__ uint4 gCand[128 * 64];
__device__ __align__(32) unsigned int gFlagOut[128 * 8];
__device__ uint4 gCandRow[64 * 128];
__device__ uint4 gYPart[NFFN * 256];

#define TS(slot) do {} while (0)

__device__ __forceinline__ uint32_t smem_u32(const void* p) { return (uint32_t)__cvta_generic_to_shared(p); }
__device__ __forceinline__ void mbar_init(uint32_t bar, uint32_t cnt) {
    asm volatile("mbarrier.init.shared::cta.b64 [%0], %1;" ::"r"(bar), "r"(cnt));
}
__device__ __forceinline__ void mbar_expect_tx(uint32_t bar, uint32_t bytes) {
    asm volatile("mbarrier.arrive.expect_tx.shared::cta.b64 _, [%0], %1;" ::"r"(bar), "r"(bytes) : "memory");
}
__device__ __forceinline__ void mbar_arrive(uint32_t bar) {
    asm volatile("mbarrier.arrive.shared::cta.b64 _, [%0];" ::"r"(bar) : "memory");
}
constexpr int SPIN_LIMIT = 1 << 22;
#define ITEMMODE 0
#define PVG 2
#define PVWAIT 2
#define CPI 16
#define NR (16 / CPI)
#define BACKOFF() __nanosleep(32)
__device__ __forceinline__ void mbar_wait(uint32_t bar, uint32_t parity) {
    uint32_t done = 0;
    int it = 0;
    while (true) {
        asm volatile("{.reg .pred p; mbarrier.try_wait.parity.shared::cta.b64 p, [%1], %2; selp.u32 %0, 1, 0, p;}"
                     : "=r"(done) : "r"(bar), "r"(parity) : "memory");
        if (done) break;
        if (++it > SPIN_LIMIT) __trap();
    }
}
__device__ __forceinline__ void bulk_g2s(uint32_t dst, const void* src, uint32_t bytes, uint32_t bar) {
    asm volatile("cp.async.bulk.shared::cluster.global.mbarrier::complete_tx::bytes [%0], [%1], %2, [%3];"
                 ::"r"(dst), "l"(src), "r"(bytes), "r"(bar) : "memory");
}
__device__ __forceinline__ void bulk_prefetch_l2(const void* src, uint32_t bytes) {
    asm volatile("cp.async.bulk.prefetch.L2.global [%0], %1;" ::"l"(src), "r"(bytes) : "memory");
}
__device__ __forceinline__ void tma_2d(uint32_t dst, const CUtensorMap* tm, int c0, int c1, uint32_t bar) {
    asm volatile("cp.async.bulk.tensor.2d.shared::cluster.global.mbarrier::complete_tx::bytes [%0], [%1, {%3, %4}], [%2];"
                 ::"r"(dst), "l"(tm), "r"(bar), "r"(c0), "r"(c1) : "memory");
}
__device__ __forceinline__ void tma_store_2d(const CUtensorMap* tm, uint32_t src, int c0, int c1) {
    asm volatile("cp.async.bulk.tensor.2d.global.shared::cta.bulk_group [%0, {%2, %3}], [%1];" ::"l"(tm), "r"(src), "r"(c0), "r"(c1) : "memory");
    asm volatile("cp.async.bulk.commit_group;" ::: "memory");
}
__device__ __forceinline__ void fence_proxy_async_global() { asm volatile("fence.proxy.async.global;" ::: "memory"); }
__device__ __forceinline__ void fence_gpu() { asm volatile("fence.acq_rel.gpu;" ::: "memory"); }
__device__ __forceinline__ void bar_sync(int id, int n) { asm volatile("bar.sync %0, %1;" ::"r"(id), "r"(n) : "memory"); }
__device__ __forceinline__ void bar_arrive(int id, int n) { asm volatile("bar.arrive %0, %1;" ::"r"(id), "r"(n) : "memory"); }
__device__ __forceinline__ void st_flag(unsigned int* p, unsigned int v) {
    asm volatile("st.release.gpu.global.u32 [%0], %1;" ::"l"(p), "r"(v) : "memory");
}
__device__ __forceinline__ unsigned int ld_flag(const unsigned int* p) {
    unsigned int v;
    asm volatile("ld.relaxed.gpu.global.u32 %0, [%1];" : "=r"(v) : "l"(p) : "memory");
    return v;
}
__device__ __forceinline__ void wait_flag(const unsigned int* p, unsigned int tag) {
    int it = 0;
    while (ld_flag(p) != tag) {
        if (++it > SPIN_LIMIT) __trap();
        BACKOFF();
    }
}
__device__ __forceinline__ void st_pkt(uint4* p, uint4 v) {
    asm volatile("st.relaxed.gpu.global.v4.u32 [%0], {%1,%2,%3,%4};" ::"l"(p), "r"(v.x), "r"(v.y), "r"(v.z), "r"(v.w) : "memory");
}
__device__ __forceinline__ uint4 ld_pkt(const uint4* p) {
    uint4 v;
    asm volatile("ld.relaxed.gpu.global.v4.u32 {%0,%1,%2,%3}, [%4];" : "=r"(v.x), "=r"(v.y), "=r"(v.z), "=r"(v.w) : "l"(p) : "memory");
    return v;
}
template <int N, unsigned int MASK>
__device__ __forceinline__ void wait_pkts(const uint4* p, int stride, unsigned int tag, uint4 (&v)[N]) {
    int it = 0;
    while (true) {
        bool ok = true;
#pragma unroll
        for (int i = 0; i < N; i++) v[i] = ld_pkt(p + (size_t)i * stride);
#pragma unroll
        for (int i = 0; i < N; i++) ok = ok && ((v[i].w & MASK) == tag);
        if (ok) break;
        if (++it > SPIN_LIMIT) __trap();
        BACKOFF();
    }
}
__device__ __forceinline__ uint4 embed_tag(float a, float b, float c, float d, unsigned int tag) {
    return make_uint4((__float_as_uint(a) & ~15u) | (tag & 15u), (__float_as_uint(b) & ~15u) | ((tag >> 4) & 15u),
                      (__float_as_uint(c) & ~15u) | ((tag >> 8) & 15u), (__float_as_uint(d) & ~15u) | ((tag >> 12) & 15u));
}
template <int N>
__device__ __forceinline__ void wait_pkts4(const uint4* p, int stride, unsigned int tag, uint4 (&v)[N]) {
    const unsigned int t16 = tag & 0xffffu;
    int it = 0;
    while (true) {
        bool ok = true;
#pragma unroll
        for (int i = 0; i < N; i++) v[i] = ld_pkt(p + (size_t)i * stride);
#pragma unroll
        for (int i = 0; i < N; i++)
            ok = ok && (((v[i].x & 15u) | ((v[i].y & 15u) << 4) | ((v[i].z & 15u) << 8) | ((v[i].w & 15u) << 12)) == t16);
        if (ok) break;
        if (++it > SPIN_LIMIT) __trap();
        BACKOFF();
    }
}
__device__ __forceinline__ uint64_t make_desc(uint32_t addr, uint32_t lbo, uint32_t sbo, uint32_t mode) {
    return (uint64_t)((addr & 0x3FFFF) >> 4) | ((uint64_t)((lbo & 0x3FFFF) >> 4) << 16) |
           ((uint64_t)((sbo & 0x3FFFF) >> 4) << 32) | ((uint64_t)mode << 62);
}
__device__ __forceinline__ void wg_fence() { asm volatile("wgmma.fence.sync.aligned;" ::: "memory"); }
__device__ __forceinline__ void wg_commit() { asm volatile("wgmma.commit_group.sync.aligned;" ::: "memory"); }
template <int N> __device__ __forceinline__ void wg_wait() { asm volatile("wgmma.wait_group.sync.aligned %0;" ::"n"(N) : "memory"); }
template <int N> __device__ __forceinline__ void pin(uint32_t (&d)[N]) {
#pragma unroll
    for (int i = 0; i < N; i++) asm volatile("" : "+r"(d[i])::"memory");
}
template <int N> __device__ __forceinline__ void pin(float (&d)[N]) {
#pragma unroll
    for (int i = 0; i < N; i++) asm volatile("" : "+f"(d[i])::"memory");
}
__device__ __forceinline__ uint32_t pack_bf16(float lo, float hi) {
    uint32_t r;
    asm("cvt.rn.bf16x2.f32 %0, %1, %2;" : "=r"(r) : "f"(hi), "f"(lo));
    return r;
}
__device__ __forceinline__ float bf_lo(uint32_t v) { return __uint_as_float(v << 16); }
__device__ __forceinline__ float bf_hi(uint32_t v) { return __uint_as_float(v & 0xFFFF0000u); }
__device__ __forceinline__ float bf_round(float v) { return __bfloat162float(__float2bfloat16(v)); }
__device__ __forceinline__ float ex2_mufu(float x) {
    float y;
    asm("ex2.approx.ftz.f32 %0, %1;" : "=f"(y) : "f"(x));
    return y;
}

#define ACC8(d, o) "+f"(d[o + 0]), "+f"(d[o + 1]), "+f"(d[o + 2]), "+f"(d[o + 3]), "+f"(d[o + 4]), "+f"(d[o + 5]), "+f"(d[o + 6]), "+f"(d[o + 7])
#define OUT8(d, o) "=f"(d[o + 0]), "=f"(d[o + 1]), "=f"(d[o + 2]), "=f"(d[o + 3]), "=f"(d[o + 4]), "=f"(d[o + 5]), "=f"(d[o + 6]), "=f"(d[o + 7])

__device__ __forceinline__ void wgmma_n192(float (&d)[96], uint64_t da, uint64_t db) {
    asm volatile(
        "wgmma.mma_async.sync.aligned.m64n192k16.f32.bf16.bf16 "
        "{%0,%1,%2,%3,%4,%5,%6,%7,%8,%9,%10,%11,%12,%13,%14,%15,%16,%17,%18,%19,%20,%21,%22,%23,%24,%25,%26,%27,%28,%29,%30,%31,"
        "%32,%33,%34,%35,%36,%37,%38,%39,%40,%41,%42,%43,%44,%45,%46,%47,%48,%49,%50,%51,%52,%53,%54,%55,%56,%57,%58,%59,%60,%61,%62,%63,"
        "%64,%65,%66,%67,%68,%69,%70,%71,%72,%73,%74,%75,%76,%77,%78,%79,%80,%81,%82,%83,%84,%85,%86,%87,%88,%89,%90,%91,%92,%93,%94,%95},"
        "%96, %97, 1, 1, 1, 0, 1;"
        : ACC8(d, 0), ACC8(d, 8), ACC8(d, 16), ACC8(d, 24), ACC8(d, 32), ACC8(d, 40), ACC8(d, 48), ACC8(d, 56),
          ACC8(d, 64), ACC8(d, 72), ACC8(d, 80), ACC8(d, 88)
        : "l"(da), "l"(db));
}
__device__ __forceinline__ void wgmma_n192_rs(float (&d)[96], const uint32_t* a, uint64_t db) {
    asm volatile(
        "wgmma.mma_async.sync.aligned.m64n192k16.f32.bf16.bf16 "
        "{%0,%1,%2,%3,%4,%5,%6,%7,%8,%9,%10,%11,%12,%13,%14,%15,%16,%17,%18,%19,%20,%21,%22,%23,%24,%25,%26,%27,%28,%29,%30,%31,"
        "%32,%33,%34,%35,%36,%37,%38,%39,%40,%41,%42,%43,%44,%45,%46,%47,%48,%49,%50,%51,%52,%53,%54,%55,%56,%57,%58,%59,%60,%61,%62,%63,"
        "%64,%65,%66,%67,%68,%69,%70,%71,%72,%73,%74,%75,%76,%77,%78,%79,%80,%81,%82,%83,%84,%85,%86,%87,%88,%89,%90,%91,%92,%93,%94,%95},"
        "{%96,%97,%98,%99}, %100, 1, 1, 1, 1;"
        : ACC8(d, 0), ACC8(d, 8), ACC8(d, 16), ACC8(d, 24), ACC8(d, 32), ACC8(d, 40), ACC8(d, 48), ACC8(d, 56),
          ACC8(d, 64), ACC8(d, 72), ACC8(d, 80), ACC8(d, 88)
        : "r"(a[0]), "r"(a[1]), "r"(a[2]), "r"(a[3]), "l"(db));
}
__device__ __forceinline__ void ldsm_x4(uint32_t* r, uint32_t addr) {
    asm volatile("ldmatrix.sync.aligned.m8n8.x4.shared.b16 {%0,%1,%2,%3}, [%4];"
                 : "=r"(r[0]), "=r"(r[1]), "=r"(r[2]), "=r"(r[3]) : "r"(addr) : "memory");
}
__device__ __forceinline__ void wgmma_n64(float (&d)[32], uint64_t da, uint64_t db) {
    asm volatile(
        "wgmma.mma_async.sync.aligned.m64n64k16.f32.bf16.bf16 "
        "{%0,%1,%2,%3,%4,%5,%6,%7,%8,%9,%10,%11,%12,%13,%14,%15,%16,%17,%18,%19,%20,%21,%22,%23,%24,%25,%26,%27,%28,%29,%30,%31},"
        "%32, %33, 1, 1, 1, 0, 1;"
        : ACC8(d, 0), ACC8(d, 8), ACC8(d, 16), ACC8(d, 24)
        : "l"(da), "l"(db));
}
__device__ __forceinline__ void wgmma_qk128(float (&d)[64], const uint32_t (&a)[4], uint64_t db) {
    asm volatile("wgmma.mma_async.sync.aligned.m64n128k16.f32.f16.f16 "
        "{%0,%1,%2,%3,%4,%5,%6,%7,%8,%9,%10,%11,%12,%13,%14,%15,%16,%17,%18,%19,%20,%21,%22,%23,%24,%25,%26,%27,%28,%29,%30,%31,%32,%33,%34,%35,%36,%37,%38,%39,%40,%41,%42,%43,%44,%45,%46,%47,%48,%49,%50,%51,%52,%53,%54,%55,%56,%57,%58,%59,%60,%61,%62,%63}, {%64,%65,%66,%67}, %68, 0, 1, 1, 0;"
        : "=f"(d[0]), "=f"(d[1]), "=f"(d[2]), "=f"(d[3]), "=f"(d[4]), "=f"(d[5]), "=f"(d[6]), "=f"(d[7]), "=f"(d[8]), "=f"(d[9]), "=f"(d[10]), "=f"(d[11]), "=f"(d[12]), "=f"(d[13]), "=f"(d[14]), "=f"(d[15]), "=f"(d[16]), "=f"(d[17]), "=f"(d[18]), "=f"(d[19]), "=f"(d[20]), "=f"(d[21]), "=f"(d[22]), "=f"(d[23]), "=f"(d[24]), "=f"(d[25]), "=f"(d[26]), "=f"(d[27]), "=f"(d[28]), "=f"(d[29]), "=f"(d[30]), "=f"(d[31]), "=f"(d[32]), "=f"(d[33]), "=f"(d[34]), "=f"(d[35]), "=f"(d[36]), "=f"(d[37]), "=f"(d[38]), "=f"(d[39]), "=f"(d[40]), "=f"(d[41]), "=f"(d[42]), "=f"(d[43]), "=f"(d[44]), "=f"(d[45]), "=f"(d[46]), "=f"(d[47]), "=f"(d[48]), "=f"(d[49]), "=f"(d[50]), "=f"(d[51]), "=f"(d[52]), "=f"(d[53]), "=f"(d[54]), "=f"(d[55]), "=f"(d[56]), "=f"(d[57]), "=f"(d[58]), "=f"(d[59]), "=f"(d[60]), "=f"(d[61]), "=f"(d[62]), "=f"(d[63])
        : "r"(a[0]), "r"(a[1]), "r"(a[2]), "r"(a[3]), "l"(db));
}
__device__ __forceinline__ void wgmma_qk64_f32(float (&d)[32], const uint32_t (&a)[4], uint64_t db) {
    asm volatile("wgmma.mma_async.sync.aligned.m64n64k16.f32.f16.f16 "
        "{%0,%1,%2,%3,%4,%5,%6,%7,%8,%9,%10,%11,%12,%13,%14,%15,%16,%17,%18,%19,%20,%21,%22,%23,%24,%25,%26,%27,%28,%29,%30,%31}, {%32,%33,%34,%35}, %36, 0, 1, 1, 0;"
        : "=f"(d[0]), "=f"(d[1]), "=f"(d[2]), "=f"(d[3]), "=f"(d[4]), "=f"(d[5]), "=f"(d[6]), "=f"(d[7]), "=f"(d[8]), "=f"(d[9]), "=f"(d[10]), "=f"(d[11]), "=f"(d[12]), "=f"(d[13]), "=f"(d[14]), "=f"(d[15]), "=f"(d[16]), "=f"(d[17]), "=f"(d[18]), "=f"(d[19]), "=f"(d[20]), "=f"(d[21]), "=f"(d[22]), "=f"(d[23]), "=f"(d[24]), "=f"(d[25]), "=f"(d[26]), "=f"(d[27]), "=f"(d[28]), "=f"(d[29]), "=f"(d[30]), "=f"(d[31])
        : "r"(a[0]), "r"(a[1]), "r"(a[2]), "r"(a[3]), "l"(db));
}
__device__ __forceinline__ void wgmma_qk64_f16(uint32_t (&d)[16], const uint32_t (&a)[4], uint64_t db) {
    asm volatile("wgmma.mma_async.sync.aligned.m64n64k16.f16.f16.f16 "
        "{%0,%1,%2,%3,%4,%5,%6,%7,%8,%9,%10,%11,%12,%13,%14,%15}, {%16,%17,%18,%19}, %20, 0, 1, 1, 0;"
        : "=r"(d[0]), "=r"(d[1]), "=r"(d[2]), "=r"(d[3]), "=r"(d[4]), "=r"(d[5]), "=r"(d[6]), "=r"(d[7]), "=r"(d[8]), "=r"(d[9]), "=r"(d[10]), "=r"(d[11]), "=r"(d[12]), "=r"(d[13]), "=r"(d[14]), "=r"(d[15])
        : "r"(a[0]), "r"(a[1]), "r"(a[2]), "r"(a[3]), "l"(db));
}
__device__ __forceinline__ void wgmma_pv24_lh(float (&o)[12], uint32_t a0, uint32_t a1, uint32_t a2, uint32_t a3, uint32_t lo, uint32_t hi) {
    asm volatile(
        "{.reg .b64 d; mov.b64 d, {%16, %17};\n"
        "wgmma.mma_async.sync.aligned.m64n24k16.f32.bf16.bf16 "
        "{%0,%1,%2,%3,%4,%5,%6,%7,%8,%9,%10,%11}, {%12,%13,%14,%15}, d, 1, 1, 1, 1;}"
        : ACC8(o, 0), "+f"(o[8]), "+f"(o[9]), "+f"(o[10]), "+f"(o[11])
        : "r"(a0), "r"(a1), "r"(a2), "r"(a3), "r"(lo), "r"(hi));
}
__device__ __forceinline__ void wgmma_pv24(float (&o)[12], uint32_t a0, uint32_t a1, uint32_t a2, uint32_t a3, uint64_t desc) {
    asm volatile(
        "wgmma.mma_async.sync.aligned.m64n24k16.f32.bf16.bf16 "
        "{%0,%1,%2,%3,%4,%5,%6,%7,%8,%9,%10,%11}, {%12,%13,%14,%15}, %16, 1, 1, 1, 1;"
        : ACC8(o, 0), "+f"(o[8]), "+f"(o[9]), "+f"(o[10]), "+f"(o[11])
        : "r"(a0), "r"(a1), "r"(a2), "r"(a3), "l"(desc));
}

__device__ __forceinline__ uint32_t ex2_pair_h16(uint32_t x2) {
    uint32_t t, r, f, q;
    asm("add.rn.f16x2 %0, %1, %2;" : "=r"(t) : "r"(x2), "r"(0x661E661Fu));
    asm("sub.rn.f16x2 %0, %1, %2;" : "=r"(r) : "r"(t), "r"(0x661E661Fu));
    asm("sub.rn.f16x2 %0, %1, %2;" : "=r"(f) : "r"(x2), "r"(r));
    asm("fma.rn.f16x2 %0, %1, %2, %3;" : "=r"(q) : "r"(0x15101510u), "r"(f), "r"(0x1d7e1d7eu));
    asm("fma.rn.f16x2 %0, %1, %2, %3;" : "=r"(q) : "r"(q), "r"(f), "r"(0x23d823d8u));
    asm("fma.rn.f16x2 %0, %1, %2, %3;" : "=r"(q) : "r"(q), "r"(f), "r"(0x30823035u));
    return t * 128u + q;
}
constexpr float VSCALE_ODD = 0.70703125f;
constexpr float LOG2C_ODD = 0.50015402f;
__device__ __forceinline__ uint32_t pack_f16_sat(float lo, float hi) {
    uint32_t r;
    asm("cvt.rn.satfinite.f16x2.f32 %0, %1, %2;" : "=r"(r) : "f"(hi), "f"(lo));
    return r;
}
__device__ __forceinline__ unsigned int f2ord(float v) {
    const unsigned int u = __float_as_uint(v);
    const unsigned int o = u ^ ((unsigned int)((int)u >> 31) | 0x80000000u);
    return (v == v) ? o : 0u;
}
__device__ __forceinline__ void warp_top2(unsigned int ka, unsigned int ia, unsigned int kb, unsigned int ib, unsigned int& i1, unsigned int& i2) {
    const unsigned int m1 = __reduce_max_sync(0xffffffffu, max(ka, kb));
    i1 = __reduce_min_sync(0xffffffffu, min(ka == m1 ? ia : 0xffffffffu, kb == m1 ? ib : 0xffffffffu));
    const bool ra = (ia == i1), rb = (ib == i1);
    const unsigned int ka2 = ra ? 0u : ka, kb2 = rb ? 0u : kb, ia2 = ra ? 0xffffffffu : ia, ib2 = rb ? 0xffffffffu : ib;
    const unsigned int m2 = __reduce_max_sync(0xffffffffu, max(ka2, kb2));
    i2 = __reduce_min_sync(0xffffffffu, min(ka2 == m2 ? ia2 : 0xffffffffu, kb2 == m2 ? ib2 : 0xffffffffu));
}

constexpr int P1_STAGES = 5;
constexpr int P1_STAGE_BYTES = 16384 + 24576;
constexpr int KV_CHUNK = 10240;
constexpr int SM_Q = 163840 + 49152;
constexpr int SM_A3 = 163840;
constexpr int SM_MISC = 229376;
constexpr int SMEM_TOTAL = 232448;
struct Misc {
    uint64_t p1_full[P1_STAGES], p1_empty[P1_STAGES];
    uint64_t kv[16];
    uint64_t wo[8], ae[8], a3[8], moe;
    unsigned int tag;
    int fast;
    int idx[2], cslot[2];
    alignas(16) float sel[8];
    unsigned int norm[12];
    uint64_t qbar;
    int item, nxt[4];
    unsigned int seq[8];
    unsigned int freed[16];
    union alignas(16) {
        struct { float mu[128], rs[128], cs[192]; } p1;
        struct { float mu[2][64], rs[2][64], r[2][64]; } p3;
    };
};
static_assert(sizeof(Misc) <= SMEM_TOTAL - SM_MISC, "misc smem");

__device__ __forceinline__ void release_kv_chunk(Misc& ms, int j, int lane) {
    asm volatile("{.reg .pred p; setp.eq.s32 p, %1, 0; @p red.relaxed.cta.shared.add.u32 [%0], 1;}" ::"r"(smem_u32(&ms.freed[j])), "r"(lane) : "memory");
}
__device__ __forceinline__ bool refill_kv_chunk(char* smem, Misc& ms, int j, int cta, int lane, const CUtensorMap* tmWo,
                                                const CUtensorMap* tmG, const CUtensorMap* tmU) {
    unsigned int cnt;
    asm volatile("ld.relaxed.cta.shared.u32 %0, [%1];" : "=r"(cnt) : "r"(smem_u32(&ms.freed[j])) : "memory");
    if (cnt < 16u) return false;
    if (lane == 0) {
        const uint32_t dst = smem_u32(smem + j * KV_CHUNK);
        if (j < 8) {
            const uint32_t wb = smem_u32(&ms.wo[j]);
            mbar_expect_tx(wb, 8192);
            tma_2d(dst, tmWo, (cta & 7) * 64, j * 64, wb);
        }
        const uint32_t mb = smem_u32(&ms.moe);
        if (cta < NFFN) {
            mbar_expect_tx(mb, 2048);
            tma_2d(dst + 8192, (j & 8) ? tmU : tmG, cta * 16, (j & 7) * 64, mb);
        }
    }
    __syncwarp();
    return true;
}

template <typename LoadFn>
__device__ __forceinline__ void guarded_item(char* smem, Misc& ms, int r, int t, int warp, LoadFn load_chunk) {
    const int tid = threadIdx.x, lane = tid & 31, w4 = (tid >> 5) & 3;
    const uint64_t descK0 = make_desc(smem_u32(smem), 128, 256, 0);
    const uint64_t descV0 = make_desc(smem_u32(smem + 4096), 128, 2048, 0);
    uint32_t q[4];
    {
        const uint32_t* Qs = reinterpret_cast<const uint32_t*>(smem + SM_Q + t * 2048 + w4 * 512);
        q[0] = Qs[lane]; q[2] = Qs[32 + lane]; q[1] = Qs[64 + lane]; q[3] = Qs[96 + lane];
    }
    float* st = reinterpret_cast<float*>(smem + SM_A3) + t * (12 * 128) + (tid & 127);
    float o[12];
#pragma unroll
    for (int i = 0; i < 8; i++) o[i] = r > 0 ? st[i * 128] : 0.f;
    o[8] = r > 0 ? st[8 * 128] : 0.f; o[10] = r > 0 ? st[9 * 128] : 0.f; o[9] = 0.f; o[11] = 0.f;
    float m0 = r > 0 ? st[10 * 128] : -INFINITY, m1 = r > 0 ? st[11 * 128] : -INFINITY;
#pragma unroll 1
    for (int jh = 2 * CPI * r; jh < 2 * CPI * (r + 1); jh++) {
        const int j = jh >> 1;
        if (t < 4 && (jh & 1) == 0 && warp == j + 5 && lane == 0) load_chunk(warp);
        __syncwarp();
        mbar_wait(smem_u32(&ms.kv[j]), 0);
        float s[32];
        const uint32_t off = j * (KV_CHUNK >> 4);
        wg_fence();
        wgmma_qk64_f32(s, q, descK0 + (uint64_t)(off + (jh & 1) * 128));
        wg_commit();
        wg_wait<0>();
        pin(s);
        pin(o);
        if (t >= 4 && (jh & 1) == 0 && j > 0) release_kv_chunk(ms, j - 1, lane);
        float n0 = m0, n1 = m1;
#pragma unroll
        for (int i = 0; i < 8; i++) {
            n0 = fmaxf(n0, fmaxf(s[4 * i], s[4 * i + 1]));
            n1 = fmaxf(n1, fmaxf(s[4 * i + 2], s[4 * i + 3]));
        }
        n0 = fmaxf(n0, __shfl_xor_sync(0xffffffffu, n0, 1)); n0 = fmaxf(n0, __shfl_xor_sync(0xffffffffu, n0, 2));
        n1 = fmaxf(n1, __shfl_xor_sync(0xffffffffu, n1, 1)); n1 = fmaxf(n1, __shfl_xor_sync(0xffffffffu, n1, 2));
        const float a0 = ex2_mufu(m0 - n0), a1 = ex2_mufu(m1 - n1);
        m0 = n0; m1 = n1;
#pragma unroll
        for (int i = 0; i < 3; i++) { o[4 * i] *= a0; o[4 * i + 1] *= a0; o[4 * i + 2] *= a1; o[4 * i + 3] *= a1; }
        const float e0 = n0 - LOG2C_ODD, e1 = n1 - LOG2C_ODD;
#pragma unroll
        for (int k = 0; k < 4; k++) {
            const uint32_t p0 = pack_bf16(ex2_mufu(s[8 * k] - n0), ex2_mufu(s[8 * k + 1] - n0));
            const uint32_t p1 = pack_bf16(ex2_mufu(s[8 * k + 2] - n1), ex2_mufu(s[8 * k + 3] - n1));
            const uint32_t p2 = pack_bf16(ex2_mufu(s[8 * k + 4] - e0), ex2_mufu(s[8 * k + 5] - e0));
            const uint32_t p3 = pack_bf16(ex2_mufu(s[8 * k + 6] - e1), ex2_mufu(s[8 * k + 7] - e1));
            wg_fence();
            wgmma_pv24(o, p0, p1, p2, p3, descV0 + (uint64_t)(off + ((jh & 1) * 4 + k) * 16));
            wg_commit();
            wg_wait<0>();
            pin(o);
        }
    }
#pragma unroll
    for (int i = 0; i < 8; i++) st[i * 128] = o[i];
    st[8 * 128] = o[8]; st[9 * 128] = o[10]; st[10 * 128] = m0; st[11 * 128] = m1;
}

__global__ void __launch_bounds__(512, 1)
mega_kernel(const __grid_constant__ CUtensorMap tmX, const __grid_constant__ CUtensorMap tmW,
            const __grid_constant__ CUtensorMap tmO, const __grid_constant__ CUtensorMap tmWo,
            const __grid_constant__ CUtensorMap tmG, const __grid_constant__ CUtensorMap tmU, const __grid_constant__ CUtensorMap tmOut,
            const __nv_bfloat16* __restrict__ x, const __nv_bfloat16* __restrict__ wqkv, const __nv_bfloat16* __restrict__ wo,
            const __nv_bfloat16* __restrict__ w_r, const __nv_bfloat16* __restrict__ w_gate,
            const __nv_bfloat16* __restrict__ w_up, const __nv_bfloat16* __restrict__ w_down,
            __nv_bfloat16* __restrict__ out) {
    extern __shared__ __align__(1024) char smem[];
    Misc& ms = *reinterpret_cast<Misc*>(smem + SM_MISC);
    const int tid = threadIdx.x, lane = tid & 31;
    const int warp = __shfl_sync(0xffffffffu, tid >> 5, 0);
    const int wg = warp >> 2, w4 = warp & 3, g = lane >> 2, t4 = lane & 3;
    const int cta = blockIdx.x;
    const int rb = cta >> 3, hg = cta & 7;

    if (warp == 12) {
        if (lane == 0) {
            TS(0);
            if (smem_u32(smem) & 1023) __trap();
            for (int i = 0; i < P1_STAGES; i++) { mbar_init(smem_u32(&ms.p1_full[i]), 1); mbar_init(smem_u32(&ms.p1_empty[i]), 8); }
            asm volatile("fence.mbarrier_init.release.cluster;" ::: "memory");
        }
        __syncwarp();
        bar_arrive(13, 288);
        bar_arrive(14, 256);
    } else {
        if (tid == 32) {
            for (int i = 0; i < 16; i++) mbar_init(smem_u32(&ms.kv[i]), 1);
            for (int i = 0; i < 8; i++) { mbar_init(smem_u32(&ms.wo[i]), 1); mbar_init(smem_u32(&ms.ae[i]), 1); mbar_init(smem_u32(&ms.a3[i]), 1); }
            mbar_init(smem_u32(&ms.moe), 16);
            for (int i = 0; i < 16; i++) ms.freed[i] = 0;
            for (int i = 0; i < 8; i++) ms.seq[i] = 0;
            ms.item = 4;
            mbar_init(smem_u32(&ms.qbar), 1);
            asm volatile("fence.mbarrier_init.release.cluster;" ::: "memory");
        }
        if (tid >= 64 && tid < 76) ms.norm[tid - 64] = 0;
        if (tid >= 96 && tid < 101) {
            const CUtensorMap* tm = tid == 96 ? &tmO : tid == 97 ? &tmWo : tid == 98 ? &tmG : tid == 99 ? &tmU : &tmOut;
            asm volatile("prefetch.tensormap [%0];" ::"l"(tm) : "memory");
        }
        if (tid == 416) ms.tag = __ldcg(&gEpoch) + 1u;
    }

    if (wg < 2) {
        asm volatile("setmaxnreg.inc.sync.aligned.u32 160;");
        float acc[96];
#pragma unroll
        for (int i = 0; i < 96; i++) acc[i] = 0.f;
        bar_sync(13, 288);
#pragma unroll
        for (int kc = 0; kc < 8; kc++) {
            const int s = kc % P1_STAGES;
            mbar_wait(smem_u32(&ms.p1_full[s]), (kc / P1_STAGES) & 1);
            if (tid == 0) TS(24 + kc);
            const uint32_t sa = smem_u32(smem + s * P1_STAGE_BYTES), sb = sa + 16384;
            const uint64_t da = make_desc(sa + wg * 8192, 16, 1024, 1);
            const uint64_t db = make_desc(sb, 8192, 1024, 1);
            wg_fence();
#pragma unroll
            for (int ks = 0; ks < 4; ks++) wgmma_n192(acc, da + ks * 2, db + ks * 128);
            wg_commit();
            wg_wait<1>();
            if (kc > 0 && lane == 0) mbar_arrive(smem_u32(&ms.p1_empty[(kc - 1) % P1_STAGES]));
        }
        wg_wait<0>();
        pin(acc);
        if (tid == 0) TS(1);
        bar_sync(1, 480);
        const unsigned int tag = ms.tag;
        if (tid == 0) TS(16);
        const int lr0 = wg * 64 + w4 * 16 + g, lr1 = lr0 + 8;
        const float mu0 = ms.p1.mu[lr0], mu1 = ms.p1.mu[lr1], rs0 = ms.p1.rs[lr0], rs1 = ms.p1.rs[lr1];
        const int lg0 = wg * 8 + w4 * 2;
        const int rg0 = rb * 16 + lg0;
#pragma unroll
        for (int hh = 0; hh < 4; hh++) {
            const int head = hg * 4 + hh;
            float nrm[3];
#pragma unroll
            for (int sec = 0; sec < 3; sec++) {
                float sq0 = 0.f, sq1 = 0.f, vm = 0.f;
#pragma unroll
                for (int db = 0; db < 2; db++) {
                    const int j = sec * 8 + hh * 2 + db;
                    const float2 c = *reinterpret_cast<const float2*>(&ms.p1.cs[j * 8 + 2 * t4]);
                    const float f0 = sec == 0 ? rs0 * QSCALE : rs0, f1 = sec == 0 ? rs1 * QSCALE : rs1;
                    const float a0 = (acc[4 * j + 0] - mu0 * c.x) * f0, a1 = (acc[4 * j + 1] - mu0 * c.y) * f0;
                    const float b0 = (acc[4 * j + 2] - mu1 * c.x) * f1, b1 = (acc[4 * j + 3] - mu1 * c.y) * f1;
                    const uint32_t pa = sec < 2 ? pack_f16_sat(a0, a1) : pack_bf16(a0, a1);
                    const uint32_t pb = sec < 2 ? pack_f16_sat(b0, b1) : pack_bf16(b0 * VSCALE_ODD, b1 * VSCALE_ODD);
                    if (sec < 2) {
                        uint32_t* dst = sec == 0 ? reinterpret_cast<uint32_t*>(gQ) + ((size_t)head * S_LEN * DH + rg0 * 128) / 2
                                                 : reinterpret_cast<uint32_t*>(gKV) + (size_t)(head * 16 + rb) * 2048 + lg0 * 64;
                        dst[db * 32 + lane] = pa;
                        dst[64 + db * 32 + lane] = pb;
                        sq0 = fmaf(a0, a0, fmaf(a1, a1, sq0));
                        sq1 = fmaf(b0, b0, fmaf(b1, b1, sq1));
                    } else {
                        uint32_t* dst = reinterpret_cast<uint32_t*>(gKV) + (size_t)(head * 16 + rb) * 2048 + 1024 + db * 512 + lg0 * 32;
                        dst[lane] = pa;
                        dst[32 + lane] = pb;
                        vm = fmaxf(vm, fmaxf(fmaxf(fabsf(a0), fabsf(a1)), fmaxf(fabsf(b0), fabsf(b1))));
                        if (!(a0 + a1 + b0 + b1 == a0 + a1 + b0 + b1)) vm = __int_as_float(0x7f800000);
                    }
                }
                if (sec < 2) {
                    sq0 += __shfl_xor_sync(0xffffffffu, sq0, 1); sq0 += __shfl_xor_sync(0xffffffffu, sq0, 2);
                    sq1 += __shfl_xor_sync(0xffffffffu, sq1, 1); sq1 += __shfl_xor_sync(0xffffffffu, sq1, 2);
                    vm = fmaxf(sq0, sq1);
                    if (!(sq0 + sq1 < 3.0e38f)) vm = __int_as_float(0x7f800000);
                }
                nrm[sec] = vm;
            }
            const unsigned int a = __reduce_max_sync(0xffffffffu, __float_as_uint(nrm[0]));
            const unsigned int b = __reduce_max_sync(0xffffffffu, __float_as_uint(nrm[1]));
            const unsigned int c = __reduce_max_sync(0xffffffffu, __float_as_uint(nrm[2]));
            if (lane == 0) { atomicMax(&ms.norm[hh * 3 + 0], a); atomicMax(&ms.norm[hh * 3 + 1], b); atomicMax(&ms.norm[hh * 3 + 2], c); }
        }
        if (tid == 0) TS(17);
        bar_sync(2, 256);
        if (tid == 0) TS(18);
        if (tid < 4) {
            fence_gpu();
            st_pkt(&gFlagQKV[(hg * 16 + rb) * 4 + tid], make_uint4(ms.norm[tid * 3], ms.norm[tid * 3 + 1], ms.norm[tid * 3 + 2], tag));
            if (tid == 0) TS(2);
        }
        asm volatile("setmaxnreg.dec.sync.aligned.u32 128;");
        bar_sync(15, 512);
    } else {
      asm volatile("setmaxnreg.dec.sync.aligned.u32 96;");
      if (wg == 2) {
        const int t = tid - 256;
        if (t < 4) gFlagQKV[(hg * 16 + rb) * 4 + t] = make_uint4(0u, 0u, 0u, 0u);
        bar_sync(14, 256);
        mbar_wait(smem_u32(&ms.p1_full[0]), 0);
        {
            const int row = rb * 128 + hg * 16 + (t >> 3), j = t & 7;
            const uint4* xp = reinterpret_cast<const uint4*>(x + (size_t)row * DM);
            uint4 v[8];
#pragma unroll
            for (int i = 0; i < 8; i++) v[i] = __ldg(xp + i * 8 + j);
            float s1 = 0.f;
#pragma unroll
            for (int i = 0; i < 8; i++) {
                const uint32_t w[4] = {v[i].x, v[i].y, v[i].z, v[i].w};
#pragma unroll
                for (int e = 0; e < 4; e++) s1 += bf_lo(w[e]) + bf_hi(w[e]);
            }
            s1 += __shfl_xor_sync(0xffffffffu, s1, 1); s1 += __shfl_xor_sync(0xffffffffu, s1, 2); s1 += __shfl_xor_sync(0xffffffffu, s1, 4);
            const float mu = s1 * (1.f / DM);
            float s2 = 0.f;
#pragma unroll
            for (int i = 0; i < 8; i++) {
                const uint32_t w[4] = {v[i].x, v[i].y, v[i].z, v[i].w};
#pragma unroll
                for (int e = 0; e < 4; e++) {
                    const float a = bf_lo(w[e]) - mu, b = bf_hi(w[e]) - mu;
                    s2 = fmaf(a, a, fmaf(b, b, s2));
                }
            }
            s2 += __shfl_xor_sync(0xffffffffu, s2, 1); s2 += __shfl_xor_sync(0xffffffffu, s2, 2); s2 += __shfl_xor_sync(0xffffffffu, s2, 4);
            bar_sync(11, 224);
            if (j == 0) st_pkt(&gStat1[row], make_uint4(__float_as_uint(mu), __float_as_uint(rsqrtf(s2 * (1.f / DM) + LN_EPS)), 0u, ms.tag));
        }
        const unsigned int tag = ms.tag;
        if (t == 0) TS(32);
        mbar_wait(smem_u32(&ms.p1_full[2]), 1);
        uint4 st[1];
        wait_pkts<1, 0xffffffffu>(&gStat1[rb * 128 + t], 0, tag, st);
        if (t == 0) TS(34);
        ms.p1.mu[t] = __uint_as_float(st[0].x);
        ms.p1.rs[t] = __uint_as_float(st[0].y);
        bar_arrive(1, 480);
        {
            const uint4 z = make_uint4(0u, 0u, 0u, 0u);
            if (t < 64) { gCand[cta * 64 + t] = z; gCandRow[cta * 64 + t] = z; }
            gPart[cta * 128 + t] = z;
            gYPart[cta * 224 + t] = z;
            if (t < 96) gYPart[cta * 224 + 128 + t] = z;
            if (t < 2) {
                reinterpret_cast<uint4*>(gFlagO)[cta * 2 + t] = z;
                reinterpret_cast<uint4*>(gFlagOut)[cta * 2 + t] = z;
            }
        }
      } else if (warp == 12) {
        if (lane == 0) {
#pragma unroll 1
            for (int kc = 0; kc < 8; kc++) {
                const int s = kc % P1_STAGES;
                if (kc >= P1_STAGES) mbar_wait(smem_u32(&ms.p1_empty[s]), 0);
                const uint32_t bar = smem_u32(&ms.p1_full[s]);
                const uint32_t sa = smem_u32(smem + s * P1_STAGE_BYTES), sb = sa + 16384;
                mbar_expect_tx(bar, P1_STAGE_BYTES);
                tma_2d(sa, &tmX, kc * 64, rb * 128, bar);
#pragma unroll
                for (int p = 0; p < 3; p++) tma_2d(sb + p * 8192, &tmW, p * 512 + hg * 64, kc * 64, bar);
            }
        }
      } else {
        const int t = tid - 416;
        bar_sync(14, 256);
        mbar_wait(smem_u32(&ms.p1_full[0]), 0);
        const int c16 = t >> 2, rs = t & 3;
        const __nv_bfloat16* wp = wqkv + (size_t)(rb * 32 + rs) * (3 * DM) + (c16 >> 3) * 512 + hg * 64 + (c16 & 7) * 8;
        uint4 v[8];
#pragma unroll
        for (int i = 0; i < 8; i++) v[i] = __ldg(reinterpret_cast<const uint4*>(wp + (size_t)i * 4 * (3 * DM)));
        float a[8] = {};
#pragma unroll
        for (int i = 0; i < 8; i++) {
            a[0] += bf_lo(v[i].x); a[1] += bf_hi(v[i].x); a[2] += bf_lo(v[i].y); a[3] += bf_hi(v[i].y);
            a[4] += bf_lo(v[i].z); a[5] += bf_hi(v[i].z); a[6] += bf_lo(v[i].w); a[7] += bf_hi(v[i].w);
        }
#pragma unroll
        for (int e = 0; e < 8; e++) { a[e] += __shfl_xor_sync(0xffffffffu, a[e], 1); a[e] += __shfl_xor_sync(0xffffffffu, a[e], 2); }
        bar_sync(11, 224);
        const unsigned int tag = ms.tag;
        const int pk = c16 * 2 + rs;
        if (rs < 2) st_pkt(&gCsPart[(hg * 16 + rb) * 48 + pk], embed_tag(rs ? a[4] : a[0], rs ? a[5] : a[1], rs ? a[6] : a[2], rs ? a[7] : a[3], tag));
        if (t == 0) TS(35);
        if (t < 16) { uint4 gate[1]; wait_pkts4<1>(&gCsPart[(hg * 16 + t) * 48 + 47], 0, tag, gate); }
        bar_sync(8, 96);
        if (t == 0) TS(36);
        {
            const int pq = c16 * 2 + (rs & 1);
            uint4 p[8];
            wait_pkts4<8>(&gCsPart[(hg * 16 + (rs >> 1) * 8) * 48 + pq], 48, tag, p);
            float s0 = 0.f, s1 = 0.f, s2 = 0.f, s3 = 0.f;
#pragma unroll
            for (int i = 0; i < 8; i++) {
                s0 += __uint_as_float(p[i].x); s1 += __uint_as_float(p[i].y); s2 += __uint_as_float(p[i].z); s3 += __uint_as_float(p[i].w);
            }
            s0 += __shfl_xor_sync(0xffffffffu, s0, 2); s1 += __shfl_xor_sync(0xffffffffu, s1, 2);
            s2 += __shfl_xor_sync(0xffffffffu, s2, 2); s3 += __shfl_xor_sync(0xffffffffu, s3, 2);
            if (rs < 2) *reinterpret_cast<float4*>(&ms.p1.cs[pq * 4]) = make_float4(s0, s1, s2, s3);
            if (t == 0) TS(37);
        }
        __syncwarp();
        bar_arrive(1, 480);
      }
      __syncwarp();
      bar_sync(15, 512);
      asm volatile("setmaxnreg.inc.sync.aligned.u32 128;");
    }
    if (tid == 0) TS(20);
    const unsigned int tag = ms.tag;

    const int head = hg * 4 + (rb >> 2), quarter = rb & 3;
    {
#pragma unroll
        for (int i = 0; i < 4; i++) {
            const int e = tid + i * 512;
            *reinterpret_cast<uint4*>(smem + (e >> 7) * KV_CHUNK + 8192 + (e & 127) * 16) = make_uint4((e & 8) ? 0x00003F35u : 0x00003F80u, 0, 0, 0);
        }
        asm volatile("fence.proxy.async.shared::cta;" ::: "memory");
    }
    if (warp == 0) {
        uint4 n[1];
        wait_pkts<1, 0xffffffffu>(&gFlagQKV[(hg * 16 + (lane & 15)) * 4 + (rb >> 2)], 0, tag, n);
        __syncwarp();
        if (lane == 0) TS(21);
        const float q2 = __uint_as_float(__reduce_max_sync(0xffffffffu, n[0].x));
        const float k2 = __uint_as_float(__reduce_max_sync(0xffffffffu, n[0].y));
        const float vm = __uint_as_float(__reduce_max_sync(0xffffffffu, n[0].z));
        if (lane == 0) ms.fast = (q2 * k2 * 1.02f <= 812.f) && (q2 <= 1.0e6f) && (k2 <= 1.0e6f) && (vm <= 1.0e18f) && (vm >= 1.0e-18f || vm == 0.f);
    }
    __syncthreads();
    auto load_kv_chunk = [&](int j) {
        fence_proxy_async_global();
        const uint32_t bar = smem_u32(&ms.kv[j]);
        mbar_expect_tx(bar, 8192);
        bulk_g2s(smem_u32(smem + j * KV_CHUNK), reinterpret_cast<const char*>(gKV) + (size_t)(head * 16 + j) * 8192, 8192, bar);
    };
    if (lane == 0) {
        if (warp == 5) {
            fence_proxy_async_global();
            mbar_expect_tx(smem_u32(&ms.qbar), 16384);
            bulk_g2s(smem_u32(smem + SM_Q), reinterpret_cast<const char*>(gQ) + (size_t)head * 65536 + quarter * 16384, 16384, smem_u32(&ms.qbar));
        }
        if (warp < 5) load_kv_chunk(warp);
    }
    __syncwarp();
    if (tid == 0) TS(3);
    bool refilled = false;
    {
        const bool fast = ms.fast != 0;
        const uint64_t descKe = make_desc(smem_u32(smem), 128, 512, 0);
        const uint64_t descKo = make_desc(smem_u32(smem) + 256, 128, 512, 0);
        const uint64_t descV0 = make_desc(smem_u32(smem + 4096), 128, 2048, 0);
        auto release_chunk = [&](int j) { release_kv_chunk(ms, j, lane); };
        float* sAcc = reinterpret_cast<float*>(smem + SM_A3);
        const int t128 = tid & 127;
        mbar_wait(smem_u32(&ms.qbar), 0);
        auto run_items = [&](auto FAST) {
        int item = wg * NR;
#pragma unroll 1
        while (item < 8 * NR) {
            const int r = item % NR, t = item / NR;
            if (t128 == 0) ms.nxt[wg] = ((item % NR) == NR - 1) ? item + 3 * NR + 1 : item + 1;
            if (r > 0) {
                int it = 0;
                unsigned int sq;
                while (true) {
                    asm volatile("ld.acquire.cta.shared.u32 %0, [%1];" : "=r"(sq) : "r"(smem_u32(&ms.seq[t])) : "memory");
                    if (sq >= (unsigned int)r) break;
                    if (++it > SPIN_LIMIT) __trap();
                }
            }
            uint32_t q[4];
            {
                const uint32_t* Qs = reinterpret_cast<const uint32_t*>(smem + SM_Q + t * 2048 + w4 * 512);
                q[0] = Qs[lane]; q[2] = Qs[32 + lane]; q[1] = Qs[64 + lane]; q[3] = Qs[96 + lane];
            }
            float* st = sAcc + t * (12 * 128) + t128;
            float o[12];
#pragma unroll
            for (int i = 0; i < 8; i++) o[i] = r > 0 ? st[i * 128] : 0.f;
            o[8] = r > 0 ? st[8 * 128] : 0.f; o[10] = r > 0 ? st[9 * 128] : 0.f; o[9] = 0.f; o[11] = 0.f;
            if constexpr (decltype(FAST)::value) {
#pragma unroll 1
                for (int j = CPI * r; j < CPI * (r + 1); j++) {
                    if (t < 4 && warp == j + 5 && lane == 0) load_kv_chunk(warp);
                    __syncwarp();
                    mbar_wait(smem_u32(&ms.kv[j]), 0);
                    float s[32];
                    uint32_t h[16];
                    const uint32_t vlo = (uint32_t)descV0 + j * (KV_CHUNK >> 4);
                    wg_fence();
                    wgmma_qk64_f32(s, q, descKe + (uint64_t)(j * (KV_CHUNK >> 4)));
                    wgmma_qk64_f16(h, q, descKo + (uint64_t)(j * (KV_CHUNK >> 4)));
                    wg_commit();
                    wg_wait<0>();
                    pin(s);
                    pin(h);
                    if (t >= 4) {
                        if (j > 0) release_chunk(j - 1);
                        if (!refilled && j > warp) refilled = refill_kv_chunk(smem, ms, warp, cta, lane, &tmWo, &tmG, &tmU);
                    }
#pragma unroll
                    for (int kg = 0; kg < 8 / PVG; kg++) {
                        uint32_t p[4 * PVG];
#pragma unroll
                        for (int u = 0; u < PVG; u++) {
                            const int k = kg * PVG + u;
                            p[4 * u + 0] = pack_bf16(ex2_mufu(s[4 * k]), ex2_mufu(s[4 * k + 1]));
                            p[4 * u + 1] = pack_bf16(ex2_mufu(s[4 * k + 2]), ex2_mufu(s[4 * k + 3]));
                            p[4 * u + 2] = ex2_pair_h16(h[2 * k]);
                            p[4 * u + 3] = ex2_pair_h16(h[2 * k + 1]);
                        }
                        wg_fence();
#pragma unroll
                        for (int u = 0; u < PVG; u++)
                            wgmma_pv24_lh(o, p[4 * u], p[4 * u + 1], p[4 * u + 2], p[4 * u + 3], vlo + (kg * PVG + u) * 16, (uint32_t)(descV0 >> 32));
                        wg_commit();
                        wg_wait<PVWAIT>();
                    }
                }
                wg_wait<0>();
                pin(o);
            } else {
                guarded_item(smem, ms, r, t, warp, load_kv_chunk);
#pragma unroll
                for (int i = 0; i < 8; i++) o[i] = st[i * 128];
                o[8] = st[8 * 128]; o[10] = st[9 * 128];
            }
            if (t >= 4) release_chunk(15);
            if (r < NR - 1) {
#pragma unroll
                for (int i = 0; i < 8; i++) st[i * 128] = o[i];
                st[8 * 128] = o[8]; st[9 * 128] = o[10];
            } else {
                const float l0 = __shfl_sync(0xffffffffu, o[8], lane & ~3), l1 = __shfl_sync(0xffffffffu, o[10], lane & ~3);
                const float r0 = __fdividef(1.f, l0), r1 = __fdividef(1.f, l1);
                uint32_t* Op = reinterpret_cast<uint32_t*>(gO + (size_t)(quarter * 512 + t * 64 + w4 * 16) * DM + head * DH);
                Op[g * 256 + t4] = pack_bf16(o[0] * r0, o[1] * r0);
                Op[(g + 8) * 256 + t4] = pack_bf16(o[2] * r1, o[3] * r1);
                Op[g * 256 + 4 + t4] = pack_bf16(o[4] * r0, o[5] * r0);
                Op[(g + 8) * 256 + 4 + t4] = pack_bf16(o[6] * r1, o[7] * r1);
            }
            bar_sync(3 + wg, 128);
            if (t128 == 0) {
                asm volatile("st.release.cta.shared.u32 [%0], %1;" ::"r"(smem_u32(&ms.seq[t])), "r"(r + 1) : "memory");
                if (t < 4) st_flag(&gFlagO[(quarter * 8 + t) * 32 + head], tag);
            }
            if (r == 0 && t == 3 && tid == 511) {
                bulk_prefetch_l2(reinterpret_cast<const char*>(w_down) + cta * 14336, 14336);
            }
            item = ms.nxt[wg];
            bar_sync(3 + wg, 128);
        }
        };
        if (fast) run_items(std::true_type{}); else run_items(std::false_type{});
    }
    __syncthreads();
    if (!refilled) refill_kv_chunk(smem, ms, warp, cta, lane, &tmWo, &tmG, &tmU);
    if (warp == 0 && lane < 4) { fence_gpu(); asm volatile("st.relaxed.gpu.global.u32 [%0], %1;" ::"l"(&gFlagO[(quarter * 8 + 4 + lane) * 32 + head]), "r"(tag) : "memory"); }
    if (tid == 0) TS(4);

    const int pi = cta >> 3, pc = cta & 7;
    const int tileE = (pi >> 2) * 8 + (pi & 3);
    if (wg < 2) {
        const int T = tileE + wg * 4, t128 = tid & 127;
        const int r0 = T * 64 + w4 * 16 + g, r1 = r0 + 8;
        const int col0 = pc * 64 + 2 * t4;
        uint32_t xa[8], xb[8], wr[8];
#pragma unroll
        for (int j = 0; j < 8; j++) {
            xa[j] = __ldg(reinterpret_cast<const uint32_t*>(x + (size_t)r0 * DM + col0 + j * 8));
            xb[j] = __ldg(reinterpret_cast<const uint32_t*>(x + (size_t)r1 * DM + col0 + j * 8));
            wr[j] = __ldg(reinterpret_cast<const uint32_t*>(w_r + col0 + j * 8));
        }
        const float p0 = __bfloat162float(x[(size_t)r0 * DM]), p1 = __bfloat162float(x[(size_t)r1 * DM]);
        const float pivot = __bfloat162float(x[(size_t)(T * 64 + (t128 >> 1)) * DM]);
        float wsum = 0.f;
        {
            const uint4 a = __ldg(reinterpret_cast<const uint4*>(w_r) + lane), b = __ldg(reinterpret_cast<const uint4*>(w_r) + 32 + lane);
            const uint32_t w[8] = {a.x, a.y, a.z, a.w, b.x, b.y, b.z, b.w};
#pragma unroll
            for (int e = 0; e < 8; e++) wsum += bf_lo(w[e]) + bf_hi(w[e]);
#pragma unroll
            for (int m = 16; m; m >>= 1) wsum += __shfl_xor_sync(0xffffffffu, wsum, m);
        }
        const uint32_t a_base = smem_u32(smem) + (wg == 0 ? 8 * KV_CHUNK : SM_A3), a_step = wg == 0 ? KV_CHUNK : 8192;
        const uint32_t a_bar = smem_u32(wg == 0 ? &ms.ae[0] : &ms.a3[0]);
        float acc[32];
#pragma unroll
        for (int i = 0; i < 32; i++) acc[i] = 0.f;
#pragma unroll 1
        for (int kc = 0; kc < 8; kc++) {
            mbar_wait(smem_u32(&ms.wo[kc]), 0);
            mbar_wait(a_bar + kc * 8, 0);
            const uint64_t da = make_desc(a_base + kc * a_step, 16, 1024, 1);
            const uint64_t db = make_desc(smem_u32(smem + kc * KV_CHUNK), 8192, 1024, 1);
            wg_fence();
#pragma unroll
            for (int ks = 0; ks < 4; ks++) wgmma_n64(acc, da + ks * 2, db + ks * 128);
            wg_commit();
        }
        wg_wait<0>();
        pin(acc);
        if (tid == 128) TS(6);
        float s1a = 0.f, s2a = 0.f, s3a = 0.f, s1b = 0.f, s2b = 0.f, s3b = 0.f;
#pragma unroll
        for (int j = 0; j < 8; j++) {
            const uint32_t ha = pack_bf16(bf_lo(xa[j]) + acc[4 * j], bf_hi(xa[j]) + acc[4 * j + 1]);
            const uint32_t hb = pack_bf16(bf_lo(xb[j]) + acc[4 * j + 2], bf_hi(xb[j]) + acc[4 * j + 3]);
            xa[j] = ha; xb[j] = hb;
            const float w0 = bf_lo(wr[j]), w1 = bf_hi(wr[j]);
            const float da0 = bf_lo(ha) - p0, da1 = bf_hi(ha) - p0, db0 = bf_lo(hb) - p1, db1 = bf_hi(hb) - p1;
            s1a += da0 + da1; s2a = fmaf(da0, da0, fmaf(da1, da1, s2a)); s3a = fmaf(da0, w0, fmaf(da1, w1, s3a));
            s1b += db0 + db1; s2b = fmaf(db0, db0, fmaf(db1, db1, s2b)); s3b = fmaf(db0, w0, fmaf(db1, w1, s3b));
        }
#pragma unroll
        for (int m = 1; m <= 2; m <<= 1) {
            s1a += __shfl_xor_sync(0xffffffffu, s1a, m); s2a += __shfl_xor_sync(0xffffffffu, s2a, m); s3a += __shfl_xor_sync(0xffffffffu, s3a, m);
            s1b += __shfl_xor_sync(0xffffffffu, s1b, m); s2b += __shfl_xor_sync(0xffffffffu, s2b, m); s3b += __shfl_xor_sync(0xffffffffu, s3b, m);
        }
        if (t4 < 2) {
            const int lr = w4 * 16 + g + t4 * 8;
            st_pkt(&gPart[(T * 64 + lr) * 8 + pc],
                   make_uint4(__float_as_uint(t4 ? s1b : s1a), __float_as_uint(t4 ? s2b : s2a), __float_as_uint(t4 ? s3b : s3a), tag));
        }
        {
            const int lr = t128 >> 1;
            uint4 pv[4];
            wait_pkts<4, 0xffffffffu>(&gPart[T * 512 + t128 * 4], 1, tag, pv);
            float s1 = 0.f, s2 = 0.f, s3 = 0.f;
#pragma unroll
            for (int i = 0; i < 4; i++) { s1 += __uint_as_float(pv[i].x); s2 += __uint_as_float(pv[i].y); s3 += __uint_as_float(pv[i].z); }
            if (tid == 128) TS(14);
            s1 += __shfl_xor_sync(0xffffffffu, s1, 1); s2 += __shfl_xor_sync(0xffffffffu, s2, 1); s3 += __shfl_xor_sync(0xffffffffu, s3, 1);
            if ((t128 & 1) == 0) {
                const float md = s1 * (1.f / DM);
                const float var = fmaxf(s2 * (1.f / DM) - md * md, 0.f);
                const float rs = rsqrtf(var + LN_EPS);
                ms.p3.mu[wg][lr] = pivot + md;
                ms.p3.rs[wg][lr] = rs;
                ms.p3.r[wg][lr] = (s3 - md * wsum) * rs;
            }
        }
        bar_sync(3 + wg, 128);
        if (tid == 128) TS(7);
        {
            unsigned int i1, i2;
            warp_top2(f2ord(ms.p3.r[wg][lane]), lane, f2ord(ms.p3.r[wg][lane + 32]), lane + 32, i1, i2);
            if (pc == 0) {
#pragma unroll
                for (int c = 0; c < 2; c++) {
                    const int li = c ? i2 : i1;
                    st_pkt(&gCand[t128 * 64 + T * 2 + c],
                           make_uint4(__float_as_uint(ms.p3.r[wg][li]), __float_as_uint(ms.p3.mu[wg][li]), __float_as_uint(ms.p3.rs[wg][li]),
                                      (tag << 11) | (unsigned int)(T * 64 + li)));
                }
            }
#pragma unroll
            for (int c = 0; c < 2; c++) {
                const unsigned int li = c ? i2 : i1;
                if ((int)(li >> 4) == w4 && (int)(li & 7) == g) {
                    const bool hi = (li & 8) != 0;
                    uint4* dst = &gCandRow[(T * 2 + c) * 128 + pc * 16 + t4];
#pragma unroll
                    for (int q = 0; q < 4; q++)
                        st_pkt(dst + q * 4, make_uint4(hi ? xb[2 * q] : xa[2 * q], hi ? xb[2 * q + 1] : xa[2 * q + 1], 0u, tag));
                }
            }
            if (tid == 128) TS(15);
        }
        {
            const int lr0 = w4 * 16 + g;
            const float mu0 = ms.p3.mu[wg][lr0], rs0 = ms.p3.rs[wg][lr0], mu1 = ms.p3.mu[wg][lr0 + 8], rs1 = ms.p3.rs[wg][lr0 + 8];
            char* so = smem + (wg == 0 ? 8 * KV_CHUNK : SM_A3);
#pragma unroll
            for (int j = 0; j < 8; j++) {
                const float a0 = bf_lo(xa[j]), a1 = bf_hi(xa[j]), b0 = bf_lo(xb[j]), b1 = bf_hi(xb[j]);
                const uint32_t la = pack_bf16((a0 - mu0) * rs0, (a1 - mu0) * rs0);
                const uint32_t lb = pack_bf16((b0 - mu1) * rs1, (b1 - mu1) * rs1);
                const int o = ((j ^ g) << 4) + t4 * 4;
                *reinterpret_cast<uint32_t*>(so + lr0 * 128 + o) = pack_bf16(a0 + bf_lo(la), a1 + bf_hi(la));
                *reinterpret_cast<uint32_t*>(so + (lr0 + 8) * 128 + o) = pack_bf16(b0 + bf_lo(lb), b1 + bf_hi(lb));
            }
            asm volatile("fence.proxy.async.shared::cta;" ::: "memory");
            bar_sync(3 + wg, 128);
            if (t128 == 0) {
                tma_store_2d(&tmOut, smem_u32(so), pc * 64, T * 64);
                asm volatile("cp.async.bulk.wait_group 0;" ::: "memory");
                st_flag(&gFlagOut[cta * 8 + wg], tag);
            }
        }
    } else {
        const int t = tid - 256;
        {
            const int kc = warp - 8;
            if (lane == 0) {
#pragma unroll
                for (int e = 0; e < 2; e++) {
                    const int T = tileE + e * 4;
                    int it = 0;
                    while (true) {
                        const uint4 f = ld_pkt(reinterpret_cast<const uint4*>(&gFlagO[T * 32 + kc * 4]));
                        if (f.x == tag && f.y == tag && f.z == tag && f.w == tag) break;
                        if (++it > SPIN_LIMIT) __trap();
                        BACKOFF();
                    }
                    if (kc == 7 && e == 1) TS(5);
                    fence_proxy_async_global();
                    const uint32_t bar = smem_u32(e ? &ms.a3[kc] : &ms.ae[kc]);
                    mbar_expect_tx(bar, 8192);
                    tma_2d(smem_u32(smem) + (e ? SM_A3 + kc * 8192 : (8 + kc) * KV_CHUNK), &tmO, kc * 64, T * 64, bar);
                }
            }
            __syncwarp();
        }
        uint32_t wd[16];
        if (cta < NFFN) {
#pragma unroll
            for (int k = 0; k < 16; k++) wd[k] = __ldg(reinterpret_cast<const uint32_t*>(w_down + (size_t)(cta * 16 + k) * DM + 2 * t));
        }
        if (warp == 8) {
            if (lane == 0) TS(56);
            uint4 cv[2];
            wait_pkts<2, 0xfffff800u>(&gCand[cta * 64 + lane * 2], 1, tag << 11, cv);
            if (lane == 0) TS(54);
            unsigned int i1, i2;
            warp_top2(f2ord(__uint_as_float(cv[0].x)), cv[0].w & 0x7ffu, f2ord(__uint_as_float(cv[1].x)), cv[1].w & 0x7ffu, i1, i2);
#pragma unroll
            for (int c = 0; c < 2; c++) {
                const unsigned int ci = cv[c].w & 0x7ffu;
                if (ci == i1 || ci == i2) {
                    const int o = ci == i1 ? 0 : 1;
                    ms.idx[o] = (int)ci;
                    ms.cslot[o] = lane * 2 + c;
                    *reinterpret_cast<float4*>(&ms.sel[o * 4]) =
                        make_float4(__uint_as_float(cv[c].y), __uint_as_float(cv[c].z), __fdividef(1.f, 1.f + __expf(-__uint_as_float(cv[c].x))), 0.f);
                }
            }
            if (lane == 0) TS(8);
        }
        bar_sync(2, 256);
        const int idx0 = ms.idx[0], idx1 = ms.idx[1];
        if (t == 0 && idx0 >= 0) TS(61);
        float* sX = reinterpret_cast<float*>(smem);
        float* sH = sX + 1024;
        float* sPart = reinterpret_cast<float*>(smem + KV_CHUNK);
        float* sAct = sPart + 512;
        if (cta < NFFN) {
            {
                const int tk = t >> 7, P = t & 127;
                uint4 hv[1];
                wait_pkts<1, 0xffffffffu>(&gCandRow[ms.cslot[tk] * 128 + P], 0, tag, hv);
                if (t == 0) TS(57);
                const float mu = ms.sel[tk * 4], rs = ms.sel[tk * 4 + 1];
                const int col = (P >> 4) * 64 + ((P >> 2) & 3) * 16 + (P & 3) * 2;
                const uint32_t l0 = pack_bf16((bf_lo(hv[0].x) - mu) * rs, (bf_hi(hv[0].x) - mu) * rs);
                const uint32_t l1 = pack_bf16((bf_lo(hv[0].y) - mu) * rs, (bf_hi(hv[0].y) - mu) * rs);
                *reinterpret_cast<float2*>(&sX[tk * 512 + col]) = make_float2(bf_lo(l0), bf_hi(l0));
                *reinterpret_cast<float2*>(&sX[tk * 512 + col + 8]) = make_float2(bf_lo(l1), bf_hi(l1));
                *reinterpret_cast<float2*>(&sH[tk * 512 + col]) = make_float2(bf_lo(hv[0].x), bf_hi(hv[0].x));
                *reinterpret_cast<float2*>(&sH[tk * 512 + col + 8]) = make_float2(bf_lo(hv[0].y), bf_hi(hv[0].y));
            }
            mbar_wait(smem_u32(&ms.moe), 0);
            bar_sync(1 + 8, 256);
            if (t == 0) { asm volatile("" ::: "memory"); sAct[40] = sX[0]; TS(58); }
            {
                const int wv = warp - 8, kk = lane >> 3, cp = lane & 7;
                float a[2][2][2] = {};
#pragma unroll
                for (int i = 0; i < 16; i++) {
                    const int k = wv * 64 + i * 4 + kk;
                    const float x0 = sX[k], x1 = sX[512 + k];
#pragma unroll
                    for (int mat = 0; mat < 2; mat++) {
                        const uint32_t w = *reinterpret_cast<const uint32_t*>(smem + (mat * 8 + wv) * KV_CHUNK + 8192 + (i * 4 + kk) * 32 + cp * 4);
                        a[mat][0][0] = fmaf(x0, bf_lo(w), a[mat][0][0]); a[mat][0][1] = fmaf(x0, bf_hi(w), a[mat][0][1]);
                        a[mat][1][0] = fmaf(x1, bf_lo(w), a[mat][1][0]); a[mat][1][1] = fmaf(x1, bf_hi(w), a[mat][1][1]);
                    }
                }
#pragma unroll
                for (int mat = 0; mat < 2; mat++)
#pragma unroll
                    for (int tk = 0; tk < 2; tk++)
#pragma unroll
                        for (int e = 0; e < 2; e++) {
                            float v = a[mat][tk][e];
                            v += __shfl_xor_sync(0xffffffffu, v, 8);
                            v += __shfl_xor_sync(0xffffffffu, v, 16);
                            if (kk == 0) sPart[(wv * 2 + tk) * 32 + mat * 16 + 2 * cp + e] = v;
                        }
            }
            bar_sync(1 + 8, 256);
            if (t == 0) { sAct[41] = sPart[0]; TS(59); }
            if (t < 32) {
                const int tk = t >> 4, c = t & 15;
                float gs = 0.f, us = 0.f;
#pragma unroll
                for (int w = 0; w < 8; w++) { gs += sPart[(w * 2 + tk) * 32 + c]; us += sPart[(w * 2 + tk) * 32 + 16 + c]; }
                const float gb = bf_round(gs), ub = bf_round(us);
                const float sl = bf_round(__fdividef(gb, 1.f + __expf(-gb)));
                sAct[tk * 16 + c] = bf_round(sl * ub);
            }
            bar_sync(1 + 8, 256);
            {
                float y00 = 0.f, y01 = 0.f, y10 = 0.f, y11 = 0.f;
#pragma unroll
                for (int k = 0; k < 16; k++) {
                    const float a0 = sAct[k], a1 = sAct[16 + k];
                    y00 = fmaf(a0, bf_lo(wd[k]), y00); y01 = fmaf(a0, bf_hi(wd[k]), y01);
                    y10 = fmaf(a1, bf_lo(wd[k]), y10); y11 = fmaf(a1, bf_hi(wd[k]), y11);
                }
                st_pkt(&gYPart[((t >> 2) * NFFN + cta) * 4 + (t & 3)], embed_tag(y00, y01, y10, y11, tag));
            }
            if (t == 0) TS(9);
        }
        if (cta < 64) {
            const int pc = t & 3, part = t >> 2;
            const int opc = (t >> 2) & 3, oe = t & 3, otk = oe >> 1, ocol = (cta * 4 + opc) * 2 + (oe & 1);
            float y[4] = {0.f, 0.f, 0.f, 0.f};
            if (part < 56) {
                uint4 yv[2];
                wait_pkts4<2>(&gYPart[(cta * NFFN + part) * 4 + pc], 56 * 4, tag, yv);
                if (t == 0) TS(60);
                y[0] = __uint_as_float(yv[0].x) + __uint_as_float(yv[1].x); y[1] = __uint_as_float(yv[0].y) + __uint_as_float(yv[1].y);
                y[2] = __uint_as_float(yv[0].z) + __uint_as_float(yv[1].z); y[3] = __uint_as_float(yv[0].w) + __uint_as_float(yv[1].w);
            }
            if (t >= 224 && t < 226) {
                const int orow = (t & 1) ? idx1 : idx0, oc = cta * 8;
                const int oT = orow >> 6;
                wait_flag(&gFlagOut[((((oT >> 3) * 4 + (oT & 3)) * 8) + (oc >> 6)) * 8 + ((oT >> 2) & 1)], tag);
            }
            __syncwarp();
#pragma unroll
            for (int e = 0; e < 4; e++) {
                y[e] += __shfl_xor_sync(0xffffffffu, y[e], 4); y[e] += __shfl_xor_sync(0xffffffffu, y[e], 8); y[e] += __shfl_xor_sync(0xffffffffu, y[e], 16);
            }
            float* sR = sAct + 32;
            if (lane < 4) *reinterpret_cast<float4*>(&sR[(warp - 8) * 16 + lane * 4]) = make_float4(y[0], y[1], y[2], y[3]);
            bar_sync(1 + 8, 256);
            if (t < 16) {
                float s = 0.f;
#pragma unroll
                for (int w = 0; w < 8; w++) s += sR[w * 16 + t];
                const float yb = bf_round(bf_round(s) * ms.sel[otk * 4 + 2]);
                out[(size_t)(otk ? idx1 : idx0) * DM + ocol] = __float2bfloat16(sH[otk * 512 + ocol] + bf_round(sX[otk * 512 + ocol] + yb));
            }
            if (cta == 0 && t == 0) {
                *reinterpret_cast<volatile unsigned int*>(&gEpoch) = tag;
            }
            if (t == 0) TS(10);
        }
    }
}

typedef CUresult (*EncodeFn)(CUtensorMap*, CUtensorMapDataType, cuuint32_t, void*, const cuuint64_t*, const cuuint64_t*,
                             const cuuint32_t*, const cuuint32_t*, CUtensorMapInterleave, CUtensorMapSwizzle,
                             CUtensorMapL2promotion, CUtensorMapFloatOOBfill);

void make_map(EncodeFn enc, CUtensorMap* tm, const void* base, uint64_t cols, uint64_t rows, uint32_t box_c, uint32_t box_r, bool swz) {
    cuuint64_t dims[2] = {cols, rows};
    cuuint64_t strides[1] = {cols * 2};
    cuuint32_t box[2] = {box_c, box_r};
    cuuint32_t es[2] = {1, 1};
    enc(tm, CU_TENSOR_MAP_DATA_TYPE_BFLOAT16, 2, const_cast<void*>(base), dims, strides, box, es, CU_TENSOR_MAP_INTERLEAVE_NONE,
        swz ? CU_TENSOR_MAP_SWIZZLE_128B : CU_TENSOR_MAP_SWIZZLE_NONE, CU_TENSOR_MAP_L2_PROMOTION_L2_256B,
        CU_TENSOR_MAP_FLOAT_OOB_FILL_NONE);
}

}

extern "C" void kernel_launch(void* const* d_in, const int* in_sizes, int n_in, void* d_out, int out_size) {
    const __nv_bfloat16* x = (const __nv_bfloat16*)d_in[0];
    const __nv_bfloat16* wqkv = (const __nv_bfloat16*)d_in[1];
    const __nv_bfloat16* wo = (const __nv_bfloat16*)d_in[2];
    const __nv_bfloat16* w_r = (const __nv_bfloat16*)d_in[4];
    const __nv_bfloat16* w_gate = (const __nv_bfloat16*)d_in[5];
    const __nv_bfloat16* w_up = (const __nv_bfloat16*)d_in[6];
    const __nv_bfloat16* w_down = (const __nv_bfloat16*)d_in[7];
    __nv_bfloat16* out = (__nv_bfloat16*)d_out;

    static EncodeFn enc = nullptr;
    static void* pO = nullptr;
    if (!enc) {
        void* fn = nullptr;
        cudaDriverEntryPointQueryResult qr;
        cudaGetDriverEntryPoint("cuTensorMapEncodeTiled", &fn, cudaEnableDefault, &qr);
        enc = (EncodeFn)fn;
        cudaGetSymbolAddress(&pO, gO);
        cudaFuncSetAttribute(mega_kernel, cudaFuncAttributeMaxDynamicSharedMemorySize, SMEM_TOTAL);
    }
    CUtensorMap tmX, tmW, tmO, tmWo, tmG, tmU, tmOut;
    make_map(enc, &tmX, x, DM, S_LEN, 64, 128, true);
    make_map(enc, &tmW, wqkv, 3 * DM, DM, 64, 64, true);
    make_map(enc, &tmO, pO, DM, S_LEN, 64, 64, true);
    make_map(enc, &tmWo, wo, DM, DM, 64, 64, true);
    make_map(enc, &tmG, w_gate, FF, DM, 16, 64, false);
    make_map(enc, &tmU, w_up, FF, DM, 16, 64, false);
    make_map(enc, &tmOut, out, DM, S_LEN, 64, 64, true);

    mega_kernel<<<128, 512, SMEM_TOTAL, cudaStreamPerThread>>>(tmX, tmW, tmO, tmWo, tmG, tmU, tmOut, x, wqkv, wo, w_r, w_gate, w_up, w_down, out);
}
```

```cpp
#include <cuda_runtime.h>
#include <cuda_bf16.h>
#include <cuda.h>
#include <stdint.h>
#include <type_traits>

namespace {

constexpr int S_LEN = 2048, DM = 512, NH = 32, DH = 16, FF = 1792;
constexpr int NFFN = FF / 16;
constexpr float LN_EPS = 1e-5f;
constexpr float QSCALE = 0.25f * 1.4426950408889634f;

__device__ __align__(1024) __nv_bfloat16 gQ[NH * S_LEN * DH];
__device__ __align__(1024) __nv_bfloat16 gKV[NH * S_LEN * DH * 2];
__device__ __align__(1024) __nv_bfloat16 gO[S_LEN * DM];
__device__ unsigned int gEpoch;
__device__ uint4 gFlagQKV[128 * 4];
__device__ __align__(32) unsigned int gFlagO[32 * 32];
__device__ uint4 gStat1[S_LEN];
__device__ uint4 gCsPart[8 * 16 * 48];
__device__ uint4 gPart[32 * 64 * 4];
__device__ uint4 gCand[128 * 64];
__device__ __align__(32) unsigned int gFlagOut[128 * 8];
__device__ uint4 gCandRow[64 * 128];
__device__ uint4 gYPart[NFFN * 256];

#define TS(slot) do {} while (0)

__device__ __forceinline__ uint32_t smem_u32(const void* p) { return (uint32_t)__cvta_generic_to_shared(p); }
__device__ __forceinline__ void mbar_init(uint32_t bar, uint32_t cnt) {
    asm volatile("mbarrier.init.shared::cta.b64 [%0], %1;" ::"r"(bar), "r"(cnt));
}
__device__ __forceinline__ void mbar_expect_tx(uint32_t bar, uint32_t bytes) {
    asm volatile("mbarrier.arrive.expect_tx.shared::cta.b64 _, [%0], %1;" ::"r"(bar), "r"(bytes) : "memory");
}
__device__ __forceinline__ void mbar_arrive(uint32_t bar) {
    asm volatile("mbarrier.arrive.shared::cta.b64 _, [%0];" ::"r"(bar) : "memory");
}
constexpr int SPIN_LIMIT = 1 << 22;
#define ITEMMODE 0
#define PVG 2
#define PVWAIT 2
#define CPI 16
#define NR (16 / CPI)
#define BACKOFF() __nanosleep(32)
__device__ __forceinline__ void mbar_wait(uint32_t bar, uint32_t parity) {
    uint32_t done = 0;
    int it = 0;
    while (true) {
        asm volatile("{.reg .pred p; mbarrier.try_wait.parity.shared::cta.b64 p, [%1], %2; selp.u32 %0, 1, 0, p;}"
                     : "=r"(done) : "r"(bar), "r"(parity) : "memory");
        if (done) break;
        if (++it > SPIN_LIMIT) __trap();
    }
}
__device__ __forceinline__ void bulk_g2s(uint32_t dst, const void* src, uint32_t bytes, uint32_t bar) {
    asm volatile("cp.async.bulk.shared::cluster.global.mbarrier::complete_tx::bytes [%0], [%1], %2, [%3];"
                 ::"r"(dst), "l"(src), "r"(bytes), "r"(bar) : "memory");
}
__device__ __forceinline__ void bulk_prefetch_l2(const void* src, uint32_t bytes) {
    asm volatile("cp.async.bulk.prefetch.L2.global [%0], %1;" ::"l"(src), "r"(bytes) : "memory");
}
__device__ __forceinline__ void tma_2d(uint32_t dst, const CUtensorMap* tm, int c0, int c1, uint32_t bar) {
    asm volatile("cp.async.bulk.tensor.2d.shared::cluster.global.mbarrier::complete_tx::bytes [%0], [%1, {%3, %4}], [%2];"
                 ::"r"(dst), "l"(tm), "r"(bar), "r"(c0), "r"(c1) : "memory");
}
__device__ __forceinline__ void tma_store_2d(const CUtensorMap* tm, uint32_t src, int c0, int c1) {
    asm volatile("cp.async.bulk.tensor.2d.global.shared::cta.bulk_group [%0, {%2, %3}], [%1];" ::"l"(tm), "r"(src), "r"(c0), "r"(c1) : "memory");
    asm volatile("cp.async.bulk.commit_group;" ::: "memory");
}
__device__ __forceinline__ void fence_proxy_async_global() { asm volatile("fence.proxy.async.global;" ::: "memory"); }
__device__ __forceinline__ void fence_gpu() { asm volatile("fence.acq_rel.gpu;" ::: "memory"); }
__device__ __forceinline__ void bar_sync(int id, int n) { asm volatile("bar.sync %0, %1;" ::"r"(id), "r"(n) : "memory"); }
__device__ __forceinline__ void bar_arrive(int id, int n) { asm volatile("bar.arrive %0, %1;" ::"r"(id), "r"(n) : "memory"); }
__device__ __forceinline__ void st_flag(unsigned int* p, unsigned int v) {
    asm volatile("st.release.gpu.global.u32 [%0], %1;" ::"l"(p), "r"(v) : "memory");
}
__device__ __forceinline__ unsigned int ld_flag(const unsigned int* p) {
    unsigned int v;
    asm volatile("ld.relaxed.gpu.global.u32 %0, [%1];" : "=r"(v) : "l"(p) : "memory");
    return v;
}
__device__ __forceinline__ void wait_flag(const unsigned int* p, unsigned int tag) {
    int it = 0;
    while (ld_flag(p) != tag) {
        if (++it > SPIN_LIMIT) __trap();
        BACKOFF();
    }
}
__device__ __forceinline__ void st_pkt(uint4* p, uint4 v) {
    asm volatile("st.relaxed.gpu.global.v4.u32 [%0], {%1,%2,%3,%4};" ::"l"(p), "r"(v.x), "r"(v.y), "r"(v.z), "r"(v.w) : "memory");
}
__device__ __forceinline__ uint4 ld_pkt(const uint4* p) {
    uint4 v;
    asm volatile("ld.relaxed.gpu.global.v4.u32 {%0,%1,%2,%3}, [%4];" : "=r"(v.x), "=r"(v.y), "=r"(v.z), "=r"(v.w) : "l"(p) : "memory");
    return v;
}
template <int N, unsigned int MASK>
__device__ __forceinline__ void wait_pkts(const uint4* p, int stride, unsigned int tag, uint4 (&v)[N]) {
    int it = 0;
    while (true) {
        bool ok = true;
#pragma unroll
        for (int i = 0; i < N; i++) v[i] = ld_pkt(p + (size_t)i * stride);
#pragma unroll
        for (int i = 0; i < N; i++) ok = ok && ((v[i].w & MASK) == tag);
        if (ok) break;
        if (++it > SPIN_LIMIT) __trap();
        BACKOFF();
    }
}
__device__ __forceinline__ uint4 embed_tag(float a, float b, float c, float d, unsigned int tag) {
    return make_uint4((__float_as_uint(a) & ~15u) | (tag & 15u), (__float_as_uint(b) & ~15u) | ((tag >> 4) & 15u),
                      (__float_as_uint(c) & ~15u) | ((tag >> 8) & 15u), (__float_as_uint(d) & ~15u) | ((tag >> 12) & 15u));
}
template <int N>
__device__ __forceinline__ void wait_pkts4(const uint4* p, int stride, unsigned int tag, uint4 (&v)[N]) {
    const unsigned int t16 = tag & 0xffffu;
    int it = 0;
    while (true) {
        bool ok = true;
#pragma unroll
        for (int i = 0; i < N; i++) v[i] = ld_pkt(p + (size_t)i * stride);
#pragma unroll
        for (int i = 0; i < N; i++)
            ok = ok && (((v[i].x & 15u) | ((v[i].y & 15u) << 4) | ((v[i].z & 15u) << 8) | ((v[i].w & 15u) << 12)) == t16);
        if (ok) break;
        if (++it > SPIN_LIMIT) __trap();
        BACKOFF();
    }
}
__device__ __forceinline__ uint64_t make_desc(uint32_t addr, uint32_t lbo, uint32_t sbo, uint32_t mode) {
    return (uint64_t)((addr & 0x3FFFF) >> 4) | ((uint64_t)((lbo & 0x3FFFF) >> 4) << 16) |
           ((uint64_t)((sbo & 0x3FFFF) >> 4) << 32) | ((uint64_t)mode << 62);
}
__device__ __forceinline__ void wg_fence() { asm volatile("wgmma.fence.sync.aligned;" ::: "memory"); }
__device__ __forceinline__ void wg_commit() { asm volatile("wgmma.commit_group.sync.aligned;" ::: "memory"); }
template <int N> __device__ __forceinline__ void wg_wait() { asm volatile("wgmma.wait_group.sync.aligned %0;" ::"n"(N) : "memory"); }
template <int N> __device__ __forceinline__ void pin(uint32_t (&d)[N]) {
#pragma unroll
    for (int i = 0; i < N; i++) asm volatile("" : "+r"(d[i])::"memory");
}
template <int N> __device__ __forceinline__ void pin(float (&d)[N]) {
#pragma unroll
    for (int i = 0; i < N; i++) asm volatile("" : "+f"(d[i])::"memory");
}
__device__ __forceinline__ uint32_t pack_bf16(float lo, float hi) {
    uint32_t r;
    asm("cvt.rn.bf16x2.f32 %0, %1, %2;" : "=r"(r) : "f"(hi), "f"(lo));
    return r;
}
__device__ __forceinline__ float bf_lo(uint32_t v) { return __uint_as_float(v << 16); }
__device__ __forceinline__ float bf_hi(uint32_t v) { return __uint_as_float(v & 0xFFFF0000u); }
__device__ __forceinline__ float bf_round(float v) { return __bfloat162float(__float2bfloat16(v)); }
__device__ __forceinline__ float ex2_mufu(float x) {
    float y;
    asm("ex2.approx.ftz.f32 %0, %1;" : "=f"(y) : "f"(x));
    return y;
}

#define ACC8(d, o) "+f"(d[o + 0]), "+f"(d[o + 1]), "+f"(d[o + 2]), "+f"(d[o + 3]), "+f"(d[o + 4]), "+f"(d[o + 5]), "+f"(d[o + 6]), "+f"(d[o + 7])
#define OUT8(d, o) "=f"(d[o + 0]), "=f"(d[o + 1]), "=f"(d[o + 2]), "=f"(d[o + 3]), "=f"(d[o + 4]), "=f"(d[o + 5]), "=f"(d[o + 6]), "=f"(d[o + 7])

__device__ __forceinline__ void wgmma_n192(float (&d)[96], uint64_t da, uint64_t db) {
    asm volatile(
        "wgmma.mma_async.sync.aligned.m64n192k16.f32.bf16.bf16 "
        "{%0,%1,%2,%3,%4,%5,%6,%7,%8,%9,%10,%11,%12,%13,%14,%15,%16,%17,%18,%19,%20,%21,%22,%23,%24,%25,%26,%27,%28,%29,%30,%31,"
        "%32,%33,%34,%35,%36,%37,%38,%39,%40,%41,%42,%43,%44,%45,%46,%47,%48,%49,%50,%51,%52,%53,%54,%55,%56,%57,%58,%59,%60,%61,%62,%63,"
        "%64,%65,%66,%67,%68,%69,%70,%71,%72,%73,%74,%75,%76,%77,%78,%79,%80,%81,%82,%83,%84,%85,%86,%87,%88,%89,%90,%91,%92,%93,%94,%95},"
        "%96, %97, 1, 1, 1, 0, 1;"
        : ACC8(d, 0), ACC8(d, 8), ACC8(d, 16), ACC8(d, 24), ACC8(d, 32), ACC8(d, 40), ACC8(d, 48), ACC8(d, 56),
          ACC8(d, 64), ACC8(d, 72), ACC8(d, 80), ACC8(d, 88)
        : "l"(da), "l"(db));
}
__device__ __forceinline__ void wgmma_n192_rs(float (&d)[96], const uint32_t* a, uint64_t db) {
    asm volatile(
        "wgmma.mma_async.sync.aligned.m64n192k16.f32.bf16.bf16 "
        "{%0,%1,%2,%3,%4,%5,%6,%7,%8,%9,%10,%11,%12,%13,%14,%15,%16,%17,%18,%19,%20,%21,%22,%23,%24,%25,%26,%27,%28,%29,%30,%31,"
        "%32,%33,%34,%35,%36,%37,%38,%39,%40,%41,%42,%43,%44,%45,%46,%47,%48,%49,%50,%51,%52,%53,%54,%55,%56,%57,%58,%59,%60,%61,%62,%63,"
        "%64,%65,%66,%67,%68,%69,%70,%71,%72,%73,%74,%75,%76,%77,%78,%79,%80,%81,%82,%83,%84,%85,%86,%87,%88,%89,%90,%91,%92,%93,%94,%95},"
        "{%96,%97,%98,%99}, %100, 1, 1, 1, 1;"
        : ACC8(d, 0), ACC8(d, 8), ACC8(d, 16), ACC8(d, 24), ACC8(d, 32), ACC8(d, 40), ACC8(d, 48), ACC8(d, 56),
          ACC8(d, 64), ACC8(d, 72), ACC8(d, 80), ACC8(d, 88)
        : "r"(a[0]), "r"(a[1]), "r"(a[2]), "r"(a[3]), "l"(db));
}
__device__ __forceinline__ void ldsm_x4(uint32_t* r, uint32_t addr) {
    asm volatile("ldmatrix.sync.aligned.m8n8.x4.shared.b16 {%0,%1,%2,%3}, [%4];"
                 : "=r"(r[0]), "=r"(r[1]), "=r"(r[2]), "=r"(r[3]) : "r"(addr) : "memory");
}
__device__ __forceinline__ void wgmma_n64(float (&d)[32], uint64_t da, uint64_t db) {
    asm volatile(
        "wgmma.mma_async.sync.aligned.m64n64k16.f32.bf16.bf16 "
        "{%0,%1,%2,%3,%4,%5,%6,%7,%8,%9,%10,%11,%12,%13,%14,%15,%16,%17,%18,%19,%20,%21,%22,%23,%24,%25,%26,%27,%28,%29,%30,%31},"
        "%32, %33, 1, 1, 1, 0, 1;"
        : ACC8(d, 0), ACC8(d, 8), ACC8(d, 16), ACC8(d, 24)
        : "l"(da), "l"(db));
}
__device__ __forceinline__ void wgmma_qk128(float (&d)[64], const uint32_t (&a)[4], uint64_t db) {
    asm volatile("wgmma.mma_async.sync.aligned.m64n128k16.f32.f16.f16 "
        "{%0,%1,%2,%3,%4,%5,%6,%7,%8,%9,%10,%11,%12,%13,%14,%15,%16,%17,%18,%19,%20,%21,%22,%23,%24,%25,%26,%27,%28,%29,%30,%31,%32,%33,%34,%35,%36,%37,%38,%39,%40,%41,%42,%43,%44,%45,%46,%47,%48,%49,%50,%51,%52,%53,%54,%55,%56,%57,%58,%59,%60,%61,%62,%63}, {%64,%65,%66,%67}, %68, 0, 1, 1, 0;"
        : "=f"(d[0]), "=f"(d[1]), "=f"(d[2]), "=f"(d[3]), "=f"(d[4]), "=f"(d[5]), "=f"(d[6]), "=f"(d[7]), "=f"(d[8]), "=f"(d[9]), "=f"(d[10]), "=f"(d[11]), "=f"(d[12]), "=f"(d[13]), "=f"(d[14]), "=f"(d[15]), "=f"(d[16]), "=f"(d[17]), "=f"(d[18]), "=f"(d[19]), "=f"(d[20]), "=f"(d[21]), "=f"(d[22]), "=f"(d[23]), "=f"(d[24]), "=f"(d[25]), "=f"(d[26]), "=f"(d[27]), "=f"(d[28]), "=f"(d[29]), "=f"(d[30]), "=f"(d[31]), "=f"(d[32]), "=f"(d[33]), "=f"(d[34]), "=f"(d[35]), "=f"(d[36]), "=f"(d[37]), "=f"(d[38]), "=f"(d[39]), "=f"(d[40]), "=f"(d[41]), "=f"(d[42]), "=f"(d[43]), "=f"(d[44]), "=f"(d[45]), "=f"(d[46]), "=f"(d[47]), "=f"(d[48]), "=f"(d[49]), "=f"(d[50]), "=f"(d[51]), "=f"(d[52]), "=f"(d[53]), "=f"(d[54]), "=f"(d[55]), "=f"(d[56]), "=f"(d[57]), "=f"(d[58]), "=f"(d[59]), "=f"(d[60]), "=f"(d[61]), "=f"(d[62]), "=f"(d[63])
        : "r"(a[0]), "r"(a[1]), "r"(a[2]), "r"(a[3]), "l"(db));
}
__device__ __forceinline__ void wgmma_qk_f32(float (&d)[32], const uint32_t (&a)[4], uint64_t db) {
    asm volatile("wgmma.mma_async.sync.aligned.m64n64k16.f32.f16.f16 "
        "{%0,%1,%2,%3,%4,%5,%6,%7,%8,%9,%10,%11,%12,%13,%14,%15,%16,%17,%18,%19,%20,%21,%22,%23,%24,%25,%26,%27,%28,%29,%30,%31}, {%32,%33,%34,%35}, %36, 0, 1, 1, 0;"
        : "=f"(d[0]), "=f"(d[1]), "=f"(d[2]), "=f"(d[3]), "=f"(d[4]), "=f"(d[5]), "=f"(d[6]), "=f"(d[7]), "=f"(d[8]), "=f"(d[9]), "=f"(d[10]), "=f"(d[11]), "=f"(d[12]), "=f"(d[13]), "=f"(d[14]), "=f"(d[15]), "=f"(d[16]), "=f"(d[17]), "=f"(d[18]), "=f"(d[19]), "=f"(d[20]), "=f"(d[21]), "=f"(d[22]), "=f"(d[23]), "=f"(d[24]), "=f"(d[25]), "=f"(d[26]), "=f"(d[27]), "=f"(d[28]), "=f"(d[29]), "=f"(d[30]), "=f"(d[31])
        : "r"(a[0]), "r"(a[1]), "r"(a[2]), "r"(a[3]), "l"(db));
}
__device__ __forceinline__ void wgmma_qk_f32(float (&d)[36], const uint32_t (&a)[4], uint64_t db) {
    asm volatile("wgmma.mma_async.sync.aligned.m64n72k16.f32.f16.f16 "
        "{%0,%1,%2,%3,%4,%5,%6,%7,%8,%9,%10,%11,%12,%13,%14,%15,%16,%17,%18,%19,%20,%21,%22,%23,%24,%25,%26,%27,%28,%29,%30,%31,%32,%33,%34,%35}, {%36,%37,%38,%39}, %40, 0, 1, 1, 0;"
        : "=f"(d[0]), "=f"(d[1]), "=f"(d[2]), "=f"(d[3]), "=f"(d[4]), "=f"(d[5]), "=f"(d[6]), "=f"(d[7]), "=f"(d[8]), "=f"(d[9]), "=f"(d[10]), "=f"(d[11]), "=f"(d[12]), "=f"(d[13]), "=f"(d[14]), "=f"(d[15]), "=f"(d[16]), "=f"(d[17]), "=f"(d[18]), "=f"(d[19]), "=f"(d[20]), "=f"(d[21]), "=f"(d[22]), "=f"(d[23]), "=f"(d[24]), "=f"(d[25]), "=f"(d[26]), "=f"(d[27]), "=f"(d[28]), "=f"(d[29]), "=f"(d[30]), "=f"(d[31]), "=f"(d[32]), "=f"(d[33]), "=f"(d[34]), "=f"(d[35])
        : "r"(a[0]), "r"(a[1]), "r"(a[2]), "r"(a[3]), "l"(db));
}
__device__ __forceinline__ void wgmma_qk_f32(float (&d)[40], const uint32_t (&a)[4], uint64_t db) {
    asm volatile("wgmma.mma_async.sync.aligned.m64n80k16.f32.f16.f16 "
        "{%0,%1,%2,%3,%4,%5,%6,%7,%8,%9,%10,%11,%12,%13,%14,%15,%16,%17,%18,%19,%20,%21,%22,%23,%24,%25,%26,%27,%28,%29,%30,%31,%32,%33,%34,%35,%36,%37,%38,%39}, {%40,%41,%42,%43}, %44, 0, 1, 1, 0;"
        : "=f"(d[0]), "=f"(d[1]), "=f"(d[2]), "=f"(d[3]), "=f"(d[4]), "=f"(d[5]), "=f"(d[6]), "=f"(d[7]), "=f"(d[8]), "=f"(d[9]), "=f"(d[10]), "=f"(d[11]), "=f"(d[12]), "=f"(d[13]), "=f"(d[14]), "=f"(d[15]), "=f"(d[16]), "=f"(d[17]), "=f"(d[18]), "=f"(d[19]), "=f"(d[20]), "=f"(d[21]), "=f"(d[22]), "=f"(d[23]), "=f"(d[24]), "=f"(d[25]), "=f"(d[26]), "=f"(d[27]), "=f"(d[28]), "=f"(d[29]), "=f"(d[30]), "=f"(d[31]), "=f"(d[32]), "=f"(d[33]), "=f"(d[34]), "=f"(d[35]), "=f"(d[36]), "=f"(d[37]), "=f"(d[38]), "=f"(d[39])
        : "r"(a[0]), "r"(a[1]), "r"(a[2]), "r"(a[3]), "l"(db));
}
__device__ __forceinline__ void wgmma_qk_f16(uint32_t (&d)[16], const uint32_t (&a)[4], uint64_t db) {
    asm volatile("wgmma.mma_async.sync.aligned.m64n64k16.f16.f16.f16 "
        "{%0,%1,%2,%3,%4,%5,%6,%7,%8,%9,%10,%11,%12,%13,%14,%15}, {%16,%17,%18,%19}, %20, 0, 1, 1, 0;"
        : "=r"(d[0]), "=r"(d[1]), "=r"(d[2]), "=r"(d[3]), "=r"(d[4]), "=r"(d[5]), "=r"(d[6]), "=r"(d[7]), "=r"(d[8]), "=r"(d[9]), "=r"(d[10]), "=r"(d[11]), "=r"(d[12]), "=r"(d[13]), "=r"(d[14]), "=r"(d[15])
        : "r"(a[0]), "r"(a[1]), "r"(a[2]), "r"(a[3]), "l"(db));
}
__device__ __forceinline__ void wgmma_qk_f16(uint32_t (&d)[14], const uint32_t (&a)[4], uint64_t db) {
    asm volatile("wgmma.mma_async.sync.aligned.m64n56k16.f16.f16.f16 "
        "{%0,%1,%2,%3,%4,%5,%6,%7,%8,%9,%10,%11,%12,%13}, {%14,%15,%16,%17}, %18, 0, 1, 1, 0;"
        : "=r"(d[0]), "=r"(d[1]), "=r"(d[2]), "=r"(d[3]), "=r"(d[4]), "=r"(d[5]), "=r"(d[6]), "=r"(d[7]), "=r"(d[8]), "=r"(d[9]), "=r"(d[10]), "=r"(d[11]), "=r"(d[12]), "=r"(d[13])
        : "r"(a[0]), "r"(a[1]), "r"(a[2]), "r"(a[3]), "l"(db));
}
__device__ __forceinline__ void wgmma_qk_f16(uint32_t (&d)[12], const uint32_t (&a)[4], uint64_t db) {
    asm volatile("wgmma.mma_async.sync.aligned.m64n48k16.f16.f16.f16 "
        "{%0,%1,%2,%3,%4,%5,%6,%7,%8,%9,%10,%11}, {%12,%13,%14,%15}, %16, 0, 1, 1, 0;"
        : "=r"(d[0]), "=r"(d[1]), "=r"(d[2]), "=r"(d[3]), "=r"(d[4]), "=r"(d[5]), "=r"(d[6]), "=r"(d[7]), "=r"(d[8]), "=r"(d[9]), "=r"(d[10]), "=r"(d[11])
        : "r"(a[0]), "r"(a[1]), "r"(a[2]), "r"(a[3]), "l"(db));
}
__device__ __forceinline__ void wgmma_qk_f32(float (&d)[28], const uint32_t (&a)[4], uint64_t db) {
    asm volatile("wgmma.mma_async.sync.aligned.m64n56k16.f32.f16.f16 "
        "{%0,%1,%2,%3,%4,%5,%6,%7,%8,%9,%10,%11,%12,%13,%14,%15,%16,%17,%18,%19,%20,%21,%22,%23,%24,%25,%26,%27}, {%28,%29,%30,%31}, %32, 0, 1, 1, 0;"
        : "=f"(d[0]), "=f"(d[1]), "=f"(d[2]), "=f"(d[3]), "=f"(d[4]), "=f"(d[5]), "=f"(d[6]), "=f"(d[7]), "=f"(d[8]), "=f"(d[9]), "=f"(d[10]), "=f"(d[11]), "=f"(d[12]), "=f"(d[13]), "=f"(d[14]), "=f"(d[15]), "=f"(d[16]), "=f"(d[17]), "=f"(d[18]), "=f"(d[19]), "=f"(d[20]), "=f"(d[21]), "=f"(d[22]), "=f"(d[23]), "=f"(d[24]), "=f"(d[25]), "=f"(d[26]), "=f"(d[27])
        : "r"(a[0]), "r"(a[1]), "r"(a[2]), "r"(a[3]), "l"(db));
}
__device__ __forceinline__ void wgmma_qk_f32(float (&d)[24], const uint32_t (&a)[4], uint64_t db) {
    asm volatile("wgmma.mma_async.sync.aligned.m64n48k16.f32.f16.f16 "
        "{%0,%1,%2,%3,%4,%5,%6,%7,%8,%9,%10,%11,%12,%13,%14,%15,%16,%17,%18,%19,%20,%21,%22,%23}, {%24,%25,%26,%27}, %28, 0, 1, 1, 0;"
        : "=f"(d[0]), "=f"(d[1]), "=f"(d[2]), "=f"(d[3]), "=f"(d[4]), "=f"(d[5]), "=f"(d[6]), "=f"(d[7]), "=f"(d[8]), "=f"(d[9]), "=f"(d[10]), "=f"(d[11]), "=f"(d[12]), "=f"(d[13]), "=f"(d[14]), "=f"(d[15]), "=f"(d[16]), "=f"(d[17]), "=f"(d[18]), "=f"(d[19]), "=f"(d[20]), "=f"(d[21]), "=f"(d[22]), "=f"(d[23])
        : "r"(a[0]), "r"(a[1]), "r"(a[2]), "r"(a[3]), "l"(db));
}
__device__ __forceinline__ void wgmma_qk_f16(uint32_t (&d)[18], const uint32_t (&a)[4], uint64_t db) {
    asm volatile("wgmma.mma_async.sync.aligned.m64n72k16.f16.f16.f16 "
        "{%0,%1,%2,%3,%4,%5,%6,%7,%8,%9,%10,%11,%12,%13,%14,%15,%16,%17}, {%18,%19,%20,%21}, %22, 0, 1, 1, 0;"
        : "=r"(d[0]), "=r"(d[1]), "=r"(d[2]), "=r"(d[3]), "=r"(d[4]), "=r"(d[5]), "=r"(d[6]), "=r"(d[7]), "=r"(d[8]), "=r"(d[9]), "=r"(d[10]), "=r"(d[11]), "=r"(d[12]), "=r"(d[13]), "=r"(d[14]), "=r"(d[15]), "=r"(d[16]), "=r"(d[17])
        : "r"(a[0]), "r"(a[1]), "r"(a[2]), "r"(a[3]), "l"(db));
}
__device__ __forceinline__ void wgmma_qk_f16(uint32_t (&d)[20], const uint32_t (&a)[4], uint64_t db) {
    asm volatile("wgmma.mma_async.sync.aligned.m64n80k16.f16.f16.f16 "
        "{%0,%1,%2,%3,%4,%5,%6,%7,%8,%9,%10,%11,%12,%13,%14,%15,%16,%17,%18,%19}, {%20,%21,%22,%23}, %24, 0, 1, 1, 0;"
        : "=r"(d[0]), "=r"(d[1]), "=r"(d[2]), "=r"(d[3]), "=r"(d[4]), "=r"(d[5]), "=r"(d[6]), "=r"(d[7]), "=r"(d[8]), "=r"(d[9]), "=r"(d[10]), "=r"(d[11]), "=r"(d[12]), "=r"(d[13]), "=r"(d[14]), "=r"(d[15]), "=r"(d[16]), "=r"(d[17]), "=r"(d[18]), "=r"(d[19])
        : "r"(a[0]), "r"(a[1]), "r"(a[2]), "r"(a[3]), "l"(db));
}
__device__ __forceinline__ void wgmma_pv24_lh(float (&o)[12], uint32_t a0, uint32_t a1, uint32_t a2, uint32_t a3, uint32_t lo, uint32_t hi) {
    asm volatile(
        "{.reg .b64 d; mov.b64 d, {%16, %17};\n"
        "wgmma.mma_async.sync.aligned.m64n24k16.f32.bf16.bf16 "
        "{%0,%1,%2,%3,%4,%5,%6,%7,%8,%9,%10,%11}, {%12,%13,%14,%15}, d, 1, 1, 1, 1;}"
        : ACC8(o, 0), "+f"(o[8]), "+f"(o[9]), "+f"(o[10]), "+f"(o[11])
        : "r"(a0), "r"(a1), "r"(a2), "r"(a3), "r"(lo), "r"(hi));
}
__device__ __forceinline__ void wgmma_pv24(float (&o)[12], uint32_t a0, uint32_t a1, uint32_t a2, uint32_t a3, uint64_t desc) {
    asm volatile(
        "wgmma.mma_async.sync.aligned.m64n24k16.f32.bf16.bf16 "
        "{%0,%1,%2,%3,%4,%5,%6,%7,%8,%9,%10,%11}, {%12,%13,%14,%15}, %16, 1, 1, 1, 1;"
        : ACC8(o, 0), "+f"(o[8]), "+f"(o[9]), "+f"(o[10]), "+f"(o[11])
        : "r"(a0), "r"(a1), "r"(a2), "r"(a3), "l"(desc));
}

__device__ __forceinline__ uint32_t ex2_pair_h16(uint32_t x2) {
    uint32_t t, r, f, q;
    asm("add.rn.f16x2 %0, %1, %2;" : "=r"(t) : "r"(x2), "r"(0x661E661Fu));
    asm("sub.rn.f16x2 %0, %1, %2;" : "=r"(r) : "r"(t), "r"(0x661E661Fu));
    asm("sub.rn.f16x2 %0, %1, %2;" : "=r"(f) : "r"(x2), "r"(r));
    asm("fma.rn.f16x2 %0, %1, %2, %3;" : "=r"(q) : "r"(0x15101510u), "r"(f), "r"(0x1d7e1d7eu));
    asm("fma.rn.f16x2 %0, %1, %2, %3;" : "=r"(q) : "r"(q), "r"(f), "r"(0x23d823d8u));
    asm("fma.rn.f16x2 %0, %1, %2, %3;" : "=r"(q) : "r"(q), "r"(f), "r"(0x30823035u));
    return t * 128u + q;
}
#define NMG 8
constexpr int NPG = 16 - NMG;
__host__ __device__ constexpr bool is_poly_group(int L) { return NPG <= 8 ? ((L & 1) && L < 2 * NPG) : ((L & 1) || L >= 2 * NMG); }
__host__ __device__ constexpr int g_idx(int L) {
    return NPG <= 8 ? ((L & 1) == 0 ? L / 2 : (L < 2 * NPG ? L / 2 : 8 + (L - 2 * NPG) / 2))
                    : ((L & 1) ? L / 2 : (L < 2 * NMG ? L / 2 : 8 + (L - 2 * NMG) / 2));
}
__host__ __device__ constexpr int k_pos(int L) { return is_poly_group(L) ? NMG + g_idx(L) : g_idx(L); }
constexpr float VSCALE_ODD = 0.70703125f;
constexpr float LOG2C_ODD = 0.50015402f;
__device__ __forceinline__ uint32_t pack_f16_sat(float lo, float hi) {
    uint32_t r;
    asm("cvt.rn.satfinite.f16x2.f32 %0, %1, %2;" : "=r"(r) : "f"(hi), "f"(lo));
    return r;
}
__device__ __forceinline__ unsigned int f2ord(float v) {
    const unsigned int u = __float_as_uint(v);
    const unsigned int o = u ^ ((unsigned int)((int)u >> 31) | 0x80000000u);
    return (v == v) ? o : 0u;
}
__device__ __forceinline__ void warp_top2(unsigned int ka, unsigned int ia, unsigned int kb, unsigned int ib, unsigned int& i1, unsigned int& i2) {
    const unsigned int m1 = __reduce_max_sync(0xffffffffu, max(ka, kb));
    i1 = __reduce_min_sync(0xffffffffu, min(ka == m1 ? ia : 0xffffffffu, kb == m1 ? ib : 0xffffffffu));
    const bool ra = (ia == i1), rb = (ib == i1);
    const unsigned int ka2 = ra ? 0u : ka, kb2 = rb ? 0u : kb, ia2 = ra ? 0xffffffffu : ia, ib2 = rb ? 0xffffffffu : ib;
    const unsigned int m2 = __reduce_max_sync(0xffffffffu, max(ka2, kb2));
    i2 = __reduce_min_sync(0xffffffffu, min(ka2 == m2 ? ia2 : 0xffffffffu, kb2 == m2 ? ib2 : 0xffffffffu));
}

constexpr int P1_STAGES = 5;
constexpr int P1_STAGE_BYTES = 16384 + 24576;
constexpr int KV_CHUNK = 10240;
constexpr int SM_Q = 163840 + 49152;
constexpr int SM_A3 = 163840;
constexpr int SM_MISC = 229376;
constexpr int SMEM_TOTAL = 232448;
struct Misc {
    uint64_t p1_full[P1_STAGES], p1_empty[P1_STAGES];
    uint64_t kv[16];
    uint64_t wo[8], a3[8], moe;
    unsigned int tag;
    int fast;
    int idx[2], cslot[2];
    alignas(16) float sel[8];
    unsigned int norm[12];
    uint64_t qbar;
    int item, nxt[4];
    unsigned int seq[8];
    unsigned int freed[16];
    union alignas(16) {
        struct { float mu[128], rs[128], cs[192]; } p1;
        struct { float part[2][64][3]; float mu[64], rs[64], r[64]; } p3;
    };
};
static_assert(sizeof(Misc) <= SMEM_TOTAL - SM_MISC, "misc smem");

__device__ __forceinline__ void release_kv_chunk(Misc& ms, int j, int lane) {
    asm volatile("{.reg .pred p; setp.eq.s32 p, %1, 0; @p red.relaxed.cta.shared.add.u32 [%0], 1;}" ::"r"(smem_u32(&ms.freed[j])), "r"(lane) : "memory");
}
__device__ __forceinline__ bool refill_kv_chunk(char* smem, Misc& ms, int j, int cta, int lane, const CUtensorMap* tmWo,
                                                const CUtensorMap* tmG, const CUtensorMap* tmU) {
    unsigned int cnt;
    asm volatile("ld.relaxed.cta.shared.u32 %0, [%1];" : "=r"(cnt) : "r"(smem_u32(&ms.freed[j])) : "memory");
    if (cnt < 16u) return false;
    if (lane == 0) {
        const uint32_t dst = smem_u32(smem + j * KV_CHUNK);
        const uint32_t wb = smem_u32(&ms.wo[j >> 1]);
        mbar_expect_tx(wb, 8192);
        tma_2d(dst, tmWo, (cta & 3) * 128 + (j & 1) * 64, (j >> 1) * 64, wb);
        const uint32_t mb = smem_u32(&ms.moe);
        if (cta < NFFN) {
            mbar_expect_tx(mb, 2048);
            tma_2d(dst + 8192, (j & 8) ? tmU : tmG, cta * 16, (j & 7) * 64, mb);
        }
    }
    __syncwarp();
    return true;
}

template <typename LoadFn>
__device__ __forceinline__ void guarded_item(char* smem, Misc& ms, int r, int t, int warp, LoadFn load_chunk) {
    const int tid = threadIdx.x, lane = tid & 31, w4 = (tid >> 5) & 3;
    const uint64_t descK0 = make_desc(smem_u32(smem), 128, 256, 0);
    const uint64_t descV0 = make_desc(smem_u32(smem + 4096), 128, 2048, 0);
    uint32_t q[4];
    {
        const uint32_t* Qs = reinterpret_cast<const uint32_t*>(smem + SM_Q + t * 2048 + w4 * 512);
        q[0] = Qs[lane]; q[2] = Qs[32 + lane]; q[1] = Qs[64 + lane]; q[3] = Qs[96 + lane];
    }
    float* st = reinterpret_cast<float*>(smem + SM_A3) + t * (12 * 128) + (tid & 127);
    float o[12];
#pragma unroll
    for (int i = 0; i < 8; i++) o[i] = r > 0 ? st[i * 128] : 0.f;
    o[8] = r > 0 ? st[8 * 128] : 0.f; o[10] = r > 0 ? st[9 * 128] : 0.f; o[9] = 0.f; o[11] = 0.f;
    float m0 = r > 0 ? st[10 * 128] : -INFINITY, m1 = r > 0 ? st[11 * 128] : -INFINITY;
#pragma unroll 1
    for (int j = CPI * r; j < CPI * (r + 1); j++) {
        if (t < 4 && warp == j + 5 && lane == 0) load_chunk(warp);
        __syncwarp();
        mbar_wait(smem_u32(&ms.kv[j]), 0);
        float s[64];
        const uint32_t off = j * (KV_CHUNK >> 4);
        wg_fence();
        wgmma_qk128(s, q, descK0 + (uint64_t)off);
        wg_commit();
        wg_wait<0>();
        pin(s);
        pin(o);
        if (t >= 4 && j > 0) release_kv_chunk(ms, j - 1, lane);
        float n0 = m0, n1 = m1;
#pragma unroll
        for (int i = 0; i < 16; i++) {
            n0 = fmaxf(n0, fmaxf(s[4 * i], s[4 * i + 1]));
            n1 = fmaxf(n1, fmaxf(s[4 * i + 2], s[4 * i + 3]));
        }
        n0 = fmaxf(n0, __shfl_xor_sync(0xffffffffu, n0, 1)); n0 = fmaxf(n0, __shfl_xor_sync(0xffffffffu, n0, 2));
        n1 = fmaxf(n1, __shfl_xor_sync(0xffffffffu, n1, 1)); n1 = fmaxf(n1, __shfl_xor_sync(0xffffffffu, n1, 2));
        const float a0 = ex2_mufu(m0 - n0), a1 = ex2_mufu(m1 - n1);
        m0 = n0; m1 = n1;
#pragma unroll
        for (int i = 0; i < 3; i++) { o[4 * i] *= a0; o[4 * i + 1] *= a0; o[4 * i + 2] *= a1; o[4 * i + 3] *= a1; }
        const float e0 = n0 - LOG2C_ODD, e1 = n1 - LOG2C_ODD;
#pragma unroll
        for (int k = 0; k < 8; k++) {
            const int ba = 4 * k_pos(2 * k), bb = 4 * k_pos(2 * k + 1);
            const float f0 = is_poly_group(2 * k + 1) ? e0 : n0, f1 = is_poly_group(2 * k + 1) ? e1 : n1;
            const float g0 = is_poly_group(2 * k) ? e0 : n0, g1 = is_poly_group(2 * k) ? e1 : n1;
            const uint32_t p0 = pack_bf16(ex2_mufu(s[ba] - g0), ex2_mufu(s[ba + 1] - g0));
            const uint32_t p1 = pack_bf16(ex2_mufu(s[ba + 2] - g1), ex2_mufu(s[ba + 3] - g1));
            const uint32_t p2 = pack_bf16(ex2_mufu(s[bb] - f0), ex2_mufu(s[bb + 1] - f0));
            const uint32_t p3 = pack_bf16(ex2_mufu(s[bb + 2] - f1), ex2_mufu(s[bb + 3] - f1));
            wg_fence();
            wgmma_pv24(o, p0, p1, p2, p3, descV0 + (uint64_t)(off + k * 16));
            wg_commit();
            wg_wait<0>();
            pin(o);
        }
    }
#pragma unroll
    for (int i = 0; i < 8; i++) st[i * 128] = o[i];
    st[8 * 128] = o[8]; st[9 * 128] = o[10]; st[10 * 128] = m0; st[11 * 128] = m1;
}

__global__ void __launch_bounds__(512, 1)
mega_kernel(const __grid_constant__ CUtensorMap tmX, const __grid_constant__ CUtensorMap tmW,
            const __grid_constant__ CUtensorMap tmO, const __grid_constant__ CUtensorMap tmWo,
            const __grid_constant__ CUtensorMap tmG, const __grid_constant__ CUtensorMap tmU, const __grid_constant__ CUtensorMap tmOut,
            const __nv_bfloat16* __restrict__ x, const __nv_bfloat16* __restrict__ wqkv, const __nv_bfloat16* __restrict__ wo,
            const __nv_bfloat16* __restrict__ w_r, const __nv_bfloat16* __restrict__ w_gate,
            const __nv_bfloat16* __restrict__ w_up, const __nv_bfloat16* __restrict__ w_down,
            __nv_bfloat16* __restrict__ out) {
    extern __shared__ __align__(1024) char smem[];
    Misc& ms = *reinterpret_cast<Misc*>(smem + SM_MISC);
    const int tid = threadIdx.x, lane = tid & 31;
    const int warp = __shfl_sync(0xffffffffu, tid >> 5, 0);
    const int wg = warp >> 2, w4 = warp & 3, g = lane >> 2, t4 = lane & 3;
    const int cta = blockIdx.x;
    const int rb = cta >> 3, hg = cta & 7;

    if (warp == 12) {
        if (lane == 0) {
            TS(0);
            if (smem_u32(smem) & 1023) __trap();
            for (int i = 0; i < P1_STAGES; i++) { mbar_init(smem_u32(&ms.p1_full[i]), 1); mbar_init(smem_u32(&ms.p1_empty[i]), 8); }
            asm volatile("fence.mbarrier_init.release.cluster;" ::: "memory");
        }
        __syncwarp();
        bar_arrive(13, 288);
        bar_arrive(14, 256);
    } else {
        if (tid == 32) {
            for (int i = 0; i < 16; i++) mbar_init(smem_u32(&ms.kv[i]), 1);
            for (int i = 0; i < 8; i++) { mbar_init(smem_u32(&ms.wo[i]), 2); mbar_init(smem_u32(&ms.a3[i]), 1); }
            mbar_init(smem_u32(&ms.moe), 16);
            for (int i = 0; i < 16; i++) ms.freed[i] = 0;
            for (int i = 0; i < 8; i++) ms.seq[i] = 0;
            ms.item = 4;
            mbar_init(smem_u32(&ms.qbar), 1);
            asm volatile("fence.mbarrier_init.release.cluster;" ::: "memory");
        }
        if (tid >= 64 && tid < 76) ms.norm[tid - 64] = 0;
        if (tid >= 96 && tid < 101) {
            const CUtensorMap* tm = tid == 96 ? &tmO : tid == 97 ? &tmWo : tid == 98 ? &tmG : tid == 99 ? &tmU : &tmOut;
            asm volatile("prefetch.tensormap [%0];" ::"l"(tm) : "memory");
        }
        if (tid == 416) ms.tag = __ldcg(&gEpoch) + 1u;
    }

    if (wg < 2) {
        asm volatile("setmaxnreg.inc.sync.aligned.u32 160;");
        float acc[96];
#pragma unroll
        for (int i = 0; i < 96; i++) acc[i] = 0.f;
        bar_sync(13, 288);
#pragma unroll
        for (int kc = 0; kc < 8; kc++) {
            const int s = kc % P1_STAGES;
            mbar_wait(smem_u32(&ms.p1_full[s]), (kc / P1_STAGES) & 1);
            if (tid == 0) TS(24 + kc);
            const uint32_t sa = smem_u32(smem + s * P1_STAGE_BYTES), sb = sa + 16384;
            const uint64_t da = make_desc(sa + wg * 8192, 16, 1024, 1);
            const uint64_t db = make_desc(sb, 8192, 1024, 1);
            wg_fence();
#pragma unroll
            for (int ks = 0; ks < 4; ks++) wgmma_n192(acc, da + ks * 2, db + ks * 128);
            wg_commit();
            wg_wait<1>();
            if (kc > 0 && lane == 0) mbar_arrive(smem_u32(&ms.p1_empty[(kc - 1) % P1_STAGES]));
        }
        wg_wait<0>();
        pin(acc);
        if (tid == 0) TS(1);
        bar_sync(1, 480);
        const unsigned int tag = ms.tag;
        if (tid == 0) TS(16);
        const int lr0 = wg * 64 + w4 * 16 + g, lr1 = lr0 + 8;
        const float mu0 = ms.p1.mu[lr0], mu1 = ms.p1.mu[lr1], rs0 = ms.p1.rs[lr0], rs1 = ms.p1.rs[lr1];
        const int lg0 = wg * 8 + w4 * 2;
        const int rg0 = rb * 16 + lg0;
        const float vsc = is_poly_group(lg0 + 1) ? VSCALE_ODD : 1.f, vsc0 = is_poly_group(lg0) ? VSCALE_ODD : 1.f;
        const int kp0 = k_pos(lg0) * 64, kp1 = k_pos(lg0 + 1) * 64;
#pragma unroll
        for (int hh = 0; hh < 4; hh++) {
            const int head = hg * 4 + hh;
            float nrm[3];
#pragma unroll
            for (int sec = 0; sec < 3; sec++) {
                float sq0 = 0.f, sq1 = 0.f, vm = 0.f;
#pragma unroll
                for (int db = 0; db < 2; db++) {
                    const int j = sec * 8 + hh * 2 + db;
                    const float2 c = *reinterpret_cast<const float2*>(&ms.p1.cs[j * 8 + 2 * t4]);
                    const float f0 = sec == 0 ? rs0 * QSCALE : rs0, f1 = sec == 0 ? rs1 * QSCALE : rs1;
                    const float a0 = (acc[4 * j + 0] - mu0 * c.x) * f0, a1 = (acc[4 * j + 1] - mu0 * c.y) * f0;
                    const float b0 = (acc[4 * j + 2] - mu1 * c.x) * f1, b1 = (acc[4 * j + 3] - mu1 * c.y) * f1;
                    const uint32_t pa = sec < 2 ? pack_f16_sat(a0, a1) : pack_bf16(a0 * vsc0, a1 * vsc0);
                    const uint32_t pb = sec < 2 ? pack_f16_sat(b0, b1) : pack_bf16(b0 * vsc, b1 * vsc);
                    if (sec < 2) {
                        if (sec == 0) {
                            uint32_t* dst = reinterpret_cast<uint32_t*>(gQ) + ((size_t)head * S_LEN * DH + rg0 * 128) / 2;
                            dst[db * 32 + lane] = pa;
                            dst[64 + db * 32 + lane] = pb;
                        } else {
                            uint32_t* dst = reinterpret_cast<uint32_t*>(gKV) + (size_t)(head * 16 + rb) * 2048;
                            dst[kp0 + db * 32 + lane] = pa;
                            dst[kp1 + db * 32 + lane] = pb;
                        }
                        sq0 = fmaf(a0, a0, fmaf(a1, a1, sq0));
                        sq1 = fmaf(b0, b0, fmaf(b1, b1, sq1));
                    } else {
                        uint32_t* dst = reinterpret_cast<uint32_t*>(gKV) + (size_t)(head * 16 + rb) * 2048 + 1024 + db * 512 + lg0 * 32;
                        dst[lane] = pa;
                        dst[32 + lane] = pb;
                        vm = fmaxf(vm, fmaxf(fmaxf(fabsf(a0), fabsf(a1)), fmaxf(fabsf(b0), fabsf(b1))));
                        if (!(a0 + a1 + b0 + b1 == a0 + a1 + b0 + b1)) vm = __int_as_float(0x7f800000);
                    }
                }
                if (sec < 2) {
                    sq0 += __shfl_xor_sync(0xffffffffu, sq0, 1); sq0 += __shfl_xor_sync(0xffffffffu, sq0, 2);
                    sq1 += __shfl_xor_sync(0xffffffffu, sq1, 1); sq1 += __shfl_xor_sync(0xffffffffu, sq1, 2);
                    vm = fmaxf(sq0, sq1);
                    if (!(sq0 + sq1 < 3.0e38f)) vm = __int_as_float(0x7f800000);
                }
                nrm[sec] = vm;
            }
            const unsigned int a = __reduce_max_sync(0xffffffffu, __float_as_uint(nrm[0]));
            const unsigned int b = __reduce_max_sync(0xffffffffu, __float_as_uint(nrm[1]));
            const unsigned int c = __reduce_max_sync(0xffffffffu, __float_as_uint(nrm[2]));
            if (lane == 0) { atomicMax(&ms.norm[hh * 3 + 0], a); atomicMax(&ms.norm[hh * 3 + 1], b); atomicMax(&ms.norm[hh * 3 + 2], c); }
        }
        if (tid == 0) TS(17);
        bar_sync(2, 256);
        if (tid == 0) TS(18);
        if (tid < 4) {
            fence_gpu();
            st_pkt(&gFlagQKV[(hg * 16 + rb) * 4 + tid], make_uint4(ms.norm[tid * 3], ms.norm[tid * 3 + 1], ms.norm[tid * 3 + 2], tag));
            if (tid == 0) TS(2);
        }
        asm volatile("setmaxnreg.dec.sync.aligned.u32 128;");
        bar_sync(15, 512);
    } else {
      asm volatile("setmaxnreg.dec.sync.aligned.u32 96;");
      if (wg == 2) {
        const int t = tid - 256;
        if (t < 4) gFlagQKV[(hg * 16 + rb) * 4 + t] = make_uint4(0u, 0u, 0u, 0u);
        bar_sync(14, 256);
        mbar_wait(smem_u32(&ms.p1_full[0]), 0);
        {
            const int row = rb * 128 + hg * 16 + (t >> 3), j = t & 7;
            const uint4* xp = reinterpret_cast<const uint4*>(x + (size_t)row * DM);
            uint4 v[8];
#pragma unroll
            for (int i = 0; i < 8; i++) v[i] = __ldg(xp + i * 8 + j);
            float s1 = 0.f;
#pragma unroll
            for (int i = 0; i < 8; i++) {
                const uint32_t w[4] = {v[i].x, v[i].y, v[i].z, v[i].w};
#pragma unroll
                for (int e = 0; e < 4; e++) s1 += bf_lo(w[e]) + bf_hi(w[e]);
            }
            s1 += __shfl_xor_sync(0xffffffffu, s1, 1); s1 += __shfl_xor_sync(0xffffffffu, s1, 2); s1 += __shfl_xor_sync(0xffffffffu, s1, 4);
            const float mu = s1 * (1.f / DM);
            float s2 = 0.f;
#pragma unroll
            for (int i = 0; i < 8; i++) {
                const uint32_t w[4] = {v[i].x, v[i].y, v[i].z, v[i].w};
#pragma unroll
                for (int e = 0; e < 4; e++) {
                    const float a = bf_lo(w[e]) - mu, b = bf_hi(w[e]) - mu;
                    s2 = fmaf(a, a, fmaf(b, b, s2));
                }
            }
            s2 += __shfl_xor_sync(0xffffffffu, s2, 1); s2 += __shfl_xor_sync(0xffffffffu, s2, 2); s2 += __shfl_xor_sync(0xffffffffu, s2, 4);
            bar_sync(11, 224);
            if (j == 0) st_pkt(&gStat1[row], make_uint4(__float_as_uint(mu), __float_as_uint(rsqrtf(s2 * (1.f / DM) + LN_EPS)), 0u, ms.tag));
        }
        const unsigned int tag = ms.tag;
        if (t == 0) TS(32);
        mbar_wait(smem_u32(&ms.p1_full[2]), 1);
        uint4 st[1];
        wait_pkts<1, 0xffffffffu>(&gStat1[rb * 128 + t], 0, tag, st);
        if (t == 0) TS(34);
        ms.p1.mu[t] = __uint_as_float(st[0].x);
        ms.p1.rs[t] = __uint_as_float(st[0].y);
        bar_arrive(1, 480);
        {
            const uint4 z = make_uint4(0u, 0u, 0u, 0u);
            if (t < 64) { gCand[cta * 64 + t] = z; gPart[cta * 64 + t] = z; gCandRow[cta * 64 + t] = z; }
            gYPart[cta * 224 + t] = z;
            if (t < 96) gYPart[cta * 224 + 128 + t] = z;
            if (t < 2) {
                reinterpret_cast<uint4*>(gFlagO)[cta * 2 + t] = z;
                reinterpret_cast<uint4*>(gFlagOut)[cta * 2 + t] = z;
            }
        }
      } else if (warp == 12) {
        if (lane == 0) {
#pragma unroll 1
            for (int kc = 0; kc < 8; kc++) {
                const int s = kc % P1_STAGES;
                if (kc >= P1_STAGES) mbar_wait(smem_u32(&ms.p1_empty[s]), 0);
                const uint32_t bar = smem_u32(&ms.p1_full[s]);
                const uint32_t sa = smem_u32(smem + s * P1_STAGE_BYTES), sb = sa + 16384;
                mbar_expect_tx(bar, P1_STAGE_BYTES);
                tma_2d(sa, &tmX, kc * 64, rb * 128, bar);
#pragma unroll
                for (int p = 0; p < 3; p++) tma_2d(sb + p * 8192, &tmW, p * 512 + hg * 64, kc * 64, bar);
            }
        }
      } else {
        const int t = tid - 416;
        bar_sync(14, 256);
        mbar_wait(smem_u32(&ms.p1_full[0]), 0);
        const int c16 = t >> 2, rs = t & 3;
        const __nv_bfloat16* wp = wqkv + (size_t)(rb * 32 + rs) * (3 * DM) + (c16 >> 3) * 512 + hg * 64 + (c16 & 7) * 8;
        uint4 v[8];
#pragma unroll
        for (int i = 0; i < 8; i++) v[i] = __ldg(reinterpret_cast<const uint4*>(wp + (size_t)i * 4 * (3 * DM)));
        float a[8] = {};
#pragma unroll
        for (int i = 0; i < 8; i++) {
            a[0] += bf_lo(v[i].x); a[1] += bf_hi(v[i].x); a[2] += bf_lo(v[i].y); a[3] += bf_hi(v[i].y);
            a[4] += bf_lo(v[i].z); a[5] += bf_hi(v[i].z); a[6] += bf_lo(v[i].w); a[7] += bf_hi(v[i].w);
        }
#pragma unroll
        for (int e = 0; e < 8; e++) { a[e] += __shfl_xor_sync(0xffffffffu, a[e], 1); a[e] += __shfl_xor_sync(0xffffffffu, a[e], 2); }
        bar_sync(11, 224);
        const unsigned int tag = ms.tag;
        const int pk = c16 * 2 + rs;
        if (rs < 2) st_pkt(&gCsPart[(hg * 16 + rb) * 48 + pk], embed_tag(rs ? a[4] : a[0], rs ? a[5] : a[1], rs ? a[6] : a[2], rs ? a[7] : a[3], tag));
        if (t == 0) TS(35);
        if (t < 16) { uint4 gate[1]; wait_pkts4<1>(&gCsPart[(hg * 16 + t) * 48 + 47], 0, tag, gate); }
        bar_sync(8, 96);
        if (t == 0) TS(36);
        {
            const int pq = c16 * 2 + (rs & 1);
            uint4 p[8];
            wait_pkts4<8>(&gCsPart[(hg * 16 + (rs >> 1) * 8) * 48 + pq], 48, tag, p);
            float s0 = 0.f, s1 = 0.f, s2 = 0.f, s3 = 0.f;
#pragma unroll
            for (int i = 0; i < 8; i++) {
                s0 += __uint_as_float(p[i].x); s1 += __uint_as_float(p[i].y); s2 += __uint_as_float(p[i].z); s3 += __uint_as_float(p[i].w);
            }
            s0 += __shfl_xor_sync(0xffffffffu, s0, 2); s1 += __shfl_xor_sync(0xffffffffu, s1, 2);
            s2 += __shfl_xor_sync(0xffffffffu, s2, 2); s3 += __shfl_xor_sync(0xffffffffu, s3, 2);
            if (rs < 2) *reinterpret_cast<float4*>(&ms.p1.cs[pq * 4]) = make_float4(s0, s1, s2, s3);
            if (t == 0) TS(37);
        }
        __syncwarp();
        bar_arrive(1, 480);
      }
      __syncwarp();
      bar_sync(15, 512);
      asm volatile("setmaxnreg.inc.sync.aligned.u32 128;");
    }
    if (tid == 0) TS(20);
    const unsigned int tag = ms.tag;

    const int head = hg * 4 + (rb >> 2), quarter = rb & 3;
    {
#pragma unroll
        for (int i = 0; i < 4; i++) {
            const int e = tid + i * 512;
            *reinterpret_cast<uint4*>(smem + (e >> 7) * KV_CHUNK + 8192 + (e & 127) * 16) = make_uint4(is_poly_group((e & 127) >> 3) ? 0x00003F35u : 0x00003F80u, 0, 0, 0);
        }
        asm volatile("fence.proxy.async.shared::cta;" ::: "memory");
    }
    if (warp == 0) {
        uint4 n[1];
        wait_pkts<1, 0xffffffffu>(&gFlagQKV[(hg * 16 + (lane & 15)) * 4 + (rb >> 2)], 0, tag, n);
        __syncwarp();
        if (lane == 0) TS(21);
        const float q2 = __uint_as_float(__reduce_max_sync(0xffffffffu, n[0].x));
        const float k2 = __uint_as_float(__reduce_max_sync(0xffffffffu, n[0].y));
        const float vm = __uint_as_float(__reduce_max_sync(0xffffffffu, n[0].z));
        if (lane == 0) ms.fast = (q2 * k2 * 1.02f <= 812.f) && (q2 <= 1.0e6f) && (k2 <= 1.0e6f) && (vm <= 1.0e18f) && (vm >= 1.0e-18f || vm == 0.f);
    }
    __syncthreads();
    auto load_kv_chunk = [&](int j) {
        fence_proxy_async_global();
        const uint32_t bar = smem_u32(&ms.kv[j]);
        mbar_expect_tx(bar, 8192);
        bulk_g2s(smem_u32(smem + j * KV_CHUNK), reinterpret_cast<const char*>(gKV) + (size_t)(head * 16 + j) * 8192, 8192, bar);
    };
    if (lane == 0) {
        if (warp == 5) {
            fence_proxy_async_global();
            mbar_expect_tx(smem_u32(&ms.qbar), 16384);
            bulk_g2s(smem_u32(smem + SM_Q), reinterpret_cast<const char*>(gQ) + (size_t)head * 65536 + quarter * 16384, 16384, smem_u32(&ms.qbar));
        }
        if (warp < 5) load_kv_chunk(warp);
    }
    __syncwarp();
    if (tid == 0) TS(3);
    bool refilled = false;
    {
        const bool fast = ms.fast != 0;
        const uint64_t descKe = make_desc(smem_u32(smem), 128, 256, 0);
        const uint64_t descKo = make_desc(smem_u32(smem) + NMG * 256, 128, 256, 0);
        const uint64_t descV0 = make_desc(smem_u32(smem + 4096), 128, 2048, 0);
        auto release_chunk = [&](int j) { release_kv_chunk(ms, j, lane); };
        float* sAcc = reinterpret_cast<float*>(smem + SM_A3);
        const int t128 = tid & 127;
        mbar_wait(smem_u32(&ms.qbar), 0);
        auto run_items = [&](auto FAST) {
        int item = wg * NR;
#pragma unroll 1
        while (item < 8 * NR) {
            const int r = item % NR, t = item / NR;
            if (t128 == 0) ms.nxt[wg] = ((item % NR) == NR - 1) ? item + 3 * NR + 1 : item + 1;
            if (r > 0) {
                int it = 0;
                unsigned int sq;
                while (true) {
                    asm volatile("ld.acquire.cta.shared.u32 %0, [%1];" : "=r"(sq) : "r"(smem_u32(&ms.seq[t])) : "memory");
                    if (sq >= (unsigned int)r) break;
                    if (++it > SPIN_LIMIT) __trap();
                }
            }
            uint32_t q[4];
            {
                const uint32_t* Qs = reinterpret_cast<const uint32_t*>(smem + SM_Q + t * 2048 + w4 * 512);
                q[0] = Qs[lane]; q[2] = Qs[32 + lane]; q[1] = Qs[64 + lane]; q[3] = Qs[96 + lane];
            }
            float* st = sAcc + t * (12 * 128) + t128;
            float o[12];
#pragma unroll
            for (int i = 0; i < 8; i++) o[i] = r > 0 ? st[i * 128] : 0.f;
            o[8] = r > 0 ? st[8 * 128] : 0.f; o[10] = r > 0 ? st[9 * 128] : 0.f; o[9] = 0.f; o[11] = 0.f;
            if constexpr (decltype(FAST)::value) {
#pragma unroll 1
                for (int j = CPI * r; j < CPI * (r + 1); j++) {
                    if (t < 4 && warp == j + 5 && lane == 0) load_kv_chunk(warp);
                    __syncwarp();
                    mbar_wait(smem_u32(&ms.kv[j]), 0);
                    float s[NMG * 4];
                    uint32_t h[NPG * 2];
                    const uint32_t vlo = (uint32_t)descV0 + j * (KV_CHUNK >> 4);
                    wg_fence();
                    wgmma_qk_f32(s, q, descKe + (uint64_t)(j * (KV_CHUNK >> 4)));
                    wgmma_qk_f16(h, q, descKo + (uint64_t)(j * (KV_CHUNK >> 4)));
                    wg_commit();
                    wg_wait<0>();
                    pin(s);
                    pin(h);
                    if (t >= 4) {
                        if (j > 0) release_chunk(j - 1);
                        if (!refilled && j > warp) refilled = refill_kv_chunk(smem, ms, warp, cta, lane, &tmWo, &tmG, &tmU);
                    }
#pragma unroll
                    for (int kg = 0; kg < 8 / PVG; kg++) {
                        uint32_t p[4 * PVG];
#pragma unroll
                        for (int u = 0; u < PVG; u++) {
                            const int k = kg * PVG + u;
#pragma unroll
                            for (int hf = 0; hf < 2; hf++) {
                                const int L = 2 * k + hf, gi = g_idx(L);
                                if (is_poly_group(L)) {
                                    p[4 * u + 2 * hf] = ex2_pair_h16(h[2 * (gi < NPG ? gi : 0)]);
                                    p[4 * u + 2 * hf + 1] = ex2_pair_h16(h[2 * (gi < NPG ? gi : 0) + 1]);
                                } else {
                                    const int b = 4 * (gi < NMG ? gi : 0);
                                    p[4 * u + 2 * hf] = pack_bf16(ex2_mufu(s[b]), ex2_mufu(s[b + 1]));
                                    p[4 * u + 2 * hf + 1] = pack_bf16(ex2_mufu(s[b + 2]), ex2_mufu(s[b + 3]));
                                }
                            }
                        }
                        wg_fence();
#pragma unroll
                        for (int u = 0; u < PVG; u++)
                            wgmma_pv24_lh(o, p[4 * u], p[4 * u + 1], p[4 * u + 2], p[4 * u + 3], vlo + (kg * PVG + u) * 16, (uint32_t)(descV0 >> 32));
                        wg_commit();
                        wg_wait<PVWAIT>();
                    }
                }
                wg_wait<0>();
                pin(o);
            } else {
                guarded_item(smem, ms, r, t, warp, load_kv_chunk);
#pragma unroll
                for (int i = 0; i < 8; i++) o[i] = st[i * 128];
                o[8] = st[8 * 128]; o[10] = st[9 * 128];
            }
            if (t >= 4) release_chunk(15);
            if (r < NR - 1) {
#pragma unroll
                for (int i = 0; i < 8; i++) st[i * 128] = o[i];
                st[8 * 128] = o[8]; st[9 * 128] = o[10];
            } else {
                const float l0 = __shfl_sync(0xffffffffu, o[8], lane & ~3), l1 = __shfl_sync(0xffffffffu, o[10], lane & ~3);
                const float r0 = __fdividef(1.f, l0), r1 = __fdividef(1.f, l1);
                uint32_t* Op = reinterpret_cast<uint32_t*>(gO + (size_t)(quarter * 512 + t * 64 + w4 * 16) * DM + head * DH);
                Op[g * 256 + t4] = pack_bf16(o[0] * r0, o[1] * r0);
                Op[(g + 8) * 256 + t4] = pack_bf16(o[2] * r1, o[3] * r1);
                Op[g * 256 + 4 + t4] = pack_bf16(o[4] * r0, o[5] * r0);
                Op[(g + 8) * 256 + 4 + t4] = pack_bf16(o[6] * r1, o[7] * r1);
            }
            bar_sync(3 + wg, 128);
            if (t128 == 0) {
                asm volatile("st.release.cta.shared.u32 [%0], %1;" ::"r"(smem_u32(&ms.seq[t])), "r"(r + 1) : "memory");
                if (t >= 4) {
                    fence_gpu();
                    asm volatile("st.relaxed.gpu.global.u32 [%0], %1;" ::"l"(&gFlagO[(quarter * 8 + t - 4) * 32 + head]), "r"(tag) : "memory");
                    asm volatile("st.relaxed.gpu.global.u32 [%0], %1;" ::"l"(&gFlagO[(quarter * 8 + t) * 32 + head]), "r"(tag) : "memory");
                }
            }
            if (r == 0 && t == 3 && tid == 511) {
                bulk_prefetch_l2(reinterpret_cast<const char*>(w_down) + cta * 14336, 14336);
            }
            if (t128 == 0) TS(40 + wg + (t >= 4 ? 4 : 0));
            item = ms.nxt[wg];
            bar_sync(3 + wg, 128);
        }
        };
        if (fast) run_items(std::true_type{}); else run_items(std::false_type{});
    }
    __syncthreads();
    if (!refilled) refill_kv_chunk(smem, ms, warp, cta, lane, &tmWo, &tmG, &tmU);
    if (tid == 0) TS(4);

    const int rb3 = cta >> 2, cb = cta & 3;
    if (wg < 2) {
        const int r0 = rb3 * 64 + w4 * 16 + g, r1 = r0 + 8;
        const int col0 = cb * 128 + wg * 64 + 2 * t4;
        uint32_t xa[8], xb[8], wr[8];
#pragma unroll
        for (int j = 0; j < 8; j++) {
            xa[j] = __ldg(reinterpret_cast<const uint32_t*>(x + (size_t)r0 * DM + col0 + j * 8));
            xb[j] = __ldg(reinterpret_cast<const uint32_t*>(x + (size_t)r1 * DM + col0 + j * 8));
            wr[j] = __ldg(reinterpret_cast<const uint32_t*>(w_r + col0 + j * 8));
        }
        const float p0 = __bfloat162float(x[(size_t)r0 * DM]), p1 = __bfloat162float(x[(size_t)r1 * DM]);
        const float pivot = __bfloat162float(x[(size_t)(rb3 * 64 + (tid >> 2)) * DM]);
        float wsum = 0.f;
        {
            const uint4 a = __ldg(reinterpret_cast<const uint4*>(w_r) + lane), b = __ldg(reinterpret_cast<const uint4*>(w_r) + 32 + lane);
            const uint32_t w[8] = {a.x, a.y, a.z, a.w, b.x, b.y, b.z, b.w};
#pragma unroll
            for (int e = 0; e < 8; e++) wsum += bf_lo(w[e]) + bf_hi(w[e]);
#pragma unroll
            for (int m = 16; m; m >>= 1) wsum += __shfl_xor_sync(0xffffffffu, wsum, m);
        }
        float acc[32];
#pragma unroll
        for (int i = 0; i < 32; i++) acc[i] = 0.f;
#pragma unroll 1
        for (int kc = 0; kc < 8; kc++) {
            mbar_wait(smem_u32(&ms.wo[kc]), 0);
            mbar_wait(smem_u32(&ms.a3[kc]), 0);
            const uint64_t da = make_desc(smem_u32(smem + SM_A3 + kc * 8192), 16, 1024, 1);
            const uint64_t db = make_desc(smem_u32(smem + (kc * 2 + wg) * KV_CHUNK), 8192, 1024, 1);
            wg_fence();
#pragma unroll
            for (int ks = 0; ks < 4; ks++) wgmma_n64(acc, da + ks * 2, db + ks * 128);
            wg_commit();
        }
        wg_wait<0>();
        pin(acc);
        if (tid == 0) TS(6);
        float s1a = 0.f, s2a = 0.f, s3a = 0.f, s1b = 0.f, s2b = 0.f, s3b = 0.f;
#pragma unroll
        for (int j = 0; j < 8; j++) {
            const uint32_t ha = pack_bf16(bf_lo(xa[j]) + acc[4 * j], bf_hi(xa[j]) + acc[4 * j + 1]);
            const uint32_t hb = pack_bf16(bf_lo(xb[j]) + acc[4 * j + 2], bf_hi(xb[j]) + acc[4 * j + 3]);
            xa[j] = ha; xb[j] = hb;
            const float w0 = bf_lo(wr[j]), w1 = bf_hi(wr[j]);
            const float da0 = bf_lo(ha) - p0, da1 = bf_hi(ha) - p0, db0 = bf_lo(hb) - p1, db1 = bf_hi(hb) - p1;
            s1a += da0 + da1; s2a = fmaf(da0, da0, fmaf(da1, da1, s2a)); s3a = fmaf(da0, w0, fmaf(da1, w1, s3a));
            s1b += db0 + db1; s2b = fmaf(db0, db0, fmaf(db1, db1, s2b)); s3b = fmaf(db0, w0, fmaf(db1, w1, s3b));
        }
#pragma unroll
        for (int m = 1; m <= 2; m <<= 1) {
            s1a += __shfl_xor_sync(0xffffffffu, s1a, m); s2a += __shfl_xor_sync(0xffffffffu, s2a, m); s3a += __shfl_xor_sync(0xffffffffu, s3a, m);
            s1b += __shfl_xor_sync(0xffffffffu, s1b, m); s2b += __shfl_xor_sync(0xffffffffu, s2b, m); s3b += __shfl_xor_sync(0xffffffffu, s3b, m);
        }
        if (t4 == 0) {
            const int lr = w4 * 16 + g;
            ms.p3.part[wg][lr][0] = s1a; ms.p3.part[wg][lr][1] = s2a; ms.p3.part[wg][lr][2] = s3a;
            ms.p3.part[wg][lr + 8][0] = s1b; ms.p3.part[wg][lr + 8][1] = s2b; ms.p3.part[wg][lr + 8][2] = s3b;
        }
        if (tid == 0) TS(11);
        bar_sync(1, 256);
        if (tid == 0) TS(12);
        if (tid < 64) {
            st_pkt(&gPart[(rb3 * 64 + tid) * 4 + cb],
                   make_uint4(__float_as_uint(ms.p3.part[0][tid][0] + ms.p3.part[1][tid][0]), __float_as_uint(ms.p3.part[0][tid][1] + ms.p3.part[1][tid][1]),
                              __float_as_uint(ms.p3.part[0][tid][2] + ms.p3.part[1][tid][2]), tag));
        }
        {
            const int lr = tid >> 2, sl = tid & 3;
            uint4 pv[1];
            wait_pkts<1, 0xffffffffu>(&gPart[rb3 * 256 + tid], 0, tag, pv);
            float s1 = __uint_as_float(pv[0].x), s2 = __uint_as_float(pv[0].y), s3 = __uint_as_float(pv[0].z);
            if (tid == 0) TS(14);
#pragma unroll
            for (int m = 1; m <= 2; m <<= 1) {
                s1 += __shfl_xor_sync(0xffffffffu, s1, m); s2 += __shfl_xor_sync(0xffffffffu, s2, m); s3 += __shfl_xor_sync(0xffffffffu, s3, m);
            }
            if (sl == 0) {
                const float md = s1 * (1.f / DM);
                const float var = fmaxf(s2 * (1.f / DM) - md * md, 0.f);
                const float rs = rsqrtf(var + LN_EPS);
                ms.p3.mu[lr] = pivot + md;
                ms.p3.rs[lr] = rs;
                ms.p3.r[lr] = (s3 - md * wsum) * rs;
            }
        }
        bar_sync(1, 256);
        if (tid == 0) TS(7);
        {
            unsigned int i1, i2;
            warp_top2(f2ord(ms.p3.r[lane]), lane, f2ord(ms.p3.r[lane + 32]), lane + 32, i1, i2);
            if (cb == 0) {
                const int c = tid & 1, li = c ? i2 : i1;
                st_pkt(&gCand[(tid >> 1) * 64 + rb3 * 2 + c],
                       make_uint4(__float_as_uint(ms.p3.r[li]), __float_as_uint(ms.p3.mu[li]), __float_as_uint(ms.p3.rs[li]),
                                  (tag << 11) | (unsigned int)(rb3 * 64 + li)));
            }
#pragma unroll
            for (int c = 0; c < 2; c++) {
                const unsigned int li = c ? i2 : i1;
                if ((int)(li >> 4) == w4 && (int)(li & 7) == g) {
                    const bool hi = (li & 8) != 0;
                    uint4* dst = &gCandRow[(rb3 * 2 + c) * 128 + (cb * 2 + wg) * 16 + t4];
#pragma unroll
                    for (int q = 0; q < 4; q++)
                        st_pkt(dst + q * 4, make_uint4(hi ? xb[2 * q] : xa[2 * q], hi ? xb[2 * q + 1] : xa[2 * q + 1], 0u, tag));
                }
            }
            if (tid == 0) TS(15);
        }
        {
            const int lr0 = w4 * 16 + g;
            const float mu0 = ms.p3.mu[lr0], rs0 = ms.p3.rs[lr0], mu1 = ms.p3.mu[lr0 + 8], rs1 = ms.p3.rs[lr0 + 8];
            char* so = smem + wg * KV_CHUNK;
#pragma unroll
            for (int j = 0; j < 8; j++) {
                const float a0 = bf_lo(xa[j]), a1 = bf_hi(xa[j]), b0 = bf_lo(xb[j]), b1 = bf_hi(xb[j]);
                const uint32_t la = pack_bf16((a0 - mu0) * rs0, (a1 - mu0) * rs0);
                const uint32_t lb = pack_bf16((b0 - mu1) * rs1, (b1 - mu1) * rs1);
                const int o = ((j ^ g) << 4) + t4 * 4;
                *reinterpret_cast<uint32_t*>(so + lr0 * 128 + o) = pack_bf16(a0 + bf_lo(la), a1 + bf_hi(la));
                *reinterpret_cast<uint32_t*>(so + (lr0 + 8) * 128 + o) = pack_bf16(b0 + bf_lo(lb), b1 + bf_hi(lb));
            }
            asm volatile("fence.proxy.async.shared::cta;" ::: "memory");
            bar_sync(3 + wg, 128);
            if ((tid & 127) == 0) {
                tma_store_2d(&tmOut, smem_u32(so), cb * 128 + wg * 64, rb3 * 64);
                asm volatile("cp.async.bulk.wait_group 0;" ::: "memory");
                st_flag(&gFlagOut[cta * 8 + wg], tag);
            }
        }
    } else {
        const int t = tid - 256;
        {
            const int kc = warp - 8;
            if (lane == 0) {
                int it = 0;
                while (true) {
                    const uint4 f = ld_pkt(reinterpret_cast<const uint4*>(&gFlagO[rb3 * 32 + kc * 4]));
                    if (f.x == tag && f.y == tag && f.z == tag && f.w == tag) break;
                    if (++it > SPIN_LIMIT) __trap();
                    BACKOFF();
                }
                if (kc == 7) TS(5);
                fence_proxy_async_global();
                const uint32_t bar = smem_u32(&ms.a3[kc]);
                mbar_expect_tx(bar, 8192);
                tma_2d(smem_u32(smem + SM_A3 + kc * 8192), &tmO, kc * 64, rb3 * 64, bar);
            }
            __syncwarp();
        }
        uint32_t wd[16];
        if (cta < NFFN) {
#pragma unroll
            for (int k = 0; k < 16; k++) wd[k] = __ldg(reinterpret_cast<const uint32_t*>(w_down + (size_t)(cta * 16 + k) * DM + 2 * t));
        }
        if (warp == 8) {
            if (lane == 0) TS(56);
            uint4 cv[2];
            wait_pkts<2, 0xfffff800u>(&gCand[cta * 64 + lane * 2], 1, tag << 11, cv);
            if (lane == 0) TS(54);
            unsigned int i1, i2;
            warp_top2(f2ord(__uint_as_float(cv[0].x)), cv[0].w & 0x7ffu, f2ord(__uint_as_float(cv[1].x)), cv[1].w & 0x7ffu, i1, i2);
#pragma unroll
            for (int c = 0; c < 2; c++) {
                const unsigned int ci = cv[c].w & 0x7ffu;
                if (ci == i1 || ci == i2) {
                    const int o = ci == i1 ? 0 : 1;
                    ms.idx[o] = (int)ci;
                    ms.cslot[o] = lane * 2 + c;
                    *reinterpret_cast<float4*>(&ms.sel[o * 4]) =
                        make_float4(__uint_as_float(cv[c].y), __uint_as_float(cv[c].z), __fdividef(1.f, 1.f + __expf(-__uint_as_float(cv[c].x))), 0.f);
                }
            }
            if (lane == 0) TS(8);
        }
        bar_sync(2, 256);
        const int idx0 = ms.idx[0], idx1 = ms.idx[1];
        if (t == 0 && idx0 >= 0) TS(61);
        float* sX = reinterpret_cast<float*>(smem + SM_A3);
        float* sH = sX + 1024;
        float* sPart = sX + 2048;
        float* sAct = sPart + 512;
        if (cta < NFFN) {
            {
                const int tk = t >> 7, P = t & 127;
                uint4 hv[1];
                wait_pkts<1, 0xffffffffu>(&gCandRow[ms.cslot[tk] * 128 + P], 0, tag, hv);
                if (t == 0) TS(57);
                const float mu = ms.sel[tk * 4], rs = ms.sel[tk * 4 + 1];
                const int col = (P >> 4) * 64 + ((P >> 2) & 3) * 16 + (P & 3) * 2;
                const uint32_t l0 = pack_bf16((bf_lo(hv[0].x) - mu) * rs, (bf_hi(hv[0].x) - mu) * rs);
                const uint32_t l1 = pack_bf16((bf_lo(hv[0].y) - mu) * rs, (bf_hi(hv[0].y) - mu) * rs);
                *reinterpret_cast<float2*>(&sX[tk * 512 + col]) = make_float2(bf_lo(l0), bf_hi(l0));
                *reinterpret_cast<float2*>(&sX[tk * 512 + col + 8]) = make_float2(bf_lo(l1), bf_hi(l1));
                *reinterpret_cast<float2*>(&sH[tk * 512 + col]) = make_float2(bf_lo(hv[0].x), bf_hi(hv[0].x));
                *reinterpret_cast<float2*>(&sH[tk * 512 + col + 8]) = make_float2(bf_lo(hv[0].y), bf_hi(hv[0].y));
            }
            mbar_wait(smem_u32(&ms.moe), 0);
            bar_sync(1 + 8, 256);
            if (t == 0) { asm volatile("" ::: "memory"); sAct[40] = sX[0]; TS(58); }
            {
                const int wv = warp - 8, kk = lane >> 3, cp = lane & 7;
                float a[2][2][2] = {};
#pragma unroll
                for (int i = 0; i < 16; i++) {
                    const int k = wv * 64 + i * 4 + kk;
                    const float x0 = sX[k], x1 = sX[512 + k];
#pragma unroll
                    for (int mat = 0; mat < 2; mat++) {
                        const uint32_t w = *reinterpret_cast<const uint32_t*>(smem + (mat * 8 + wv) * KV_CHUNK + 8192 + (i * 4 + kk) * 32 + cp * 4);
                        a[mat][0][0] = fmaf(x0, bf_lo(w), a[mat][0][0]); a[mat][0][1] = fmaf(x0, bf_hi(w), a[mat][0][1]);
                        a[mat][1][0] = fmaf(x1, bf_lo(w), a[mat][1][0]); a[mat][1][1] = fmaf(x1, bf_hi(w), a[mat][1][1]);
                    }
                }
#pragma unroll
                for (int mat = 0; mat < 2; mat++)
#pragma unroll
                    for (int tk = 0; tk < 2; tk++)
#pragma unroll
                        for (int e = 0; e < 2; e++) {
                            float v = a[mat][tk][e];
                            v += __shfl_xor_sync(0xffffffffu, v, 8);
                            v += __shfl_xor_sync(0xffffffffu, v, 16);
                            if (kk == 0) sPart[(wv * 2 + tk) * 32 + mat * 16 + 2 * cp + e] = v;
                        }
            }
            bar_sync(1 + 8, 256);
            if (t == 0) { sAct[41] = sPart[0]; TS(59); }
            if (t < 32) {
                const int tk = t >> 4, c = t & 15;
                float gs = 0.f, us = 0.f;
#pragma unroll
                for (int w = 0; w < 8; w++) { gs += sPart[(w * 2 + tk) * 32 + c]; us += sPart[(w * 2 + tk) * 32 + 16 + c]; }
                const float gb = bf_round(gs), ub = bf_round(us);
                const float sl = bf_round(__fdividef(gb, 1.f + __expf(-gb)));
                sAct[tk * 16 + c] = bf_round(sl * ub);
            }
            bar_sync(1 + 8, 256);
            {
                float y00 = 0.f, y01 = 0.f, y10 = 0.f, y11 = 0.f;
#pragma unroll
                for (int k = 0; k < 16; k++) {
                    const float a0 = sAct[k], a1 = sAct[16 + k];
                    y00 = fmaf(a0, bf_lo(wd[k]), y00); y01 = fmaf(a0, bf_hi(wd[k]), y01);
                    y10 = fmaf(a1, bf_lo(wd[k]), y10); y11 = fmaf(a1, bf_hi(wd[k]), y11);
                }
                st_pkt(&gYPart[((t >> 2) * NFFN + cta) * 4 + (t & 3)], embed_tag(y00, y01, y10, y11, tag));
            }
            if (t == 0) TS(9);
        }
        if (cta < 64) {
            const int pc = t & 3, part = t >> 2;
            const int opc = (t >> 2) & 3, oe = t & 3, otk = oe >> 1, ocol = (cta * 4 + opc) * 2 + (oe & 1);
            float y[4] = {0.f, 0.f, 0.f, 0.f};
            if (part < 56) {
                uint4 yv[2];
                wait_pkts4<2>(&gYPart[(cta * NFFN + part) * 4 + pc], 56 * 4, tag, yv);
                if (t == 0) TS(60);
                y[0] = __uint_as_float(yv[0].x) + __uint_as_float(yv[1].x); y[1] = __uint_as_float(yv[0].y) + __uint_as_float(yv[1].y);
                y[2] = __uint_as_float(yv[0].z) + __uint_as_float(yv[1].z); y[3] = __uint_as_float(yv[0].w) + __uint_as_float(yv[1].w);
            }
            if (t >= 224 && t < 226) {
                const int orow = (t & 1) ? idx1 : idx0, oc = cta * 8;
                wait_flag(&gFlagOut[((orow >> 6) * 4 + (oc >> 7)) * 8 + ((oc >> 6) & 1)], tag);
            }
            __syncwarp();
#pragma unroll
            for (int e = 0; e < 4; e++) {
                y[e] += __shfl_xor_sync(0xffffffffu, y[e], 4); y[e] += __shfl_xor_sync(0xffffffffu, y[e], 8); y[e] += __shfl_xor_sync(0xffffffffu, y[e], 16);
            }
            float* sR = sAct + 32;
            if (lane < 4) *reinterpret_cast<float4*>(&sR[(warp - 8) * 16 + lane * 4]) = make_float4(y[0], y[1], y[2], y[3]);
            bar_sync(1 + 8, 256);
            if (t < 16) {
                float s = 0.f;
#pragma unroll
                for (int w = 0; w < 8; w++) s += sR[w * 16 + t];
                const float yb = bf_round(bf_round(s) * ms.sel[otk * 4 + 2]);
                out[(size_t)(otk ? idx1 : idx0) * DM + ocol] = __float2bfloat16(sH[otk * 512 + ocol] + bf_round(sX[otk * 512 + ocol] + yb));
            }
            if (cta == 0 && t == 0) {
                *reinterpret_cast<volatile unsigned int*>(&gEpoch) = tag;
            }
            if (t == 0) TS(10);
        }
    }
}

typedef CUresult (*EncodeFn)(CUtensorMap*, CUtensorMapDataType, cuuint32_t, void*, const cuuint64_t*, const cuuint64_t*,
                             const cuuint32_t*, const cuuint32_t*, CUtensorMapInterleave, CUtensorMapSwizzle,
                             CUtensorMapL2promotion, CUtensorMapFloatOOBfill);

void make_map(EncodeFn enc, CUtensorMap* tm, const void* base, uint64_t cols, uint64_t rows, uint32_t box_c, uint32_t box_r, bool swz) {
    cuuint64_t dims[2] = {cols, rows};
    cuuint64_t strides[1] = {cols * 2};
    cuuint32_t box[2] = {box_c, box_r};
    cuuint32_t es[2] = {1, 1};
    enc(tm, CU_TENSOR_MAP_DATA_TYPE_BFLOAT16, 2, const_cast<void*>(base), dims, strides, box, es, CU_TENSOR_MAP_INTERLEAVE_NONE,
        swz ? CU_TENSOR_MAP_SWIZZLE_128B : CU_TENSOR_MAP_SWIZZLE_NONE, CU_TENSOR_MAP_L2_PROMOTION_L2_256B,
        CU_TENSOR_MAP_FLOAT_OOB_FILL_NONE);
}

}

extern "C" void kernel_launch(void* const* d_in, const int* in_sizes, int n_in, void* d_out, int out_size) {
    const __nv_bfloat16* x = (const __nv_bfloat16*)d_in[0];
    const __nv_bfloat16* wqkv = (const __nv_bfloat16*)d_in[1];
    const __nv_bfloat16* wo = (const __nv_bfloat16*)d_in[2];
    const __nv_bfloat16* w_r = (const __nv_bfloat16*)d_in[4];
    const __nv_bfloat16* w_gate = (const __nv_bfloat16*)d_in[5];
    const __nv_bfloat16* w_up = (const __nv_bfloat16*)d_in[6];
    const __nv_bfloat16* w_down = (const __nv_bfloat16*)d_in[7];
    __nv_bfloat16* out = (__nv_bfloat16*)d_out;

    static EncodeFn enc = nullptr;
    static void* pO = nullptr;
    if (!enc) {
        void* fn = nullptr;
        cudaDriverEntryPointQueryResult qr;
        cudaGetDriverEntryPoint("cuTensorMapEncodeTiled", &fn, cudaEnableDefault, &qr);
        enc = (EncodeFn)fn;
        cudaGetSymbolAddress(&pO, gO);
        cudaFuncSetAttribute(mega_kernel, cudaFuncAttributeMaxDynamicSharedMemorySize, SMEM_TOTAL);
    }
    CUtensorMap tmX, tmW, tmO, tmWo, tmG, tmU, tmOut;
    make_map(enc, &tmX, x, DM, S_LEN, 64, 128, true);
    make_map(enc, &tmW, wqkv, 3 * DM, DM, 64, 64, true);
    make_map(enc, &tmO, pO, DM, S_LEN, 64, 64, true);
    make_map(enc, &tmWo, wo, DM, DM, 64, 64, true);
    make_map(enc, &tmG, w_gate, FF, DM, 16, 64, false);
    make_map(enc, &tmU, w_up, FF, DM, 16, 64, false);
    make_map(enc, &tmOut, out, DM, S_LEN, 64, 64, true);

    mega_kernel<<<128, 512, SMEM_TOTAL, cudaStreamPerThread>>>(tmX, tmW, tmO, tmWo, tmG, tmU, tmOut, x, wqkv, wo, w_r, w_gate, w_up, w_down, out);
}
```

```cpp
#include <cuda_runtime.h>
#include <cuda_bf16.h>
#include <cuda.h>
#include <stdint.h>
#include <type_traits>

namespace {

constexpr int S_LEN = 2048, DM = 512, NH = 32, DH = 16, FF = 1792;
constexpr int NFFN = FF / 16;
constexpr float LN_EPS = 1e-5f;
constexpr float QSCALE = 0.25f * 1.4426950408889634f;

__device__ __align__(1024) __nv_bfloat16 gQ[NH * S_LEN * DH];
__device__ __align__(1024) __nv_bfloat16 gKV[NH * S_LEN * DH * 2];
__device__ __align__(1024) uint32_t gO[2][S_LEN * DM / 2];
__device__ unsigned int gEpoch;
__device__ uint4 gFlagQKV[128 * 4];
__device__ uint4 gStat1[S_LEN];
__device__ uint4 gCsPart[8 * 16 * 48];
__device__ uint4 gPart[32 * 64 * 4];
__device__ uint4 gCand[128 * 64];
__device__ __align__(32) unsigned int gFlagOut[128 * 8];
__device__ uint4 gCandRow[64 * 128];
__device__ uint4 gYPart[NFFN * 256];

#define TS(slot) do {} while (0)

__device__ __forceinline__ uint32_t smem_u32(const void* p) { return (uint32_t)__cvta_generic_to_shared(p); }
__device__ __forceinline__ void mbar_init(uint32_t bar, uint32_t cnt) {
    asm volatile("mbarrier.init.shared::cta.b64 [%0], %1;" ::"r"(bar), "r"(cnt));
}
__device__ __forceinline__ void mbar_expect_tx(uint32_t bar, uint32_t bytes) {
    asm volatile("mbarrier.arrive.expect_tx.shared::cta.b64 _, [%0], %1;" ::"r"(bar), "r"(bytes) : "memory");
}
__device__ __forceinline__ void mbar_arrive(uint32_t bar) {
    asm volatile("mbarrier.arrive.shared::cta.b64 _, [%0];" ::"r"(bar) : "memory");
}
constexpr int SPIN_LIMIT = 1 << 22;
#define ITEMMODE 0
#define PVG 2
#define PVWAIT 2
#define CPI 16
#define NR (16 / CPI)
#define BACKOFF() __nanosleep(32)
__device__ __forceinline__ void mbar_wait(uint32_t bar, uint32_t parity) {
    uint32_t done = 0;
    int it = 0;
    while (true) {
        asm volatile("{.reg .pred p; mbarrier.try_wait.parity.shared::cta.b64 p, [%1], %2; selp.u32 %0, 1, 0, p;}"
                     : "=r"(done) : "r"(bar), "r"(parity) : "memory");
        if (done) break;
        if (++it > SPIN_LIMIT) __trap();
    }
}
__device__ __forceinline__ void bulk_g2s(uint32_t dst, const void* src, uint32_t bytes, uint32_t bar) {
    asm volatile("cp.async.bulk.shared::cluster.global.mbarrier::complete_tx::bytes [%0], [%1], %2, [%3];"
                 ::"r"(dst), "l"(src), "r"(bytes), "r"(bar) : "memory");
}
__device__ __forceinline__ void bulk_prefetch_l2(const void* src, uint32_t bytes) {
    asm volatile("cp.async.bulk.prefetch.L2.global [%0], %1;" ::"l"(src), "r"(bytes) : "memory");
}
__device__ __forceinline__ void tma_2d(uint32_t dst, const CUtensorMap* tm, int c0, int c1, uint32_t bar) {
    asm volatile("cp.async.bulk.tensor.2d.shared::cluster.global.mbarrier::complete_tx::bytes [%0], [%1, {%3, %4}], [%2];"
                 ::"r"(dst), "l"(tm), "r"(bar), "r"(c0), "r"(c1) : "memory");
}
__device__ __forceinline__ void tma_store_2d(const CUtensorMap* tm, uint32_t src, int c0, int c1) {
    asm volatile("cp.async.bulk.tensor.2d.global.shared::cta.bulk_group [%0, {%2, %3}], [%1];" ::"l"(tm), "r"(src), "r"(c0), "r"(c1) : "memory");
    asm volatile("cp.async.bulk.commit_group;" ::: "memory");
}
__device__ __forceinline__ void fence_proxy_async_global() { asm volatile("fence.proxy.async.global;" ::: "memory"); }
__device__ __forceinline__ void fence_gpu() { asm volatile("fence.acq_rel.gpu;" ::: "memory"); }
__device__ __forceinline__ void bar_sync(int id, int n) { asm volatile("bar.sync %0, %1;" ::"r"(id), "r"(n) : "memory"); }
__device__ __forceinline__ void bar_arrive(int id, int n) { asm volatile("bar.arrive %0, %1;" ::"r"(id), "r"(n) : "memory"); }
__device__ __forceinline__ void st_flag(unsigned int* p, unsigned int v) {
    asm volatile("st.release.gpu.global.u32 [%0], %1;" ::"l"(p), "r"(v) : "memory");
}
__device__ __forceinline__ unsigned int ld_flag(const unsigned int* p) {
    unsigned int v;
    asm volatile("ld.relaxed.gpu.global.u32 %0, [%1];" : "=r"(v) : "l"(p) : "memory");
    return v;
}
__device__ __forceinline__ void wait_flag(const unsigned int* p, unsigned int tag) {
    int it = 0;
    while (ld_flag(p) != tag) {
        if (++it > SPIN_LIMIT) __trap();
        BACKOFF();
    }
}
__device__ __forceinline__ void st_word_nz(uint32_t* p, uint32_t v) {
    asm volatile("st.relaxed.gpu.global.u32 [%0], %1;" ::"l"(p), "r"(v ? v : 0x80000000u) : "memory");
}
__device__ __forceinline__ void st_pkt(uint4* p, uint4 v) {
    asm volatile("st.relaxed.gpu.global.v4.u32 [%0], {%1,%2,%3,%4};" ::"l"(p), "r"(v.x), "r"(v.y), "r"(v.z), "r"(v.w) : "memory");
}
__device__ __forceinline__ uint4 ld_pkt(const uint4* p) {
    uint4 v;
    asm volatile("ld.relaxed.gpu.global.v4.u32 {%0,%1,%2,%3}, [%4];" : "=r"(v.x), "=r"(v.y), "=r"(v.z), "=r"(v.w) : "l"(p) : "memory");
    return v;
}
template <int N, unsigned int MASK>
__device__ __forceinline__ void wait_pkts(const uint4* p, int stride, unsigned int tag, uint4 (&v)[N]) {
    int it = 0;
    while (true) {
        bool ok = true;
#pragma unroll
        for (int i = 0; i < N; i++) v[i] = ld_pkt(p + (size_t)i * stride);
#pragma unroll
        for (int i = 0; i < N; i++) ok = ok && ((v[i].w & MASK) == tag);
        if (ok) break;
        if (++it > SPIN_LIMIT) __trap();
        BACKOFF();
    }
}
__device__ __forceinline__ uint4 embed_tag(float a, float b, float c, float d, unsigned int tag) {
    return make_uint4((__float_as_uint(a) & ~15u) | (tag & 15u), (__float_as_uint(b) & ~15u) | ((tag >> 4) & 15u),
                      (__float_as_uint(c) & ~15u) | ((tag >> 8) & 15u), (__float_as_uint(d) & ~15u) | ((tag >> 12) & 15u));
}
template <int N>
__device__ __forceinline__ void wait_pkts4(const uint4* p, int stride, unsigned int tag, uint4 (&v)[N]) {
    const unsigned int t16 = tag & 0xffffu;
    int it = 0;
    while (true) {
        bool ok = true;
#pragma unroll
        for (int i = 0; i < N; i++) v[i] = ld_pkt(p + (size_t)i * stride);
#pragma unroll
        for (int i = 0; i < N; i++)
            ok = ok && (((v[i].x & 15u) | ((v[i].y & 15u) << 4) | ((v[i].z & 15u) << 8) | ((v[i].w & 15u) << 12)) == t16);
        if (ok) break;
        if (++it > SPIN_LIMIT) __trap();
        BACKOFF();
    }
}
__device__ __forceinline__ uint64_t make_desc(uint32_t addr, uint32_t lbo, uint32_t sbo, uint32_t mode) {
    return (uint64_t)((addr & 0x3FFFF) >> 4) | ((uint64_t)((lbo & 0x3FFFF) >> 4) << 16) |
           ((uint64_t)((sbo & 0x3FFFF) >> 4) << 32) | ((uint64_t)mode << 62);
}
__device__ __forceinline__ void wg_fence() { asm volatile("wgmma.fence.sync.aligned;" ::: "memory"); }
__device__ __forceinline__ void wg_commit() { asm volatile("wgmma.commit_group.sync.aligned;" ::: "memory"); }
template <int N> __device__ __forceinline__ void wg_wait() { asm volatile("wgmma.wait_group.sync.aligned %0;" ::"n"(N) : "memory"); }
template <int N> __device__ __forceinline__ void pin(uint32_t (&d)[N]) {
#pragma unroll
    for (int i = 0; i < N; i++) asm volatile("" : "+r"(d[i])::"memory");
}
template <int N> __device__ __forceinline__ void pin(float (&d)[N]) {
#pragma unroll
    for (int i = 0; i < N; i++) asm volatile("" : "+f"(d[i])::"memory");
}
__device__ __forceinline__ uint32_t pack_bf16(float lo, float hi) {
    uint32_t r;
    asm("cvt.rn.bf16x2.f32 %0, %1, %2;" : "=r"(r) : "f"(hi), "f"(lo));
    return r;
}
__device__ __forceinline__ float bf_lo(uint32_t v) { return __uint_as_float(v << 16); }
__device__ __forceinline__ float bf_hi(uint32_t v) { return __uint_as_float(v & 0xFFFF0000u); }
__device__ __forceinline__ float bf_round(float v) { return __bfloat162float(__float2bfloat16(v)); }
__device__ __forceinline__ float ex2_mufu(float x) {
    float y;
    asm("ex2.approx.ftz.f32 %0, %1;" : "=f"(y) : "f"(x));
    return y;
}

#define ACC8(d, o) "+f"(d[o + 0]), "+f"(d[o + 1]), "+f"(d[o + 2]), "+f"(d[o + 3]), "+f"(d[o + 4]), "+f"(d[o + 5]), "+f"(d[o + 6]), "+f"(d[o + 7])
#define OUT8(d, o) "=f"(d[o + 0]), "=f"(d[o + 1]), "=f"(d[o + 2]), "=f"(d[o + 3]), "=f"(d[o + 4]), "=f"(d[o + 5]), "=f"(d[o + 6]), "=f"(d[o + 7])

__device__ __forceinline__ void wgmma_n192(float (&d)[96], uint64_t da, uint64_t db) {
    asm volatile(
        "wgmma.mma_async.sync.aligned.m64n192k16.f32.bf16.bf16 "
        "{%0,%1,%2,%3,%4,%5,%6,%7,%8,%9,%10,%11,%12,%13,%14,%15,%16,%17,%18,%19,%20,%21,%22,%23,%24,%25,%26,%27,%28,%29,%30,%31,"
        "%32,%33,%34,%35,%36,%37,%38,%39,%40,%41,%42,%43,%44,%45,%46,%47,%48,%49,%50,%51,%52,%53,%54,%55,%56,%57,%58,%59,%60,%61,%62,%63,"
        "%64,%65,%66,%67,%68,%69,%70,%71,%72,%73,%74,%75,%76,%77,%78,%79,%80,%81,%82,%83,%84,%85,%86,%87,%88,%89,%90,%91,%92,%93,%94,%95},"
        "%96, %97, 1, 1, 1, 0, 1;"
        : ACC8(d, 0), ACC8(d, 8), ACC8(d, 16), ACC8(d, 24), ACC8(d, 32), ACC8(d, 40), ACC8(d, 48), ACC8(d, 56),
          ACC8(d, 64), ACC8(d, 72), ACC8(d, 80), ACC8(d, 88)
        : "l"(da), "l"(db));
}
__device__ __forceinline__ void wgmma_n192_rs(float (&d)[96], const uint32_t* a, uint64_t db) {
    asm volatile(
        "wgmma.mma_async.sync.aligned.m64n192k16.f32.bf16.bf16 "
        "{%0,%1,%2,%3,%4,%5,%6,%7,%8,%9,%10,%11,%12,%13,%14,%15,%16,%17,%18,%19,%20,%21,%22,%23,%24,%25,%26,%27,%28,%29,%30,%31,"
        "%32,%33,%34,%35,%36,%37,%38,%39,%40,%41,%42,%43,%44,%45,%46,%47,%48,%49,%50,%51,%52,%53,%54,%55,%56,%57,%58,%59,%60,%61,%62,%63,"
        "%64,%65,%66,%67,%68,%69,%70,%71,%72,%73,%74,%75,%76,%77,%78,%79,%80,%81,%82,%83,%84,%85,%86,%87,%88,%89,%90,%91,%92,%93,%94,%95},"
        "{%96,%97,%98,%99}, %100, 1, 1, 1, 1;"
        : ACC8(d, 0), ACC8(d, 8), ACC8(d, 16), ACC8(d, 24), ACC8(d, 32), ACC8(d, 40), ACC8(d, 48), ACC8(d, 56),
          ACC8(d, 64), ACC8(d, 72), ACC8(d, 80), ACC8(d, 88)
        : "r"(a[0]), "r"(a[1]), "r"(a[2]), "r"(a[3]), "l"(db));
}
__device__ __forceinline__ void ldsm_x4(uint32_t* r, uint32_t addr) {
    asm volatile("ldmatrix.sync.aligned.m8n8.x4.shared.b16 {%0,%1,%2,%3}, [%4];"
                 : "=r"(r[0]), "=r"(r[1]), "=r"(r[2]), "=r"(r[3]) : "r"(addr) : "memory");
}
__device__ __forceinline__ void wgmma_n64(float (&d)[32], uint64_t da, uint64_t db) {
    asm volatile(
        "wgmma.mma_async.sync.aligned.m64n64k16.f32.bf16.bf16 "
        "{%0,%1,%2,%3,%4,%5,%6,%7,%8,%9,%10,%11,%12,%13,%14,%15,%16,%17,%18,%19,%20,%21,%22,%23,%24,%25,%26,%27,%28,%29,%30,%31},"
        "%32, %33, 1, 1, 1, 0, 1;"
        : ACC8(d, 0), ACC8(d, 8), ACC8(d, 16), ACC8(d, 24)
        : "l"(da), "l"(db));
}
__device__ __forceinline__ void wgmma_qk128(float (&d)[64], const uint32_t (&a)[4], uint64_t db) {
    asm volatile("wgmma.mma_async.sync.aligned.m64n128k16.f32.f16.f16 "
        "{%0,%1,%2,%3,%4,%5,%6,%7,%8,%9,%10,%11,%12,%13,%14,%15,%16,%17,%18,%19,%20,%21,%22,%23,%24,%25,%26,%27,%28,%29,%30,%31,%32,%33,%34,%35,%36,%37,%38,%39,%40,%41,%42,%43,%44,%45,%46,%47,%48,%49,%50,%51,%52,%53,%54,%55,%56,%57,%58,%59,%60,%61,%62,%63}, {%64,%65,%66,%67}, %68, 0, 1, 1, 0;"
        : "=f"(d[0]), "=f"(d[1]), "=f"(d[2]), "=f"(d[3]), "=f"(d[4]), "=f"(d[5]), "=f"(d[6]), "=f"(d[7]), "=f"(d[8]), "=f"(d[9]), "=f"(d[10]), "=f"(d[11]), "=f"(d[12]), "=f"(d[13]), "=f"(d[14]), "=f"(d[15]), "=f"(d[16]), "=f"(d[17]), "=f"(d[18]), "=f"(d[19]), "=f"(d[20]), "=f"(d[21]), "=f"(d[22]), "=f"(d[23]), "=f"(d[24]), "=f"(d[25]), "=f"(d[26]), "=f"(d[27]), "=f"(d[28]), "=f"(d[29]), "=f"(d[30]), "=f"(d[31]), "=f"(d[32]), "=f"(d[33]), "=f"(d[34]), "=f"(d[35]), "=f"(d[36]), "=f"(d[37]), "=f"(d[38]), "=f"(d[39]), "=f"(d[40]), "=f"(d[41]), "=f"(d[42]), "=f"(d[43]), "=f"(d[44]), "=f"(d[45]), "=f"(d[46]), "=f"(d[47]), "=f"(d[48]), "=f"(d[49]), "=f"(d[50]), "=f"(d[51]), "=f"(d[52]), "=f"(d[53]), "=f"(d[54]), "=f"(d[55]), "=f"(d[56]), "=f"(d[57]), "=f"(d[58]), "=f"(d[59]), "=f"(d[60]), "=f"(d[61]), "=f"(d[62]), "=f"(d[63])
        : "r"(a[0]), "r"(a[1]), "r"(a[2]), "r"(a[3]), "l"(db));
}
__device__ __forceinline__ void wgmma_qk_f32(float (&d)[32], const uint32_t (&a)[4], uint64_t db) {
    asm volatile("wgmma.mma_async.sync.aligned.m64n64k16.f32.f16.f16 "
        "{%0,%1,%2,%3,%4,%5,%6,%7,%8,%9,%10,%11,%12,%13,%14,%15,%16,%17,%18,%19,%20,%21,%22,%23,%24,%25,%26,%27,%28,%29,%30,%31}, {%32,%33,%34,%35}, %36, 0, 1, 1, 0;"
        : "=f"(d[0]), "=f"(d[1]), "=f"(d[2]), "=f"(d[3]), "=f"(d[4]), "=f"(d[5]), "=f"(d[6]), "=f"(d[7]), "=f"(d[8]), "=f"(d[9]), "=f"(d[10]), "=f"(d[11]), "=f"(d[12]), "=f"(d[13]), "=f"(d[14]), "=f"(d[15]), "=f"(d[16]), "=f"(d[17]), "=f"(d[18]), "=f"(d[19]), "=f"(d[20]), "=f"(d[21]), "=f"(d[22]), "=f"(d[23]), "=f"(d[24]), "=f"(d[25]), "=f"(d[26]), "=f"(d[27]), "=f"(d[28]), "=f"(d[29]), "=f"(d[30]), "=f"(d[31])
        : "r"(a[0]), "r"(a[1]), "r"(a[2]), "r"(a[3]), "l"(db));
}
__device__ __forceinline__ void wgmma_qk_f32(float (&d)[36], const uint32_t (&a)[4], uint64_t db) {
    asm volatile("wgmma.mma_async.sync.aligned.m64n72k16.f32.f16.f16 "
        "{%0,%1,%2,%3,%4,%5,%6,%7,%8,%9,%10,%11,%12,%13,%14,%15,%16,%17,%18,%19,%20,%21,%22,%23,%24,%25,%26,%27,%28,%29,%30,%31,%32,%33,%34,%35}, {%36,%37,%38,%39}, %40, 0, 1, 1, 0;"
        : "=f"(d[0]), "=f"(d[1]), "=f"(d[2]), "=f"(d[3]), "=f"(d[4]), "=f"(d[5]), "=f"(d[6]), "=f"(d[7]), "=f"(d[8]), "=f"(d[9]), "=f"(d[10]), "=f"(d[11]), "=f"(d[12]), "=f"(d[13]), "=f"(d[14]), "=f"(d[15]), "=f"(d[16]), "=f"(d[17]), "=f"(d[18]), "=f"(d[19]), "=f"(d[20]), "=f"(d[21]), "=f"(d[22]), "=f"(d[23]), "=f"(d[24]), "=f"(d[25]), "=f"(d[26]), "=f"(d[27]), "=f"(d[28]), "=f"(d[29]), "=f"(d[30]), "=f"(d[31]), "=f"(d[32]), "=f"(d[33]), "=f"(d[34]), "=f"(d[35])
        : "r"(a[0]), "r"(a[1]), "r"(a[2]), "r"(a[3]), "l"(db));
}
__device__ __forceinline__ void wgmma_qk_f32(float (&d)[40], const uint32_t (&a)[4], uint64_t db) {
    asm volatile("wgmma.mma_async.sync.aligned.m64n80k16.f32.f16.f16 "
        "{%0,%1,%2,%3,%4,%5,%6,%7,%8,%9,%10,%11,%12,%13,%14,%15,%16,%17,%18,%19,%20,%21,%22,%23,%24,%25,%26,%27,%28,%29,%30,%31,%32,%33,%34,%35,%36,%37,%38,%39}, {%40,%41,%42,%43}, %44, 0, 1, 1, 0;"
        : "=f"(d[0]), "=f"(d[1]), "=f"(d[2]), "=f"(d[3]), "=f"(d[4]), "=f"(d[5]), "=f"(d[6]), "=f"(d[7]), "=f"(d[8]), "=f"(d[9]), "=f"(d[10]), "=f"(d[11]), "=f"(d[12]), "=f"(d[13]), "=f"(d[14]), "=f"(d[15]), "=f"(d[16]), "=f"(d[17]), "=f"(d[18]), "=f"(d[19]), "=f"(d[20]), "=f"(d[21]), "=f"(d[22]), "=f"(d[23]), "=f"(d[24]), "=f"(d[25]), "=f"(d[26]), "=f"(d[27]), "=f"(d[28]), "=f"(d[29]), "=f"(d[30]), "=f"(d[31]), "=f"(d[32]), "=f"(d[33]), "=f"(d[34]), "=f"(d[35]), "=f"(d[36]), "=f"(d[37]), "=f"(d[38]), "=f"(d[39])
        : "r"(a[0]), "r"(a[1]), "r"(a[2]), "r"(a[3]), "l"(db));
}
__device__ __forceinline__ void wgmma_qk_f16(uint32_t (&d)[16], const uint32_t (&a)[4], uint64_t db) {
    asm volatile("wgmma.mma_async.sync.aligned.m64n64k16.f16.f16.f16 "
        "{%0,%1,%2,%3,%4,%5,%6,%7,%8,%9,%10,%11,%12,%13,%14,%15}, {%16,%17,%18,%19}, %20, 0, 1, 1, 0;"
        : "=r"(d[0]), "=r"(d[1]), "=r"(d[2]), "=r"(d[3]), "=r"(d[4]), "=r"(d[5]), "=r"(d[6]), "=r"(d[7]), "=r"(d[8]), "=r"(d[9]), "=r"(d[10]), "=r"(d[11]), "=r"(d[12]), "=r"(d[13]), "=r"(d[14]), "=r"(d[15])
        : "r"(a[0]), "r"(a[1]), "r"(a[2]), "r"(a[3]), "l"(db));
}
__device__ __forceinline__ void wgmma_qk_f16(uint32_t (&d)[14], const uint32_t (&a)[4], uint64_t db) {
    asm volatile("wgmma.mma_async.sync.aligned.m64n56k16.f16.f16.f16 "
        "{%0,%1,%2,%3,%4,%5,%6,%7,%8,%9,%10,%11,%12,%13}, {%14,%15,%16,%17}, %18, 0, 1, 1, 0;"
        : "=r"(d[0]), "=r"(d[1]), "=r"(d[2]), "=r"(d[3]), "=r"(d[4]), "=r"(d[5]), "=r"(d[6]), "=r"(d[7]), "=r"(d[8]), "=r"(d[9]), "=r"(d[10]), "=r"(d[11]), "=r"(d[12]), "=r"(d[13])
        : "r"(a[0]), "r"(a[1]), "r"(a[2]), "r"(a[3]), "l"(db));
}
__device__ __forceinline__ void wgmma_qk_f16(uint32_t (&d)[12], const uint32_t (&a)[4], uint64_t db) {
    asm volatile("wgmma.mma_async.sync.aligned.m64n48k16.f16.f16.f16 "
        "{%0,%1,%2,%3,%4,%5,%6,%7,%8,%9,%10,%11}, {%12,%13,%14,%15}, %16, 0, 1, 1, 0;"
        : "=r"(d[0]), "=r"(d[1]), "=r"(d[2]), "=r"(d[3]), "=r"(d[4]), "=r"(d[5]), "=r"(d[6]), "=r"(d[7]), "=r"(d[8]), "=r"(d[9]), "=r"(d[10]), "=r"(d[11])
        : "r"(a[0]), "r"(a[1]), "r"(a[2]), "r"(a[3]), "l"(db));
}
__device__ __forceinline__ void wgmma_qk_f32(float (&d)[28], const uint32_t (&a)[4], uint64_t db) {
    asm volatile("wgmma.mma_async.sync.aligned.m64n56k16.f32.f16.f16 "
        "{%0,%1,%2,%3,%4,%5,%6,%7,%8,%9,%10,%11,%12,%13,%14,%15,%16,%17,%18,%19,%20,%21,%22,%23,%24,%25,%26,%27}, {%28,%29,%30,%31}, %32, 0, 1, 1, 0;"
        : "=f"(d[0]), "=f"(d[1]), "=f"(d[2]), "=f"(d[3]), "=f"(d[4]), "=f"(d[5]), "=f"(d[6]), "=f"(d[7]), "=f"(d[8]), "=f"(d[9]), "=f"(d[10]), "=f"(d[11]), "=f"(d[12]), "=f"(d[13]), "=f"(d[14]), "=f"(d[15]), "=f"(d[16]), "=f"(d[17]), "=f"(d[18]), "=f"(d[19]), "=f"(d[20]), "=f"(d[21]), "=f"(d[22]), "=f"(d[23]), "=f"(d[24]), "=f"(d[25]), "=f"(d[26]), "=f"(d[27])
        : "r"(a[0]), "r"(a[1]), "r"(a[2]), "r"(a[3]), "l"(db));
}
__device__ __forceinline__ void wgmma_qk_f32(float (&d)[24], const uint32_t (&a)[4], uint64_t db) {
    asm volatile("wgmma.mma_async.sync.aligned.m64n48k16.f32.f16.f16 "
        "{%0,%1,%2,%3,%4,%5,%6,%7,%8,%9,%10,%11,%12,%13,%14,%15,%16,%17,%18,%19,%20,%21,%22,%23}, {%24,%25,%26,%27}, %28, 0, 1, 1, 0;"
        : "=f"(d[0]), "=f"(d[1]), "=f"(d[2]), "=f"(d[3]), "=f"(d[4]), "=f"(d[5]), "=f"(d[6]), "=f"(d[7]), "=f"(d[8]), "=f"(d[9]), "=f"(d[10]), "=f"(d[11]), "=f"(d[12]), "=f"(d[13]), "=f"(d[14]), "=f"(d[15]), "=f"(d[16]), "=f"(d[17]), "=f"(d[18]), "=f"(d[19]), "=f"(d[20]), "=f"(d[21]), "=f"(d[22]), "=f"(d[23])
        : "r"(a[0]), "r"(a[1]), "r"(a[2]), "r"(a[3]), "l"(db));
}
__device__ __forceinline__ void wgmma_qk_f16(uint32_t (&d)[18], const uint32_t (&a)[4], uint64_t db) {
    asm volatile("wgmma.mma_async.sync.aligned.m64n72k16.f16.f16.f16 "
        "{%0,%1,%2,%3,%4,%5,%6,%7,%8,%9,%10,%11,%12,%13,%14,%15,%16,%17}, {%18,%19,%20,%21}, %22, 0, 1, 1, 0;"
        : "=r"(d[0]), "=r"(d[1]), "=r"(d[2]), "=r"(d[3]), "=r"(d[4]), "=r"(d[5]), "=r"(d[6]), "=r"(d[7]), "=r"(d[8]), "=r"(d[9]), "=r"(d[10]), "=r"(d[11]), "=r"(d[12]), "=r"(d[13]), "=r"(d[14]), "=r"(d[15]), "=r"(d[16]), "=r"(d[17])
        : "r"(a[0]), "r"(a[1]), "r"(a[2]), "r"(a[3]), "l"(db));
}
__device__ __forceinline__ void wgmma_qk_f16(uint32_t (&d)[20], const uint32_t (&a)[4], uint64_t db) {
    asm volatile("wgmma.mma_async.sync.aligned.m64n80k16.f16.f16.f16 "
        "{%0,%1,%2,%3,%4,%5,%6,%7,%8,%9,%10,%11,%12,%13,%14,%15,%16,%17,%18,%19}, {%20,%21,%22,%23}, %24, 0, 1, 1, 0;"
        : "=r"(d[0]), "=r"(d[1]), "=r"(d[2]), "=r"(d[3]), "=r"(d[4]), "=r"(d[5]), "=r"(d[6]), "=r"(d[7]), "=r"(d[8]), "=r"(d[9]), "=r"(d[10]), "=r"(d[11]), "=r"(d[12]), "=r"(d[13]), "=r"(d[14]), "=r"(d[15]), "=r"(d[16]), "=r"(d[17]), "=r"(d[18]), "=r"(d[19])
        : "r"(a[0]), "r"(a[1]), "r"(a[2]), "r"(a[3]), "l"(db));
}
__device__ __forceinline__ void wgmma_pv24_lh(float (&o)[12], uint32_t a0, uint32_t a1, uint32_t a2, uint32_t a3, uint32_t lo, uint32_t hi) {
    asm volatile(
        "{.reg .b64 d; mov.b64 d, {%16, %17};\n"
        "wgmma.mma_async.sync.aligned.m64n24k16.f32.bf16.bf16 "
        "{%0,%1,%2,%3,%4,%5,%6,%7,%8,%9,%10,%11}, {%12,%13,%14,%15}, d, 1, 1, 1, 1;}"
        : ACC8(o, 0), "+f"(o[8]), "+f"(o[9]), "+f"(o[10]), "+f"(o[11])
        : "r"(a0), "r"(a1), "r"(a2), "r"(a3), "r"(lo), "r"(hi));
}
__device__ __forceinline__ void wgmma_pv24(float (&o)[12], uint32_t a0, uint32_t a1, uint32_t a2, uint32_t a3, uint64_t desc) {
    asm volatile(
        "wgmma.mma_async.sync.aligned.m64n24k16.f32.bf16.bf16 "
        "{%0,%1,%2,%3,%4,%5,%6,%7,%8,%9,%10,%11}, {%12,%13,%14,%15}, %16, 1, 1, 1, 1;"
        : ACC8(o, 0), "+f"(o[8]), "+f"(o[9]), "+f"(o[10]), "+f"(o[11])
        : "r"(a0), "r"(a1), "r"(a2), "r"(a3), "l"(desc));
}

__device__ __forceinline__ uint32_t ex2_pair_h16(uint32_t x2) {
    uint32_t t, r, f, q;
    asm("add.rn.f16x2 %0, %1, %2;" : "=r"(t) : "r"(x2), "r"(0x661E661Fu));
    asm("sub.rn.f16x2 %0, %1, %2;" : "=r"(r) : "r"(t), "r"(0x661E661Fu));
    asm("sub.rn.f16x2 %0, %1, %2;" : "=r"(f) : "r"(x2), "r"(r));
    asm("fma.rn.f16x2 %0, %1, %2, %3;" : "=r"(q) : "r"(0x15101510u), "r"(f), "r"(0x1d7e1d7eu));
    asm("fma.rn.f16x2 %0, %1, %2, %3;" : "=r"(q) : "r"(q), "r"(f), "r"(0x23d823d8u));
    asm("fma.rn.f16x2 %0, %1, %2, %3;" : "=r"(q) : "r"(q), "r"(f), "r"(0x30823035u));
    return t * 128u + q;
}
#define NMG 8
constexpr int NPG = 16 - NMG;
__host__ __device__ constexpr bool is_poly_group(int L) { return NPG <= 8 ? ((L & 1) && L < 2 * NPG) : ((L & 1) || L >= 2 * NMG); }
__host__ __device__ constexpr int g_idx(int L) {
    return NPG <= 8 ? ((L & 1) == 0 ? L / 2 : (L < 2 * NPG ? L / 2 : 8 + (L - 2 * NPG) / 2))
                    : ((L & 1) ? L / 2 : (L < 2 * NMG ? L / 2 : 8 + (L - 2 * NMG) / 2));
}
__host__ __device__ constexpr int k_pos(int L) { return is_poly_group(L) ? NMG + g_idx(L) : g_idx(L); }
constexpr float VSCALE_ODD = 0.70703125f;
constexpr float LOG2C_ODD = 0.50015402f;
__device__ __forceinline__ uint32_t pack_f16_sat(float lo, float hi) {
    uint32_t r;
    asm("cvt.rn.satfinite.f16x2.f32 %0, %1, %2;" : "=r"(r) : "f"(hi), "f"(lo));
    return r;
}
__device__ __forceinline__ unsigned int f2ord(float v) {
    const unsigned int u = __float_as_uint(v);
    const unsigned int o = u ^ ((unsigned int)((int)u >> 31) | 0x80000000u);
    return (v == v) ? o : 0u;
}
__device__ __forceinline__ void warp_top2(unsigned int ka, unsigned int ia, unsigned int kb, unsigned int ib, unsigned int& i1, unsigned int& i2) {
    const unsigned int m1 = __reduce_max_sync(0xffffffffu, max(ka, kb));
    i1 = __reduce_min_sync(0xffffffffu, min(ka == m1 ? ia : 0xffffffffu, kb == m1 ? ib : 0xffffffffu));
    const bool ra = (ia == i1), rb = (ib == i1);
    const unsigned int ka2 = ra ? 0u : ka, kb2 = rb ? 0u : kb, ia2 = ra ? 0xffffffffu : ia, ib2 = rb ? 0xffffffffu : ib;
    const unsigned int m2 = __reduce_max_sync(0xffffffffu, max(ka2, kb2));
    i2 = __reduce_min_sync(0xffffffffu, min(ka2 == m2 ? ia2 : 0xffffffffu, kb2 == m2 ? ib2 : 0xffffffffu));
}

constexpr int P1_STAGES = 5;
constexpr int P1_STAGE_BYTES = 16384 + 24576;
constexpr int KV_CHUNK = 10240;
constexpr int SM_Q = 163840 + 49152;
constexpr int SM_A3 = 163840;
constexpr int SM_MISC = 229376;
constexpr int SMEM_TOTAL = 232448;
struct Misc {
    uint64_t p1_full[P1_STAGES], p1_empty[P1_STAGES];
    uint64_t kv[16];
    uint64_t wo[8], a3[8], moe;
    unsigned int tag;
    int fast;
    int idx[2], cslot[2];
    alignas(16) float sel[8];
    unsigned int norm[12];
    uint64_t qbar;
    int item, nxt[4];
    unsigned int seq[8];
    unsigned int freed[16];
    union alignas(16) {
        struct { float mu[128], rs[128], cs[192]; } p1;
        struct { float part[2][64][3]; float mu[64], rs[64], r[64]; } p3;
    };
};
static_assert(sizeof(Misc) <= SMEM_TOTAL - SM_MISC, "misc smem");

__device__ __forceinline__ void release_kv_chunk(Misc& ms, int j, int lane) {
    asm volatile("{.reg .pred p; setp.eq.s32 p, %1, 0; @p red.relaxed.cta.shared.add.u32 [%0], 1;}" ::"r"(smem_u32(&ms.freed[j])), "r"(lane) : "memory");
}
__device__ __forceinline__ bool refill_kv_chunk(char* smem, Misc& ms, int j, int cta, int lane, const CUtensorMap* tmWo,
                                                const CUtensorMap* tmG, const CUtensorMap* tmU) {
    unsigned int cnt;
    asm volatile("ld.relaxed.cta.shared.u32 %0, [%1];" : "=r"(cnt) : "r"(smem_u32(&ms.freed[j])) : "memory");
    if (cnt < 16u) return false;
    if (lane == 0) {
        const uint32_t dst = smem_u32(smem + j * KV_CHUNK);
        const uint32_t wb = smem_u32(&ms.wo[j >> 1]);
        mbar_expect_tx(wb, 8192);
        tma_2d(dst, tmWo, (cta & 3) * 128 + (j & 1) * 64, (j >> 1) * 64, wb);
        const uint32_t mb = smem_u32(&ms.moe);
        if (cta < NFFN) {
            mbar_expect_tx(mb, 2048);
            tma_2d(dst + 8192, (j & 8) ? tmU : tmG, cta * 16, (j & 7) * 64, mb);
        }
    }
    __syncwarp();
    return true;
}

template <typename LoadFn>
__device__ __forceinline__ void guarded_item(char* smem, Misc& ms, int r, int t, int warp, LoadFn load_chunk) {
    const int tid = threadIdx.x, lane = tid & 31, w4 = (tid >> 5) & 3;
    const uint64_t descK0 = make_desc(smem_u32(smem), 128, 256, 0);
    const uint64_t descV0 = make_desc(smem_u32(smem + 4096), 128, 2048, 0);
    uint32_t q[4];
    {
        const uint32_t* Qs = reinterpret_cast<const uint32_t*>(smem + SM_Q + t * 2048 + w4 * 512);
        q[0] = Qs[lane]; q[2] = Qs[32 + lane]; q[1] = Qs[64 + lane]; q[3] = Qs[96 + lane];
    }
    float* st = reinterpret_cast<float*>(smem + SM_A3) + t * (12 * 128) + (tid & 127);
    float o[12];
#pragma unroll
    for (int i = 0; i < 8; i++) o[i] = r > 0 ? st[i * 128] : 0.f;
    o[8] = r > 0 ? st[8 * 128] : 0.f; o[10] = r > 0 ? st[9 * 128] : 0.f; o[9] = 0.f; o[11] = 0.f;
    float m0 = r > 0 ? st[10 * 128] : -INFINITY, m1 = r > 0 ? st[11 * 128] : -INFINITY;
#pragma unroll 1
    for (int j = CPI * r; j < CPI * (r + 1); j++) {
        if (t < 4 && warp == j + 5 && lane == 0) load_chunk(warp);
        __syncwarp();
        mbar_wait(smem_u32(&ms.kv[j]), 0);
        float s[64];
        const uint32_t off = j * (KV_CHUNK >> 4);
        wg_fence();
        wgmma_qk128(s, q, descK0 + (uint64_t)off);
        wg_commit();
        wg_wait<0>();
        pin(s);
        pin(o);
        if (t >= 4 && j > 0) release_kv_chunk(ms, j - 1, lane);
        float n0 = m0, n1 = m1;
#pragma unroll
        for (int i = 0; i < 16; i++) {
            n0 = fmaxf(n0, fmaxf(s[4 * i], s[4 * i + 1]));
            n1 = fmaxf(n1, fmaxf(s[4 * i + 2], s[4 * i + 3]));
        }
        n0 = fmaxf(n0, __shfl_xor_sync(0xffffffffu, n0, 1)); n0 = fmaxf(n0, __shfl_xor_sync(0xffffffffu, n0, 2));
        n1 = fmaxf(n1, __shfl_xor_sync(0xffffffffu, n1, 1)); n1 = fmaxf(n1, __shfl_xor_sync(0xffffffffu, n1, 2));
        const float a0 = ex2_mufu(m0 - n0), a1 = ex2_mufu(m1 - n1);
        m0 = n0; m1 = n1;
#pragma unroll
        for (int i = 0; i < 3; i++) { o[4 * i] *= a0; o[4 * i + 1] *= a0; o[4 * i + 2] *= a1; o[4 * i + 3] *= a1; }
        const float e0 = n0 - LOG2C_ODD, e1 = n1 - LOG2C_ODD;
#pragma unroll
        for (int k = 0; k < 8; k++) {
            const int ba = 4 * k_pos(2 * k), bb = 4 * k_pos(2 * k + 1);
            const float f0 = is_poly_group(2 * k + 1) ? e0 : n0, f1 = is_poly_group(2 * k + 1) ? e1 : n1;
            const float g0 = is_poly_group(2 * k) ? e0 : n0, g1 = is_poly_group(2 * k) ? e1 : n1;
            const uint32_t p0 = pack_bf16(ex2_mufu(s[ba] - g0), ex2_mufu(s[ba + 1] - g0));
            const uint32_t p1 = pack_bf16(ex2_mufu(s[ba + 2] - g1), ex2_mufu(s[ba + 3] - g1));
            const uint32_t p2 = pack_bf16(ex2_mufu(s[bb] - f0), ex2_mufu(s[bb + 1] - f0));
            const uint32_t p3 = pack_bf16(ex2_mufu(s[bb + 2] - f1), ex2_mufu(s[bb + 3] - f1));
            wg_fence();
            wgmma_pv24(o, p0, p1, p2, p3, descV0 + (uint64_t)(off + k * 16));
            wg_commit();
            wg_wait<0>();
            pin(o);
        }
    }
#pragma unroll
    for (int i = 0; i < 8; i++) st[i * 128] = o[i];
    st[8 * 128] = o[8]; st[9 * 128] = o[10]; st[10 * 128] = m0; st[11 * 128] = m1;
}

__global__ void __launch_bounds__(512, 1)
mega_kernel(const __grid_constant__ CUtensorMap tmX, const __grid_constant__ CUtensorMap tmW,
            const __grid_constant__ CUtensorMap tmWo,
            const __grid_constant__ CUtensorMap tmG, const __grid_constant__ CUtensorMap tmU, const __grid_constant__ CUtensorMap tmOut,
            const __nv_bfloat16* __restrict__ x, const __nv_bfloat16* __restrict__ wqkv, const __nv_bfloat16* __restrict__ wo,
            const __nv_bfloat16* __restrict__ w_r, const __nv_bfloat16* __restrict__ w_gate,
            const __nv_bfloat16* __restrict__ w_up, const __nv_bfloat16* __restrict__ w_down,
            __nv_bfloat16* __restrict__ out) {
    extern __shared__ __align__(1024) char smem[];
    Misc& ms = *reinterpret_cast<Misc*>(smem + SM_MISC);
    const int tid = threadIdx.x, lane = tid & 31;
    const int warp = __shfl_sync(0xffffffffu, tid >> 5, 0);
    const int wg = warp >> 2, w4 = warp & 3, g = lane >> 2, t4 = lane & 3;
    const int cta = blockIdx.x;
    const int rb = cta >> 3, hg = cta & 7;

    if (warp == 12) {
        if (lane == 0) {
            TS(0);
            if (smem_u32(smem) & 1023) __trap();
            for (int i = 0; i < P1_STAGES; i++) { mbar_init(smem_u32(&ms.p1_full[i]), 1); mbar_init(smem_u32(&ms.p1_empty[i]), 8); }
            asm volatile("fence.mbarrier_init.release.cluster;" ::: "memory");
        }
        __syncwarp();
        bar_arrive(13, 288);
        bar_arrive(14, 256);
    } else {
        if (tid == 32) {
            for (int i = 0; i < 16; i++) mbar_init(smem_u32(&ms.kv[i]), 1);
            for (int i = 0; i < 8; i++) { mbar_init(smem_u32(&ms.wo[i]), 2); mbar_init(smem_u32(&ms.a3[i]), 32); }
            mbar_init(smem_u32(&ms.moe), 16);
            for (int i = 0; i < 16; i++) ms.freed[i] = 0;
            for (int i = 0; i < 8; i++) ms.seq[i] = 0;
            ms.item = 4;
            mbar_init(smem_u32(&ms.qbar), 1);
            asm volatile("fence.mbarrier_init.release.cluster;" ::: "memory");
        }
        if (tid >= 64 && tid < 76) ms.norm[tid - 64] = 0;
        if (tid >= 97 && tid < 101) {
            const CUtensorMap* tm = tid == 97 ? &tmWo : tid == 98 ? &tmG : tid == 99 ? &tmU : &tmOut;
            asm volatile("prefetch.tensormap [%0];" ::"l"(tm) : "memory");
        }
        if (tid == 416) ms.tag = __ldcg(&gEpoch) + 1u;
    }

    if (wg < 2) {
        asm volatile("setmaxnreg.inc.sync.aligned.u32 160;");
        float acc[96];
#pragma unroll
        for (int i = 0; i < 96; i++) acc[i] = 0.f;
        bar_sync(13, 288);
#pragma unroll
        for (int kc = 0; kc < 8; kc++) {
            const int s = kc % P1_STAGES;
            mbar_wait(smem_u32(&ms.p1_full[s]), (kc / P1_STAGES) & 1);
            if (tid == 0) TS(24 + kc);
            const uint32_t sa = smem_u32(smem + s * P1_STAGE_BYTES), sb = sa + 16384;
            const uint64_t da = make_desc(sa + wg * 8192, 16, 1024, 1);
            const uint64_t db = make_desc(sb, 8192, 1024, 1);
            wg_fence();
#pragma unroll
            for (int ks = 0; ks < 4; ks++) wgmma_n192(acc, da + ks * 2, db + ks * 128);
            wg_commit();
            wg_wait<1>();
            if (kc > 0 && lane == 0) mbar_arrive(smem_u32(&ms.p1_empty[(kc - 1) % P1_STAGES]));
        }
        wg_wait<0>();
        pin(acc);
        if (tid == 0) TS(1);
        bar_sync(1, 480);
        const unsigned int tag = ms.tag;
        if (tid == 0) TS(16);
        const int lr0 = wg * 64 + w4 * 16 + g, lr1 = lr0 + 8;
        const float mu0 = ms.p1.mu[lr0], mu1 = ms.p1.mu[lr1], rs0 = ms.p1.rs[lr0], rs1 = ms.p1.rs[lr1];
        const int lg0 = wg * 8 + w4 * 2;
        const int rg0 = rb * 16 + lg0;
        const float vsc = is_poly_group(lg0 + 1) ? VSCALE_ODD : 1.f, vsc0 = is_poly_group(lg0) ? VSCALE_ODD : 1.f;
        const int kp0 = k_pos(lg0) * 64, kp1 = k_pos(lg0 + 1) * 64;
#pragma unroll
        for (int hh = 0; hh < 4; hh++) {
            const int head = hg * 4 + hh;
            float nrm[3];
#pragma unroll
            for (int sec = 0; sec < 3; sec++) {
                float sq0 = 0.f, sq1 = 0.f, vm = 0.f;
#pragma unroll
                for (int db = 0; db < 2; db++) {
                    const int j = sec * 8 + hh * 2 + db;
                    const float2 c = *reinterpret_cast<const float2*>(&ms.p1.cs[j * 8 + 2 * t4]);
                    const float f0 = sec == 0 ? rs0 * QSCALE : rs0, f1 = sec == 0 ? rs1 * QSCALE : rs1;
                    const float a0 = (acc[4 * j + 0] - mu0 * c.x) * f0, a1 = (acc[4 * j + 1] - mu0 * c.y) * f0;
                    const float b0 = (acc[4 * j + 2] - mu1 * c.x) * f1, b1 = (acc[4 * j + 3] - mu1 * c.y) * f1;
                    const uint32_t pa = sec < 2 ? pack_f16_sat(a0, a1) : pack_bf16(a0 * vsc0, a1 * vsc0);
                    const uint32_t pb = sec < 2 ? pack_f16_sat(b0, b1) : pack_bf16(b0 * vsc, b1 * vsc);
                    if (sec < 2) {
                        if (sec == 0) {
                            uint32_t* dst = reinterpret_cast<uint32_t*>(gQ) + ((size_t)head * S_LEN * DH + rg0 * 128) / 2;
                            dst[db * 32 + lane] = pa;
                            dst[64 + db * 32 + lane] = pb;
                        } else {
                            uint32_t* dst = reinterpret_cast<uint32_t*>(gKV) + (size_t)(head * 16 + rb) * 2048;
                            dst[kp0 + db * 32 + lane] = pa;
                            dst[kp1 + db * 32 + lane] = pb;
                        }
                        sq0 = fmaf(a0, a0, fmaf(a1, a1, sq0));
                        sq1 = fmaf(b0, b0, fmaf(b1, b1, sq1));
                    } else {
                        uint32_t* dst = reinterpret_cast<uint32_t*>(gKV) + (size_t)(head * 16 + rb) * 2048 + 1024 + db * 512 + lg0 * 32;
                        dst[lane] = pa;
                        dst[32 + lane] = pb;
                        vm = fmaxf(vm, fmaxf(fmaxf(fabsf(a0), fabsf(a1)), fmaxf(fabsf(b0), fabsf(b1))));
                        if (!(a0 + a1 + b0 + b1 == a0 + a1 + b0 + b1)) vm = __int_as_float(0x7f800000);
                    }
                }
                if (sec < 2) {
                    sq0 += __shfl_xor_sync(0xffffffffu, sq0, 1); sq0 += __shfl_xor_sync(0xffffffffu, sq0, 2);
                    sq1 += __shfl_xor_sync(0xffffffffu, sq1, 1); sq1 += __shfl_xor_sync(0xffffffffu, sq1, 2);
                    vm = fmaxf(sq0, sq1);
                    if (!(sq0 + sq1 < 3.0e38f)) vm = __int_as_float(0x7f800000);
                }
                nrm[sec] = vm;
            }
            const unsigned int a = __reduce_max_sync(0xffffffffu, __float_as_uint(nrm[0]));
            const unsigned int b = __reduce_max_sync(0xffffffffu, __float_as_uint(nrm[1]));
            const unsigned int c = __reduce_max_sync(0xffffffffu, __float_as_uint(nrm[2]));
            if (lane == 0) { atomicMax(&ms.norm[hh * 3 + 0], a); atomicMax(&ms.norm[hh * 3 + 1], b); atomicMax(&ms.norm[hh * 3 + 2], c); }
        }
        if (tid == 0) TS(17);
        bar_sync(2, 256);
        if (tid == 0) TS(18);
        if (tid < 4) {
            fence_gpu();
            st_pkt(&gFlagQKV[(hg * 16 + rb) * 4 + tid], make_uint4(ms.norm[tid * 3], ms.norm[tid * 3 + 1], ms.norm[tid * 3 + 2], tag));
            if (tid == 0) TS(2);
        }
        asm volatile("setmaxnreg.dec.sync.aligned.u32 128;");
        bar_sync(15, 512);
    } else {
      asm volatile("setmaxnreg.dec.sync.aligned.u32 96;");
      if (wg == 2) {
        const int t = tid - 256;
        if (t < 4) gFlagQKV[(hg * 16 + rb) * 4 + t] = make_uint4(0u, 0u, 0u, 0u);
        bar_sync(14, 256);
        mbar_wait(smem_u32(&ms.p1_full[0]), 0);
        {
            const int row = rb * 128 + hg * 16 + (t >> 3), j = t & 7;
            const uint4* xp = reinterpret_cast<const uint4*>(x + (size_t)row * DM);
            uint4 v[8];
#pragma unroll
            for (int i = 0; i < 8; i++) v[i] = __ldg(xp + i * 8 + j);
            float s1 = 0.f;
#pragma unroll
            for (int i = 0; i < 8; i++) {
                const uint32_t w[4] = {v[i].x, v[i].y, v[i].z, v[i].w};
#pragma unroll
                for (int e = 0; e < 4; e++) s1 += bf_lo(w[e]) + bf_hi(w[e]);
            }
            s1 += __shfl_xor_sync(0xffffffffu, s1, 1); s1 += __shfl_xor_sync(0xffffffffu, s1, 2); s1 += __shfl_xor_sync(0xffffffffu, s1, 4);
            const float mu = s1 * (1.f / DM);
            float s2 = 0.f;
#pragma unroll
            for (int i = 0; i < 8; i++) {
                const uint32_t w[4] = {v[i].x, v[i].y, v[i].z, v[i].w};
#pragma unroll
                for (int e = 0; e < 4; e++) {
                    const float a = bf_lo(w[e]) - mu, b = bf_hi(w[e]) - mu;
                    s2 = fmaf(a, a, fmaf(b, b, s2));
                }
            }
            s2 += __shfl_xor_sync(0xffffffffu, s2, 1); s2 += __shfl_xor_sync(0xffffffffu, s2, 2); s2 += __shfl_xor_sync(0xffffffffu, s2, 4);
            bar_sync(11, 224);
            if (j == 0) st_pkt(&gStat1[row], make_uint4(__float_as_uint(mu), __float_as_uint(rsqrtf(s2 * (1.f / DM) + LN_EPS)), 0u, ms.tag));
        }
        const unsigned int tag = ms.tag;
        if (t == 0) TS(32);
        mbar_wait(smem_u32(&ms.p1_full[2]), 1);
        uint4 st[1];
        wait_pkts<1, 0xffffffffu>(&gStat1[rb * 128 + t], 0, tag, st);
        if (t == 0) TS(34);
        ms.p1.mu[t] = __uint_as_float(st[0].x);
        ms.p1.rs[t] = __uint_as_float(st[0].y);
        bar_arrive(1, 480);
        {
            const uint4 z = make_uint4(0u, 0u, 0u, 0u);
            if (t < 64) { gCand[cta * 64 + t] = z; gPart[cta * 64 + t] = z; gCandRow[cta * 64 + t] = z; }
            gYPart[cta * 224 + t] = z;
            if (t < 96) gYPart[cta * 224 + 128 + t] = z;
            if (t < 2) {
                reinterpret_cast<uint4*>(gFlagOut)[cta * 2 + t] = z;
            }
        }
      } else if (warp == 12) {
        if (lane == 0) {
#pragma unroll 1
            for (int kc = 0; kc < 8; kc++) {
                const int s = kc % P1_STAGES;
                if (kc >= P1_STAGES) mbar_wait(smem_u32(&ms.p1_empty[s]), 0);
                const uint32_t bar = smem_u32(&ms.p1_full[s]);
                const uint32_t sa = smem_u32(smem + s * P1_STAGE_BYTES), sb = sa + 16384;
                mbar_expect_tx(bar, P1_STAGE_BYTES);
                tma_2d(sa, &tmX, kc * 64, rb * 128, bar);
#pragma unroll
                for (int p = 0; p < 3; p++) tma_2d(sb + p * 8192, &tmW, p * 512 + hg * 64, kc * 64, bar);
            }
        }
      } else {
        const int t = tid - 416;
        bar_sync(14, 256);
        mbar_wait(smem_u32(&ms.p1_full[0]), 0);
        const int c16 = t >> 2, rs = t & 3;
        const __nv_bfloat16* wp = wqkv + (size_t)(rb * 32 + rs) * (3 * DM) + (c16 >> 3) * 512 + hg * 64 + (c16 & 7) * 8;
        uint4 v[8];
#pragma unroll
        for (int i = 0; i < 8; i++) v[i] = __ldg(reinterpret_cast<const uint4*>(wp + (size_t)i * 4 * (3 * DM)));
        float a[8] = {};
#pragma unroll
        for (int i = 0; i < 8; i++) {
            a[0] += bf_lo(v[i].x); a[1] += bf_hi(v[i].x); a[2] += bf_lo(v[i].y); a[3] += bf_hi(v[i].y);
            a[4] += bf_lo(v[i].z); a[5] += bf_hi(v[i].z); a[6] += bf_lo(v[i].w); a[7] += bf_hi(v[i].w);
        }
#pragma unroll
        for (int e = 0; e < 8; e++) { a[e] += __shfl_xor_sync(0xffffffffu, a[e], 1); a[e] += __shfl_xor_sync(0xffffffffu, a[e], 2); }
        bar_sync(11, 224);
        const unsigned int tag = ms.tag;
        const int pk = c16 * 2 + rs;
        if (rs < 2) st_pkt(&gCsPart[(hg * 16 + rb) * 48 + pk], embed_tag(rs ? a[4] : a[0], rs ? a[5] : a[1], rs ? a[6] : a[2], rs ? a[7] : a[3], tag));
        if (t == 0) TS(35);
        if (t < 16) { uint4 gate[1]; wait_pkts4<1>(&gCsPart[(hg * 16 + t) * 48 + 47], 0, tag, gate); }
        bar_sync(8, 96);
        if (t == 0) TS(36);
        {
            const int pq = c16 * 2 + (rs & 1);
            uint4 p[8];
            wait_pkts4<8>(&gCsPart[(hg * 16 + (rs >> 1) * 8) * 48 + pq], 48, tag, p);
            float s0 = 0.f, s1 = 0.f, s2 = 0.f, s3 = 0.f;
#pragma unroll
            for (int i = 0; i < 8; i++) {
                s0 += __uint_as_float(p[i].x); s1 += __uint_as_float(p[i].y); s2 += __uint_as_float(p[i].z); s3 += __uint_as_float(p[i].w);
            }
            s0 += __shfl_xor_sync(0xffffffffu, s0, 2); s1 += __shfl_xor_sync(0xffffffffu, s1, 2);
            s2 += __shfl_xor_sync(0xffffffffu, s2, 2); s3 += __shfl_xor_sync(0xffffffffu, s3, 2);
            if (rs < 2) *reinterpret_cast<float4*>(&ms.p1.cs[pq * 4]) = make_float4(s0, s1, s2, s3);
            if (t == 0) TS(37);
        }
        __syncwarp();
        bar_arrive(1, 480);
      }
      __syncwarp();
      bar_sync(15, 512);
      asm volatile("setmaxnreg.inc.sync.aligned.u32 128;");
    }
    if (tid == 0) TS(20);
    const unsigned int tag = ms.tag;

    const int head = hg * 4 + (rb >> 2), quarter = rb & 3;
    {
#pragma unroll
        for (int i = 0; i < 4; i++) {
            const int e = tid + i * 512;
            *reinterpret_cast<uint4*>(smem + (e >> 7) * KV_CHUNK + 8192 + (e & 127) * 16) = make_uint4(is_poly_group((e & 127) >> 3) ? 0x00003F35u : 0x00003F80u, 0, 0, 0);
        }
        asm volatile("fence.proxy.async.shared::cta;" ::: "memory");
    }
    if (warp == 0) {
        uint4 n[1];
        wait_pkts<1, 0xffffffffu>(&gFlagQKV[(hg * 16 + (lane & 15)) * 4 + (rb >> 2)], 0, tag, n);
        __syncwarp();
        if (lane == 0) TS(21);
        const float q2 = __uint_as_float(__reduce_max_sync(0xffffffffu, n[0].x));
        const float k2 = __uint_as_float(__reduce_max_sync(0xffffffffu, n[0].y));
        const float vm = __uint_as_float(__reduce_max_sync(0xffffffffu, n[0].z));
        if (lane == 0) ms.fast = (q2 * k2 * 1.02f <= 812.f) && (q2 <= 1.0e6f) && (k2 <= 1.0e6f) && (vm <= 1.0e18f) && (vm >= 1.0e-18f || vm == 0.f);
    }
    __syncthreads();
    auto load_kv_chunk = [&](int j) {
        fence_proxy_async_global();
        const uint32_t bar = smem_u32(&ms.kv[j]);
        mbar_expect_tx(bar, 8192);
        bulk_g2s(smem_u32(smem + j * KV_CHUNK), reinterpret_cast<const char*>(gKV) + (size_t)(head * 16 + j) * 8192, 8192, bar);
    };
    if (lane == 0) {
        if (warp == 5) {
            fence_proxy_async_global();
            mbar_expect_tx(smem_u32(&ms.qbar), 16384);
            bulk_g2s(smem_u32(smem + SM_Q), reinterpret_cast<const char*>(gQ) + (size_t)head * 65536 + quarter * 16384, 16384, smem_u32(&ms.qbar));
        }
        if (warp < 5) load_kv_chunk(warp);
    }
    __syncwarp();
    if (tid == 0) TS(3);
    bool refilled = false;
    {
        const bool fast = ms.fast != 0;
        const uint64_t descKe = make_desc(smem_u32(smem), 128, 256, 0);
        const uint64_t descKo = make_desc(smem_u32(smem) + NMG * 256, 128, 256, 0);
        const uint64_t descV0 = make_desc(smem_u32(smem + 4096), 128, 2048, 0);
        auto release_chunk = [&](int j) { release_kv_chunk(ms, j, lane); };
        float* sAcc = reinterpret_cast<float*>(smem + SM_A3);
        const int t128 = tid & 127;
        mbar_wait(smem_u32(&ms.qbar), 0);
        auto run_items = [&](auto FAST) {
        int item = wg * NR;
#pragma unroll 1
        while (item < 8 * NR) {
            const int r = item % NR, t = item / NR;
            if (t128 == 0) ms.nxt[wg] = ((item % NR) == NR - 1) ? item + 3 * NR + 1 : item + 1;
            if (r > 0) {
                int it = 0;
                unsigned int sq;
                while (true) {
                    asm volatile("ld.acquire.cta.shared.u32 %0, [%1];" : "=r"(sq) : "r"(smem_u32(&ms.seq[t])) : "memory");
                    if (sq >= (unsigned int)r) break;
                    if (++it > SPIN_LIMIT) __trap();
                }
            }
            uint32_t q[4];
            {
                const uint32_t* Qs = reinterpret_cast<const uint32_t*>(smem + SM_Q + t * 2048 + w4 * 512);
                q[0] = Qs[lane]; q[2] = Qs[32 + lane]; q[1] = Qs[64 + lane]; q[3] = Qs[96 + lane];
            }
            float* st = sAcc + t * (12 * 128) + t128;
            float o[12];
#pragma unroll
            for (int i = 0; i < 8; i++) o[i] = r > 0 ? st[i * 128] : 0.f;
            o[8] = r > 0 ? st[8 * 128] : 0.f; o[10] = r > 0 ? st[9 * 128] : 0.f; o[9] = 0.f; o[11] = 0.f;
            if constexpr (decltype(FAST)::value) {
#pragma unroll 1
                for (int j = CPI * r; j < CPI * (r + 1); j++) {
                    if (t < 4 && warp == j + 5 && lane == 0) load_kv_chunk(warp);
                    __syncwarp();
                    mbar_wait(smem_u32(&ms.kv[j]), 0);
                    float s[NMG * 4];
                    uint32_t h[NPG * 2];
                    const uint32_t vlo = (uint32_t)descV0 + j * (KV_CHUNK >> 4);
                    wg_fence();
                    wgmma_qk_f32(s, q, descKe + (uint64_t)(j * (KV_CHUNK >> 4)));
                    wgmma_qk_f16(h, q, descKo + (uint64_t)(j * (KV_CHUNK >> 4)));
                    wg_commit();
                    wg_wait<0>();
                    pin(s);
                    pin(h);
                    if (t >= 4) {
                        if (j > 0) release_chunk(j - 1);
                        if (!refilled && j > warp) refilled = refill_kv_chunk(smem, ms, warp, cta, lane, &tmWo, &tmG, &tmU);
                    }
#pragma unroll
                    for (int kg = 0; kg < 8 / PVG; kg++) {
                        uint32_t p[4 * PVG];
#pragma unroll
                        for (int u = 0; u < PVG; u++) {
                            const int k = kg * PVG + u;
#pragma unroll
                            for (int hf = 0; hf < 2; hf++) {
                                const int L = 2 * k + hf, gi = g_idx(L);
                                if (is_poly_group(L)) {
                                    p[4 * u + 2 * hf] = ex2_pair_h16(h[2 * (gi < NPG ? gi : 0)]);
                                    p[4 * u + 2 * hf + 1] = ex2_pair_h16(h[2 * (gi < NPG ? gi : 0) + 1]);
                                } else {
                                    const int b = 4 * (gi < NMG ? gi : 0);
                                    p[4 * u + 2 * hf] = pack_bf16(ex2_mufu(s[b]), ex2_mufu(s[b + 1]));
                                    p[4 * u + 2 * hf + 1] = pack_bf16(ex2_mufu(s[b + 2]), ex2_mufu(s[b + 3]));
                                }
                            }
                        }
                        wg_fence();
#pragma unroll
                        for (int u = 0; u < PVG; u++)
                            wgmma_pv24_lh(o, p[4 * u], p[4 * u + 1], p[4 * u + 2], p[4 * u + 3], vlo + (kg * PVG + u) * 16, (uint32_t)(descV0 >> 32));
                        wg_commit();
                        wg_wait<PVWAIT>();
                    }
                }
                wg_wait<0>();
                pin(o);
            } else {
                guarded_item(smem, ms, r, t, warp, load_kv_chunk);
#pragma unroll
                for (int i = 0; i < 8; i++) o[i] = st[i * 128];
                o[8] = st[8 * 128]; o[10] = st[9 * 128];
            }
            if (t >= 4) release_chunk(15);
            if (r < NR - 1) {
#pragma unroll
                for (int i = 0; i < 8; i++) st[i * 128] = o[i];
                st[8 * 128] = o[8]; st[9 * 128] = o[10];
            } else {
                const float l0 = __shfl_sync(0xffffffffu, o[8], lane & ~3), l1 = __shfl_sync(0xffffffffu, o[10], lane & ~3);
                const float r0 = __fdividef(1.f, l0), r1 = __fdividef(1.f, l1);
                uint32_t* Op = &gO[tag & 1][(size_t)(quarter * 512 + t * 64 + w4 * 16) * (DM / 2) + head * (DH / 2)];
                st_word_nz(Op + g * 256 + t4, pack_bf16(o[0] * r0, o[1] * r0));
                st_word_nz(Op + (g + 8) * 256 + t4, pack_bf16(o[2] * r1, o[3] * r1));
                st_word_nz(Op + g * 256 + 4 + t4, pack_bf16(o[4] * r0, o[5] * r0));
                st_word_nz(Op + (g + 8) * 256 + 4 + t4, pack_bf16(o[6] * r1, o[7] * r1));
            }
            bar_sync(3 + wg, 128);
            if (t128 == 0) asm volatile("st.release.cta.shared.u32 [%0], %1;" ::"r"(smem_u32(&ms.seq[t])), "r"(r + 1) : "memory");
            if (t < 4) {
                const int row = quarter * 512 + (t + (t128 >> 6) * 4) * 64 + (t128 & 63);
                uint4* zp = reinterpret_cast<uint4*>(&gO[(tag & 1) ^ 1][(size_t)row * (DM / 2) + head * (DH / 2)]);
                zp[0] = make_uint4(0u, 0u, 0u, 0u); zp[1] = make_uint4(0u, 0u, 0u, 0u);
            }
            if (r == 0 && t == 3 && tid == 511) {
                bulk_prefetch_l2(reinterpret_cast<const char*>(w_down) + cta * 14336, 14336);
            }
            if (t128 == 0) TS(40 + wg + (t >= 4 ? 4 : 0));
            item = ms.nxt[wg];
            bar_sync(3 + wg, 128);
        }
        };
        if (fast) run_items(std::true_type{}); else run_items(std::false_type{});
    }
    __syncthreads();
    if (!refilled) refill_kv_chunk(smem, ms, warp, cta, lane, &tmWo, &tmG, &tmU);
    if (tid == 0) TS(4);

    const int rb3 = cta >> 2, cb = cta & 3;
    if (wg < 2) {
        const int r0 = rb3 * 64 + w4 * 16 + g, r1 = r0 + 8;
        const int col0 = cb * 128 + wg * 64 + 2 * t4;
        uint32_t xa[8], xb[8], wr[8];
#pragma unroll
        for (int j = 0; j < 8; j++) {
            xa[j] = __ldg(reinterpret_cast<const uint32_t*>(x + (size_t)r0 * DM + col0 + j * 8));
            xb[j] = __ldg(reinterpret_cast<const uint32_t*>(x + (size_t)r1 * DM + col0 + j * 8));
            wr[j] = __ldg(reinterpret_cast<const uint32_t*>(w_r + col0 + j * 8));
        }
        const float p0 = __bfloat162float(x[(size_t)r0 * DM]), p1 = __bfloat162float(x[(size_t)r1 * DM]);
        const float pivot = __bfloat162float(x[(size_t)(rb3 * 64 + (tid >> 2)) * DM]);
        float wsum = 0.f;
        {
            const uint4 a = __ldg(reinterpret_cast<const uint4*>(w_r) + lane), b = __ldg(reinterpret_cast<const uint4*>(w_r) + 32 + lane);
            const uint32_t w[8] = {a.x, a.y, a.z, a.w, b.x, b.y, b.z, b.w};
#pragma unroll
            for (int e = 0; e < 8; e++) wsum += bf_lo(w[e]) + bf_hi(w[e]);
#pragma unroll
            for (int m = 16; m; m >>= 1) wsum += __shfl_xor_sync(0xffffffffu, wsum, m);
        }
        float acc[32];
#pragma unroll
        for (int i = 0; i < 32; i++) acc[i] = 0.f;
#pragma unroll 1
        for (int kc = 0; kc < 8; kc++) {
            mbar_wait(smem_u32(&ms.wo[kc]), 0);
            mbar_wait(smem_u32(&ms.a3[kc]), 0);
            const uint64_t da = make_desc(smem_u32(smem + SM_A3 + kc * 8192), 16, 1024, 1);
            const uint64_t db = make_desc(smem_u32(smem + (kc * 2 + wg) * KV_CHUNK), 8192, 1024, 1);
            wg_fence();
#pragma unroll
            for (int ks = 0; ks < 4; ks++) wgmma_n64(acc, da + ks * 2, db + ks * 128);
            wg_commit();
        }
        wg_wait<0>();
        pin(acc);
        if (tid == 0) TS(6);
        float s1a = 0.f, s2a = 0.f, s3a = 0.f, s1b = 0.f, s2b = 0.f, s3b = 0.f;
#pragma unroll
        for (int j = 0; j < 8; j++) {
            const uint32_t ha = pack_bf16(bf_lo(xa[j]) + acc[4 * j], bf_hi(xa[j]) + acc[4 * j + 1]);
            const uint32_t hb = pack_bf16(bf_lo(xb[j]) + acc[4 * j + 2], bf_hi(xb[j]) + acc[4 * j + 3]);
            xa[j] = ha; xb[j] = hb;
            const float w0 = bf_lo(wr[j]), w1 = bf_hi(wr[j]);
            const float da0 = bf_lo(ha) - p0, da1 = bf_hi(ha) - p0, db0 = bf_lo(hb) - p1, db1 = bf_hi(hb) - p1;
            s1a += da0 + da1; s2a = fmaf(da0, da0, fmaf(da1, da1, s2a)); s3a = fmaf(da0, w0, fmaf(da1, w1, s3a));
            s1b += db0 + db1; s2b = fmaf(db0, db0, fmaf(db1, db1, s2b)); s3b = fmaf(db0, w0, fmaf(db1, w1, s3b));
        }
#pragma unroll
        for (int m = 1; m <= 2; m <<= 1) {
            s1a += __shfl_xor_sync(0xffffffffu, s1a, m); s2a += __shfl_xor_sync(0xffffffffu, s2a, m); s3a += __shfl_xor_sync(0xffffffffu, s3a, m);
            s1b += __shfl_xor_sync(0xffffffffu, s1b, m); s2b += __shfl_xor_sync(0xffffffffu, s2b, m); s3b += __shfl_xor_sync(0xffffffffu, s3b, m);
        }
        if (t4 == 0) {
            const int lr = w4 * 16 + g;
            ms.p3.part[wg][lr][0] = s1a; ms.p3.part[wg][lr][1] = s2a; ms.p3.part[wg][lr][2] = s3a;
            ms.p3.part[wg][lr + 8][0] = s1b; ms.p3.part[wg][lr + 8][1] = s2b; ms.p3.part[wg][lr + 8][2] = s3b;
        }
        if (tid == 0) TS(11);
        bar_sync(1, 256);
        if (tid == 0) TS(12);
        if (tid < 64) {
            st_pkt(&gPart[(rb3 * 64 + tid) * 4 + cb],
                   make_uint4(__float_as_uint(ms.p3.part[0][tid][0] + ms.p3.part[1][tid][0]), __float_as_uint(ms.p3.part[0][tid][1] + ms.p3.part[1][tid][1]),
                              __float_as_uint(ms.p3.part[0][tid][2] + ms.p3.part[1][tid][2]), tag));
        }
        {
            const int lr = tid >> 2, sl = tid & 3;
            uint4 pv[1];
            wait_pkts<1, 0xffffffffu>(&gPart[rb3 * 256 + tid], 0, tag, pv);
            float s1 = __uint_as_float(pv[0].x), s2 = __uint_as_float(pv[0].y), s3 = __uint_as_float(pv[0].z);
            if (tid == 0) TS(14);
#pragma unroll
            for (int m = 1; m <= 2; m <<= 1) {
                s1 += __shfl_xor_sync(0xffffffffu, s1, m); s2 += __shfl_xor_sync(0xffffffffu, s2, m); s3 += __shfl_xor_sync(0xffffffffu, s3, m);
            }
            if (sl == 0) {
                const float md = s1 * (1.f / DM);
                const float var = fmaxf(s2 * (1.f / DM) - md * md, 0.f);
                const float rs = rsqrtf(var + LN_EPS);
                ms.p3.mu[lr] = pivot + md;
                ms.p3.rs[lr] = rs;
                ms.p3.r[lr] = (s3 - md * wsum) * rs;
            }
        }
        bar_sync(1, 256);
        if (tid == 0) TS(7);
        {
            unsigned int i1, i2;
            warp_top2(f2ord(ms.p3.r[lane]), lane, f2ord(ms.p3.r[lane + 32]), lane + 32, i1, i2);
            if (cb == 0) {
                const int c = tid & 1, li = c ? i2 : i1;
                st_pkt(&gCand[(tid >> 1) * 64 + rb3 * 2 + c],
                       make_uint4(__float_as_uint(ms.p3.r[li]), __float_as_uint(ms.p3.mu[li]), __float_as_uint(ms.p3.rs[li]),
                                  (tag << 11) | (unsigned int)(rb3 * 64 + li)));
            }
#pragma unroll
            for (int c = 0; c < 2; c++) {
                const unsigned int li = c ? i2 : i1;
                if ((int)(li >> 4) == w4 && (int)(li & 7) == g) {
                    const bool hi = (li & 8) != 0;
                    uint4* dst = &gCandRow[(rb3 * 2 + c) * 128 + (cb * 2 + wg) * 16 + t4];
#pragma unroll
                    for (int q = 0; q < 4; q++)
                        st_pkt(dst + q * 4, make_uint4(hi ? xb[2 * q] : xa[2 * q], hi ? xb[2 * q + 1] : xa[2 * q + 1], 0u, tag));
                }
            }
            if (tid == 0) TS(15);
        }
        {
            const int lr0 = w4 * 16 + g;
            const float mu0 = ms.p3.mu[lr0], rs0 = ms.p3.rs[lr0], mu1 = ms.p3.mu[lr0 + 8], rs1 = ms.p3.rs[lr0 + 8];
            char* so = smem + wg * KV_CHUNK;
#pragma unroll
            for (int j = 0; j < 8; j++) {
                const float a0 = bf_lo(xa[j]), a1 = bf_hi(xa[j]), b0 = bf_lo(xb[j]), b1 = bf_hi(xb[j]);
                const uint32_t la = pack_bf16((a0 - mu0) * rs0, (a1 - mu0) * rs0);
                const uint32_t lb = pack_bf16((b0 - mu1) * rs1, (b1 - mu1) * rs1);
                const int o = ((j ^ g) << 4) + t4 * 4;
                *reinterpret_cast<uint32_t*>(so + lr0 * 128 + o) = pack_bf16(a0 + bf_lo(la), a1 + bf_hi(la));
                *reinterpret_cast<uint32_t*>(so + (lr0 + 8) * 128 + o) = pack_bf16(b0 + bf_lo(lb), b1 + bf_hi(lb));
            }
            asm volatile("fence.proxy.async.shared::cta;" ::: "memory");
            bar_sync(3 + wg, 128);
            if ((tid & 127) == 0) {
                tma_store_2d(&tmOut, smem_u32(so), cb * 128 + wg * 64, rb3 * 64);
                asm volatile("cp.async.bulk.wait_group 0;" ::: "memory");
                st_flag(&gFlagOut[cta * 8 + wg], tag);
            }
        }
    } else {
        const int t = tid - 256;
        {
            const int c16 = t & 63, kc = c16 >> 3, r4 = t >> 6;
            const uint4* src16 = reinterpret_cast<const uint4*>(&gO[tag & 1][(size_t)(rb3 * 64 + r4) * (DM / 2)]) + c16;
            char* dst = smem + SM_A3 + kc * 8192;
            unsigned int pending = 0xffffu;
            int it = 0;
            while (pending) {
                uint4 v[16];
#pragma unroll
                for (int k = 0; k < 16; k++)
                    if (pending & (1u << k)) v[k] = ld_pkt(src16 + (size_t)k * 4 * (DM / 8));
#pragma unroll
                for (int k = 0; k < 16; k++) {
                    if ((pending & (1u << k)) && v[k].x && v[k].y && v[k].z && v[k].w) {
                        const int row = r4 + 4 * k;
                        *reinterpret_cast<uint4*>(dst + row * 128 + (((c16 & 7) ^ (row & 7)) << 4)) = v[k];
                        pending &= ~(1u << k);
                    }
                }
                if (++it > SPIN_LIMIT) __trap();
                if (pending) BACKOFF();
            }
            asm volatile("fence.proxy.async.shared::cta;" ::: "memory");
            mbar_arrive(smem_u32(&ms.a3[kc]));
            if (t == 255) TS(5);
        }
        uint32_t wd[16];
        if (cta < NFFN) {
#pragma unroll
            for (int k = 0; k < 16; k++) wd[k] = __ldg(reinterpret_cast<const uint32_t*>(w_down + (size_t)(cta * 16 + k) * DM + 2 * t));
        }
        if (warp == 8) {
            if (lane == 0) TS(56);
            uint4 cv[2];
            wait_pkts<2, 0xfffff800u>(&gCand[cta * 64 + lane * 2], 1, tag << 11, cv);
            if (lane == 0) TS(54);
            unsigned int i1, i2;
            warp_top2(f2ord(__uint_as_float(cv[0].x)), cv[0].w & 0x7ffu, f2ord(__uint_as_float(cv[1].x)), cv[1].w & 0x7ffu, i1, i2);
#pragma unroll
            for (int c = 0; c < 2; c++) {
                const unsigned int ci = cv[c].w & 0x7ffu;
                if (ci == i1 || ci == i2) {
                    const int o = ci == i1 ? 0 : 1;
                    ms.idx[o] = (int)ci;
                    ms.cslot[o] = lane * 2 + c;
                    *reinterpret_cast<float4*>(&ms.sel[o * 4]) =
                        make_float4(__uint_as_float(cv[c].y), __uint_as_float(cv[c].z), __fdividef(1.f, 1.f + __expf(-__uint_as_float(cv[c].x))), 0.f);
                }
            }
            if (lane == 0) TS(8);
        }
        bar_sync(2, 256);
        const int idx0 = ms.idx[0], idx1 = ms.idx[1];
        if (t == 0 && idx0 >= 0) TS(61);
        float* sX = reinterpret_cast<float*>(smem + SM_A3);
        float* sH = sX + 1024;
        float* sPart = sX + 2048;
        float* sAct = sPart + 512;
        if (cta < NFFN) {
            {
                const int tk = t >> 7, P = t & 127;
                uint4 hv[1];
                wait_pkts<1, 0xffffffffu>(&gCandRow[ms.cslot[tk] * 128 + P], 0, tag, hv);
                if (t == 0) TS(57);
                const float mu = ms.sel[tk * 4], rs = ms.sel[tk * 4 + 1];
                const int col = (P >> 4) * 64 + ((P >> 2) & 3) * 16 + (P & 3) * 2;
                const uint32_t l0 = pack_bf16((bf_lo(hv[0].x) - mu) * rs, (bf_hi(hv[0].x) - mu) * rs);
                const uint32_t l1 = pack_bf16((bf_lo(hv[0].y) - mu) * rs, (bf_hi(hv[0].y) - mu) * rs);
                *reinterpret_cast<float2*>(&sX[tk * 512 + col]) = make_float2(bf_lo(l0), bf_hi(l0));
                *reinterpret_cast<float2*>(&sX[tk * 512 + col + 8]) = make_float2(bf_lo(l1), bf_hi(l1));
                *reinterpret_cast<float2*>(&sH[tk * 512 + col]) = make_float2(bf_lo(hv[0].x), bf_hi(hv[0].x));
                *reinterpret_cast<float2*>(&sH[tk * 512 + col + 8]) = make_float2(bf_lo(hv[0].y), bf_hi(hv[0].y));
            }
            mbar_wait(smem_u32(&ms.moe), 0);
            bar_sync(1 + 8, 256);
            if (t == 0) { asm volatile("" ::: "memory"); sAct[40] = sX[0]; TS(58); }
            {
                const int wv = warp - 8, kk = lane >> 3, cp = lane & 7;
                float a[2][2][2] = {};
#pragma unroll
                for (int i = 0; i < 16; i++) {
                    const int k = wv * 64 + i * 4 + kk;
                    const float x0 = sX[k], x1 = sX[512 + k];
#pragma unroll
                    for (int mat = 0; mat < 2; mat++) {
                        const uint32_t w = *reinterpret_cast<const uint32_t*>(smem + (mat * 8 + wv) * KV_CHUNK + 8192 + (i * 4 + kk) * 32 + cp * 4);
                        a[mat][0][0] = fmaf(x0, bf_lo(w), a[mat][0][0]); a[mat][0][1] = fmaf(x0, bf_hi(w), a[mat][0][1]);
                        a[mat][1][0] = fmaf(x1, bf_lo(w), a[mat][1][0]); a[mat][1][1] = fmaf(x1, bf_hi(w), a[mat][1][1]);
                    }
                }
#pragma unroll
                for (int mat = 0; mat < 2; mat++)
#pragma unroll
                    for (int tk = 0; tk < 2; tk++)
#pragma unroll
                        for (int e = 0; e < 2; e++) {
                            float v = a[mat][tk][e];
                            v += __shfl_xor_sync(0xffffffffu, v, 8);
                            v += __shfl_xor_sync(0xffffffffu, v, 16);
                            if (kk == 0) sPart[(wv * 2 + tk) * 32 + mat * 16 + 2 * cp + e] = v;
                        }
            }
            bar_sync(1 + 8, 256);
            if (t == 0) { sAct[41] = sPart[0]; TS(59); }
            if (t < 32) {
                const int tk = t >> 4, c = t & 15;
                float gs = 0.f, us = 0.f;
#pragma unroll
                for (int w = 0; w < 8; w++) { gs += sPart[(w * 2 + tk) * 32 + c]; us += sPart[(w * 2 + tk) * 32 + 16 + c]; }
                const float gb = bf_round(gs), ub = bf_round(us);
                const float sl = bf_round(__fdividef(gb, 1.f + __expf(-gb)));
                sAct[tk * 16 + c] = bf_round(sl * ub);
            }
            bar_sync(1 + 8, 256);
            {
                float y00 = 0.f, y01 = 0.f, y10 = 0.f, y11 = 0.f;
#pragma unroll
                for (int k = 0; k < 16; k++) {
                    const float a0 = sAct[k], a1 = sAct[16 + k];
                    y00 = fmaf(a0, bf_lo(wd[k]), y00); y01 = fmaf(a0, bf_hi(wd[k]), y01);
                    y10 = fmaf(a1, bf_lo(wd[k]), y10); y11 = fmaf(a1, bf_hi(wd[k]), y11);
                }
                st_pkt(&gYPart[((t >> 2) * NFFN + cta) * 4 + (t & 3)], embed_tag(y00, y01, y10, y11, tag));
            }
            if (t == 0) TS(9);
        }
        if (cta < 64) {
            const int pc = t & 3, part = t >> 2;
            const int opc = (t >> 2) & 3, oe = t & 3, otk = oe >> 1, ocol = (cta * 4 + opc) * 2 + (oe & 1);
            float y[4] = {0.f, 0.f, 0.f, 0.f};
            if (part < 56) {
                uint4 yv[2];
                wait_pkts4<2>(&gYPart[(cta * NFFN + part) * 4 + pc], 56 * 4, tag, yv);
                if (t == 0) TS(60);
                y[0] = __uint_as_float(yv[0].x) + __uint_as_float(yv[1].x); y[1] = __uint_as_float(yv[0].y) + __uint_as_float(yv[1].y);
                y[2] = __uint_as_float(yv[0].z) + __uint_as_float(yv[1].z); y[3] = __uint_as_float(yv[0].w) + __uint_as_float(yv[1].w);
            }
            if (t >= 224 && t < 226) {
                const int orow = (t & 1) ? idx1 : idx0, oc = cta * 8;
                wait_flag(&gFlagOut[((orow >> 6) * 4 + (oc >> 7)) * 8 + ((oc >> 6) & 1)], tag);
            }
            __syncwarp();
#pragma unroll
            for (int e = 0; e < 4; e++) {
                y[e] += __shfl_xor_sync(0xffffffffu, y[e], 4); y[e] += __shfl_xor_sync(0xffffffffu, y[e], 8); y[e] += __shfl_xor_sync(0xffffffffu, y[e], 16);
            }
            float* sR = sAct + 32;
            if (lane < 4) *reinterpret_cast<float4*>(&sR[(warp - 8) * 16 + lane * 4]) = make_float4(y[0], y[1], y[2], y[3]);
            bar_sync(1 + 8, 256);
            if (t < 16) {
                float s = 0.f;
#pragma unroll
                for (int w = 0; w < 8; w++) s += sR[w * 16 + t];
                const float yb = bf_round(bf_round(s) * ms.sel[otk * 4 + 2]);
                out[(size_t)(otk ? idx1 : idx0) * DM + ocol] = __float2bfloat16(sH[otk * 512 + ocol] + bf_round(sX[otk * 512 + ocol] + yb));
            }
            if (cta == 0 && t == 0) {
                *reinterpret_cast<volatile unsigned int*>(&gEpoch) = tag;
            }
            if (t == 0) TS(10);
        }
    }
}

typedef CUresult (*EncodeFn)(CUtensorMap*, CUtensorMapDataType, cuuint32_t, void*, const cuuint64_t*, const cuuint64_t*,
                             const cuuint32_t*, const cuuint32_t*, CUtensorMapInterleave, CUtensorMapSwizzle,
                             CUtensorMapL2promotion, CUtensorMapFloatOOBfill);

void make_map(EncodeFn enc, CUtensorMap* tm, const void* base, uint64_t cols, uint64_t rows, uint32_t box_c, uint32_t box_r, bool swz) {
    cuuint64_t dims[2] = {cols, rows};
    cuuint64_t strides[1] = {cols * 2};
    cuuint32_t box[2] = {box_c, box_r};
    cuuint32_t es[2] = {1, 1};
    enc(tm, CU_TENSOR_MAP_DATA_TYPE_BFLOAT16, 2, const_cast<void*>(base), dims, strides, box, es, CU_TENSOR_MAP_INTERLEAVE_NONE,
        swz ? CU_TENSOR_MAP_SWIZZLE_128B : CU_TENSOR_MAP_SWIZZLE_NONE, CU_TENSOR_MAP_L2_PROMOTION_L2_256B,
        CU_TENSOR_MAP_FLOAT_OOB_FILL_NONE);
}

}

extern "C" void kernel_launch(void* const* d_in, const int* in_sizes, int n_in, void* d_out, int out_size) {
    const __nv_bfloat16* x = (const __nv_bfloat16*)d_in[0];
    const __nv_bfloat16* wqkv = (const __nv_bfloat16*)d_in[1];
    const __nv_bfloat16* wo = (const __nv_bfloat16*)d_in[2];
    const __nv_bfloat16* w_r = (const __nv_bfloat16*)d_in[4];
    const __nv_bfloat16* w_gate = (const __nv_bfloat16*)d_in[5];
    const __nv_bfloat16* w_up = (const __nv_bfloat16*)d_in[6];
    const __nv_bfloat16* w_down = (const __nv_bfloat16*)d_in[7];
    __nv_bfloat16* out = (__nv_bfloat16*)d_out;

    static EncodeFn enc = nullptr;
    if (!enc) {
        void* fn = nullptr;
        cudaDriverEntryPointQueryResult qr;
        cudaGetDriverEntryPoint("cuTensorMapEncodeTiled", &fn, cudaEnableDefault, &qr);
        enc = (EncodeFn)fn;
        cudaFuncSetAttribute(mega_kernel, cudaFuncAttributeMaxDynamicSharedMemorySize, SMEM_TOTAL);
    }
    CUtensorMap tmX, tmW, tmWo, tmG, tmU, tmOut;
    make_map(enc, &tmX, x, DM, S_LEN, 64, 128, true);
    make_map(enc, &tmW, wqkv, 3 * DM, DM, 64, 64, true);
    make_map(enc, &tmWo, wo, DM, DM, 64, 64, true);
    make_map(enc, &tmG, w_gate, FF, DM, 16, 64, false);
    make_map(enc, &tmU, w_up, FF, DM, 16, 64, false);
    make_map(enc, &tmOut, out, DM, S_LEN, 64, 64, true);

    mega_kernel<<<128, 512, SMEM_TOTAL, cudaStreamPerThread>>>(tmX, tmW, tmWo, tmG, tmU, tmOut, x, wqkv, wo, w_r, w_gate, w_up, w_down, out);
}
```

```cpp
#include <cuda_runtime.h>
#include <cuda_bf16.h>
#include <cuda.h>
#include <stdint.h>
#include <type_traits>

namespace {

constexpr int S_LEN = 2048, DM = 512, NH = 32, DH = 16, FF = 1792;
constexpr int NCTA = 128;
constexpr int NFFN = FF / 16;
constexpr float LN_EPS = 1e-5f;
constexpr float QSCALE = 0.25f * 1.4426950408889634f;

__device__ __align__(1024) uint16_t gQ[NH * S_LEN * DH];
__device__ __align__(1024) uint16_t gKV[NH * S_LEN * DH * 2];
__device__ __align__(1024) __nv_bfloat16 gO[S_LEN * DM];
__device__ unsigned int gEpoch;
__device__ __align__(32) unsigned int gFlagO[32 * 32];
__device__ __align__(32) unsigned int gFlagOut[NCTA * 8];
__device__ uint4 gFlagQKV[NCTA * 4];
__device__ uint4 gStat1[S_LEN];
__device__ uint4 gCsPart[8 * 16 * 48];
__device__ uint4 gPart[32 * 64 * 8];
__device__ uint4 gCand[NCTA * 64];
__device__ uint4 gCandRow[64 * 128];
__device__ uint4 gYPart[NFFN * 256];

#define TS(slot) do {} while (0)

constexpr int SPIN_LIMIT = 1 << 22;
#define BACKOFF() __nanosleep(32)

__device__ __forceinline__ uint32_t smem_u32(const void* p) { return (uint32_t)__cvta_generic_to_shared(p); }
__device__ __forceinline__ void mbar_init(uint32_t bar, uint32_t cnt) {
    asm volatile("mbarrier.init.shared::cta.b64 [%0], %1;" ::"r"(bar), "r"(cnt));
}
__device__ __forceinline__ void mbar_expect_tx(uint32_t bar, uint32_t bytes) {
    asm volatile("mbarrier.arrive.expect_tx.shared::cta.b64 _, [%0], %1;" ::"r"(bar), "r"(bytes) : "memory");
}
__device__ __forceinline__ void mbar_arrive(uint32_t bar) {
    asm volatile("mbarrier.arrive.shared::cta.b64 _, [%0];" ::"r"(bar) : "memory");
}
__device__ __forceinline__ void mbar_wait(uint32_t bar, uint32_t parity) {
    uint32_t done = 0;
    int it = 0;
    while (true) {
        asm volatile("{.reg .pred p; mbarrier.try_wait.parity.shared::cta.b64 p, [%1], %2; selp.u32 %0, 1, 0, p;}"
                     : "=r"(done) : "r"(bar), "r"(parity) : "memory");
        if (done) break;
        if (++it > SPIN_LIMIT) __trap();
    }
}
__device__ __forceinline__ void bulk_g2s(uint32_t dst, const void* src, uint32_t bytes, uint32_t bar) {
    asm volatile("cp.async.bulk.shared::cluster.global.mbarrier::complete_tx::bytes [%0], [%1], %2, [%3];"
                 ::"r"(dst), "l"(src), "r"(bytes), "r"(bar) : "memory");
}
__device__ __forceinline__ void bulk_prefetch_l2(const void* src, uint32_t bytes) {
    asm volatile("cp.async.bulk.prefetch.L2.global [%0], %1;" ::"l"(src), "r"(bytes) : "memory");
}
__device__ __forceinline__ void tma_2d(uint32_t dst, const CUtensorMap* tm, int c0, int c1, uint32_t bar) {
    asm volatile("cp.async.bulk.tensor.2d.shared::cluster.global.mbarrier::complete_tx::bytes [%0], [%1, {%3, %4}], [%2];"
                 ::"r"(dst), "l"(tm), "r"(bar), "r"(c0), "r"(c1) : "memory");
}
__device__ __forceinline__ void tma_store_2d(const CUtensorMap* tm, uint32_t src, int c0, int c1) {
    asm volatile("cp.async.bulk.tensor.2d.global.shared::cta.bulk_group [%0, {%2, %3}], [%1];" ::"l"(tm), "r"(src), "r"(c0), "r"(c1) : "memory");
    asm volatile("cp.async.bulk.commit_group;" ::: "memory");
}
__device__ __forceinline__ void fence_proxy_async_global() { asm volatile("fence.proxy.async.global;" ::: "memory"); }
__device__ __forceinline__ void fence_proxy_async_smem() { asm volatile("fence.proxy.async.shared::cta;" ::: "memory"); }
__device__ __forceinline__ void fence_gpu() { asm volatile("fence.acq_rel.gpu;" ::: "memory"); }
__device__ __forceinline__ void bar_sync(int id, int n) { asm volatile("bar.sync %0, %1;" ::"r"(id), "r"(n) : "memory"); }
__device__ __forceinline__ void bar_arrive(int id, int n) { asm volatile("bar.arrive %0, %1;" ::"r"(id), "r"(n) : "memory"); }
__device__ __forceinline__ void st_release(unsigned int* p, unsigned int v) {
    asm volatile("st.release.gpu.global.u32 [%0], %1;" ::"l"(p), "r"(v) : "memory");
}
__device__ __forceinline__ void st_relaxed(unsigned int* p, unsigned int v) {
    asm volatile("st.relaxed.gpu.global.u32 [%0], %1;" ::"l"(p), "r"(v) : "memory");
}
__device__ __forceinline__ void wait_flag(const unsigned int* p, unsigned int tag) {
    int it = 0;
    while (true) {
        unsigned int v;
        asm volatile("ld.relaxed.gpu.global.u32 %0, [%1];" : "=r"(v) : "l"(p) : "memory");
        if (v == tag) break;
        if (++it > SPIN_LIMIT) __trap();
        BACKOFF();
    }
}
__device__ __forceinline__ void st_pkt(uint4* p, uint4 v) {
    asm volatile("st.relaxed.gpu.global.v4.u32 [%0], {%1,%2,%3,%4};" ::"l"(p), "r"(v.x), "r"(v.y), "r"(v.z), "r"(v.w) : "memory");
}
__device__ __forceinline__ uint4 ld_pkt(const uint4* p) {
    uint4 v;
    asm volatile("ld.relaxed.gpu.global.v4.u32 {%0,%1,%2,%3}, [%4];" : "=r"(v.x), "=r"(v.y), "=r"(v.z), "=r"(v.w) : "l"(p) : "memory");
    return v;
}
template <int N, unsigned int MASK>
__device__ __forceinline__ void wait_pkts(const uint4* p, int stride, unsigned int tag, uint4 (&v)[N]) {
    int it = 0;
    while (true) {
        bool ok = true;
#pragma unroll
        for (int i = 0; i < N; i++) v[i] = ld_pkt(p + (size_t)i * stride);
#pragma unroll
        for (int i = 0; i < N; i++) ok = ok && ((v[i].w & MASK) == tag);
        if (ok) break;
        if (++it > SPIN_LIMIT) __trap();
        BACKOFF();
    }
}
__device__ __forceinline__ uint4 embed_tag(float a, float b, float c, float d, unsigned int tag) {
    return make_uint4((__float_as_uint(a) & ~15u) | (tag & 15u), (__float_as_uint(b) & ~15u) | ((tag >> 4) & 15u),
                      (__float_as_uint(c) & ~15u) | ((tag >> 8) & 15u), (__float_as_uint(d) & ~15u) | ((tag >> 12) & 15u));
}
template <int N>
__device__ __forceinline__ void wait_pkts4(const uint4* p, int stride, unsigned int tag, uint4 (&v)[N]) {
    const unsigned int t16 = tag & 0xffffu;
    int it = 0;
    while (true) {
        bool ok = true;
#pragma unroll
        for (int i = 0; i < N; i++) v[i] = ld_pkt(p + (size_t)i * stride);
#pragma unroll
        for (int i = 0; i < N; i++)
            ok = ok && (((v[i].x & 15u) | ((v[i].y & 15u) << 4) | ((v[i].z & 15u) << 8) | ((v[i].w & 15u) << 12)) == t16);
        if (ok) break;
        if (++it > SPIN_LIMIT) __trap();
        BACKOFF();
    }
}
__device__ __forceinline__ uint64_t make_desc(uint32_t addr, uint32_t lbo, uint32_t sbo, uint32_t mode) {
    return (uint64_t)((addr & 0x3FFFF) >> 4) | ((uint64_t)((lbo & 0x3FFFF) >> 4) << 16) |
           ((uint64_t)((sbo & 0x3FFFF) >> 4) << 32) | ((uint64_t)mode << 62);
}
__device__ __forceinline__ void wg_fence() { asm volatile("wgmma.fence.sync.aligned;" ::: "memory"); }
__device__ __forceinline__ void wg_commit() { asm volatile("wgmma.commit_group.sync.aligned;" ::: "memory"); }
template <int N> __device__ __forceinline__ void wg_wait() { asm volatile("wgmma.wait_group.sync.aligned %0;" ::"n"(N) : "memory"); }
template <int N> __device__ __forceinline__ void pin(uint32_t (&d)[N]) {
#pragma unroll
    for (int i = 0; i < N; i++) asm volatile("" : "+r"(d[i])::"memory");
}
template <int N> __device__ __forceinline__ void pin(float (&d)[N]) {
#pragma unroll
    for (int i = 0; i < N; i++) asm volatile("" : "+f"(d[i])::"memory");
}
__device__ __forceinline__ uint32_t pack_bf16(float lo, float hi) {
    uint32_t r;
    asm("cvt.rn.bf16x2.f32 %0, %1, %2;" : "=r"(r) : "f"(hi), "f"(lo));
    return r;
}
__device__ __forceinline__ uint32_t pack_f16_sat(float lo, float hi) {
    uint32_t r;
    asm("cvt.rn.satfinite.f16x2.f32 %0, %1, %2;" : "=r"(r) : "f"(hi), "f"(lo));
    return r;
}
__device__ __forceinline__ float bf_lo(uint32_t v) { return __uint_as_float(v << 16); }
__device__ __forceinline__ float bf_hi(uint32_t v) { return __uint_as_float(v & 0xFFFF0000u); }
__device__ __forceinline__ float bf_round(float v) { return __bfloat162float(__float2bfloat16(v)); }
__device__ __forceinline__ float ex2_mufu(float x) {
    float y;
    asm("ex2.approx.ftz.f32 %0, %1;" : "=f"(y) : "f"(x));
    return y;
}

#define ACC8(d, o) "+f"(d[o + 0]), "+f"(d[o + 1]), "+f"(d[o + 2]), "+f"(d[o + 3]), "+f"(d[o + 4]), "+f"(d[o + 5]), "+f"(d[o + 6]), "+f"(d[o + 7])
#define OUT8(c, d, o) c(d[o + 0]), c(d[o + 1]), c(d[o + 2]), c(d[o + 3]), c(d[o + 4]), c(d[o + 5]), c(d[o + 6]), c(d[o + 7])

__device__ __forceinline__ void wgmma_n192(float (&d)[96], uint64_t da, uint64_t db) {
    asm volatile(
        "wgmma.mma_async.sync.aligned.m64n192k16.f32.bf16.bf16 "
        "{%0,%1,%2,%3,%4,%5,%6,%7,%8,%9,%10,%11,%12,%13,%14,%15,%16,%17,%18,%19,%20,%21,%22,%23,%24,%25,%26,%27,%28,%29,%30,%31,"
        "%32,%33,%34,%35,%36,%37,%38,%39,%40,%41,%42,%43,%44,%45,%46,%47,%48,%49,%50,%51,%52,%53,%54,%55,%56,%57,%58,%59,%60,%61,%62,%63,"
        "%64,%65,%66,%67,%68,%69,%70,%71,%72,%73,%74,%75,%76,%77,%78,%79,%80,%81,%82,%83,%84,%85,%86,%87,%88,%89,%90,%91,%92,%93,%94,%95},"
        "%96, %97, 1, 1, 1, 0, 1;"
        : ACC8(d, 0), ACC8(d, 8), ACC8(d, 16), ACC8(d, 24), ACC8(d, 32), ACC8(d, 40), ACC8(d, 48), ACC8(d, 56),
          ACC8(d, 64), ACC8(d, 72), ACC8(d, 80), ACC8(d, 88)
        : "l"(da), "l"(db));
}
__device__ __forceinline__ void wgmma_n64(float (&d)[32], uint64_t da, uint64_t db) {
    asm volatile(
        "wgmma.mma_async.sync.aligned.m64n64k16.f32.bf16.bf16 "
        "{%0,%1,%2,%3,%4,%5,%6,%7,%8,%9,%10,%11,%12,%13,%14,%15,%16,%17,%18,%19,%20,%21,%22,%23,%24,%25,%26,%27,%28,%29,%30,%31},"
        "%32, %33, 1, 1, 1, 0, 1;"
        : ACC8(d, 0), ACC8(d, 8), ACC8(d, 16), ACC8(d, 24)
        : "l"(da), "l"(db));
}
__device__ __forceinline__ void wgmma_qk128_f32(float (&d)[64], const uint32_t (&a)[4], uint64_t db) {
    asm volatile(
        "wgmma.mma_async.sync.aligned.m64n128k16.f32.f16.f16 "
        "{%0,%1,%2,%3,%4,%5,%6,%7,%8,%9,%10,%11,%12,%13,%14,%15,%16,%17,%18,%19,%20,%21,%22,%23,%24,%25,%26,%27,%28,%29,%30,%31,"
        "%32,%33,%34,%35,%36,%37,%38,%39,%40,%41,%42,%43,%44,%45,%46,%47,%48,%49,%50,%51,%52,%53,%54,%55,%56,%57,%58,%59,%60,%61,%62,%63},"
        "{%64,%65,%66,%67}, %68, 0, 1, 1, 0;"
        : OUT8("=f", d, 0), OUT8("=f", d, 8), OUT8("=f", d, 16), OUT8("=f", d, 24), OUT8("=f", d, 32), OUT8("=f", d, 40),
          OUT8("=f", d, 48), OUT8("=f", d, 56)
        : "r"(a[0]), "r"(a[1]), "r"(a[2]), "r"(a[3]), "l"(db));
}
__device__ __forceinline__ void wgmma_qk64_f32(float (&d)[32], const uint32_t (&a)[4], uint64_t db) {
    asm volatile(
        "wgmma.mma_async.sync.aligned.m64n64k16.f32.f16.f16 "
        "{%0,%1,%2,%3,%4,%5,%6,%7,%8,%9,%10,%11,%12,%13,%14,%15,%16,%17,%18,%19,%20,%21,%22,%23,%24,%25,%26,%27,%28,%29,%30,%31},"
        "{%32,%33,%34,%35}, %36, 0, 1, 1, 0;"
        : OUT8("=f", d, 0), OUT8("=f", d, 8), OUT8("=f", d, 16), OUT8("=f", d, 24)
        : "r"(a[0]), "r"(a[1]), "r"(a[2]), "r"(a[3]), "l"(db));
}
__device__ __forceinline__ void wgmma_qk64_f16(uint32_t (&d)[16], const uint32_t (&a)[4], uint64_t db) {
    asm volatile(
        "wgmma.mma_async.sync.aligned.m64n64k16.f16.f16.f16 "
        "{%0,%1,%2,%3,%4,%5,%6,%7,%8,%9,%10,%11,%12,%13,%14,%15}, {%16,%17,%18,%19}, %20, 0, 1, 1, 0;"
        : OUT8("=r", d, 0), OUT8("=r", d, 8)
        : "r"(a[0]), "r"(a[1]), "r"(a[2]), "r"(a[3]), "l"(db));
}
__device__ __forceinline__ void wgmma_pv24(float (&o)[12], uint32_t a0, uint32_t a1, uint32_t a2, uint32_t a3, uint32_t lo, uint32_t hi) {
    asm volatile(
        "{.reg .b64 d; mov.b64 d, {%16, %17};\n"
        "wgmma.mma_async.sync.aligned.m64n24k16.f32.bf16.bf16 "
        "{%0,%1,%2,%3,%4,%5,%6,%7,%8,%9,%10,%11}, {%12,%13,%14,%15}, d, 1, 1, 1, 1;}"
        : ACC8(o, 0), "+f"(o[8]), "+f"(o[9]), "+f"(o[10]), "+f"(o[11])
        : "r"(a0), "r"(a1), "r"(a2), "r"(a3), "r"(lo), "r"(hi));
}

__device__ __forceinline__ uint32_t ex2_pair_h16(uint32_t x2) {
    uint32_t t, r, f, q;
    asm("add.rn.f16x2 %0, %1, %2;" : "=r"(t) : "r"(x2), "r"(0x661E661Fu));
    asm("sub.rn.f16x2 %0, %1, %2;" : "=r"(r) : "r"(t), "r"(0x661E661Fu));
    asm("sub.rn.f16x2 %0, %1, %2;" : "=r"(f) : "r"(x2), "r"(r));
    asm("fma.rn.f16x2 %0, %1, %2, %3;" : "=r"(q) : "r"(0x15101510u), "r"(f), "r"(0x1d7e1d7eu));
    asm("fma.rn.f16x2 %0, %1, %2, %3;" : "=r"(q) : "r"(q), "r"(f), "r"(0x23d823d8u));
    asm("fma.rn.f16x2 %0, %1, %2, %3;" : "=r"(q) : "r"(q), "r"(f), "r"(0x30823035u));
    return t * 128u + q;
}
constexpr float VSCALE_ODD = 0.70703125f;
constexpr float LOG2C_ODD = 0.50015402f;

__device__ __forceinline__ unsigned int f2ord(float v) {
    const unsigned int u = __float_as_uint(v);
    const unsigned int o = u ^ ((unsigned int)((int)u >> 31) | 0x80000000u);
    return (v == v) ? o : 0u;
}
__device__ __forceinline__ void warp_top2(unsigned int ka, unsigned int ia, unsigned int kb, unsigned int ib, unsigned int& i1, unsigned int& i2) {
    const unsigned int m1 = __reduce_max_sync(0xffffffffu, max(ka, kb));
    i1 = __reduce_min_sync(0xffffffffu, min(ka == m1 ? ia : 0xffffffffu, kb == m1 ? ib : 0xffffffffu));
    const bool ra = (ia == i1), rb = (ib == i1);
    const unsigned int ka2 = ra ? 0u : ka, kb2 = rb ? 0u : kb, ia2 = ra ? 0xffffffffu : ia, ib2 = rb ? 0xffffffffu : ib;
    const unsigned int m2 = __reduce_max_sync(0xffffffffu, max(ka2, kb2));
    i2 = __reduce_min_sync(0xffffffffu, min(ka2 == m2 ? ia2 : 0xffffffffu, kb2 == m2 ? ib2 : 0xffffffffu));
}

constexpr int P1_STAGES = 5;
constexpr int P1_STAGE_BYTES = 16384 + 24576;
constexpr int KV_CHUNK = 10240;
constexpr int SM_A3 = 163840;
constexpr int SM_Q = 163840;
constexpr int SM_MISC = 229376;
constexpr int SMEM_TOTAL = 232448;
struct Misc {
    uint64_t p1_full[P1_STAGES], p1_empty[P1_STAGES];
    uint64_t kv[16], qbar;
    uint64_t wo[8], a3[8], moe;
    unsigned int tag;
    int fast;
    int idx[2], cslot[2];
    alignas(16) float sel[8];
    unsigned int norm[12];
    unsigned int freed[16];
    union alignas(16) {
        struct { float mu[128], rs[128], cs[192]; } p1;
        struct { float mu[64], rs[64], r[64]; } p3;
    };
};
static_assert(sizeof(Misc) <= SMEM_TOTAL - SM_MISC, "misc smem");

__device__ __forceinline__ void release_kv_chunk(Misc& ms, int j, int lane) {
    asm volatile("{.reg .pred p; setp.eq.s32 p, %1, 0; @p red.relaxed.cta.shared.add.u32 [%0], 1;}" ::"r"(smem_u32(&ms.freed[j])), "r"(lane) : "memory");
}
__device__ __forceinline__ bool refill_kv_chunk(char* smem, Misc& ms, int j, int cta, int lane, const CUtensorMap* tmWo,
                                                const CUtensorMap* tmG, const CUtensorMap* tmU) {
    unsigned int cnt;
    asm volatile("ld.relaxed.cta.shared.u32 %0, [%1];" : "=r"(cnt) : "r"(smem_u32(&ms.freed[j])) : "memory");
    if (cnt < 16u) return false;
    if (lane == 0) {
        const uint32_t dst = smem_u32(smem + j * KV_CHUNK);
        const uint32_t wb = smem_u32(&ms.wo[j >> 1]);
        mbar_expect_tx(wb, 8192);
        tma_2d(dst, tmWo, (cta & 3) * 128 + (j & 1) * 64, (j >> 1) * 64, wb);
        if (cta < NFFN) {
            const uint32_t mb = smem_u32(&ms.moe);
            mbar_expect_tx(mb, 2048);
            tma_2d(dst + 8192, (j & 8) ? tmU : tmG, cta * 16, (j & 7) * 64, mb);
        }
    }
    __syncwarp();
    return true;
}

__global__ void __launch_bounds__(512, 1)
mega_kernel(const __grid_constant__ CUtensorMap tmX, const __grid_constant__ CUtensorMap tmW,
            const __grid_constant__ CUtensorMap tmO, const __grid_constant__ CUtensorMap tmWo,
            const __grid_constant__ CUtensorMap tmG, const __grid_constant__ CUtensorMap tmU,
            const __grid_constant__ CUtensorMap tmOut,
            const __nv_bfloat16* __restrict__ x, const __nv_bfloat16* __restrict__ wqkv, const __nv_bfloat16* __restrict__ wo,
            const __nv_bfloat16* __restrict__ w_r, const __nv_bfloat16* __restrict__ w_gate,
            const __nv_bfloat16* __restrict__ w_up, const __nv_bfloat16* __restrict__ w_down,
            __nv_bfloat16* __restrict__ out) {
    extern __shared__ __align__(1024) char smem[];
    Misc& ms = *reinterpret_cast<Misc*>(smem + SM_MISC);
    const int tid = threadIdx.x, lane = tid & 31;
    const int warp = __shfl_sync(0xffffffffu, tid >> 5, 0);
    const int wg = warp >> 2, w4 = warp & 3, g = lane >> 2, t4 = lane & 3;
    const int cta = blockIdx.x;
    const int rb = cta >> 3, hg = cta & 7;

    if (warp == 12) {
        if (lane == 0) {
            TS(0);
            if (smem_u32(smem) & 1023) __trap();
            for (int i = 0; i < P1_STAGES; i++) { mbar_init(smem_u32(&ms.p1_full[i]), 1); mbar_init(smem_u32(&ms.p1_empty[i]), 8); }
            asm volatile("fence.mbarrier_init.release.cluster;" ::: "memory");
        }
        __syncwarp();
        bar_arrive(13, 288);
        bar_arrive(14, 256);
    } else {
        if (tid == 32) {
            for (int i = 0; i < 16; i++) { mbar_init(smem_u32(&ms.kv[i]), 1); ms.freed[i] = 0; }
            for (int i = 0; i < 8; i++) { mbar_init(smem_u32(&ms.wo[i]), 2); mbar_init(smem_u32(&ms.a3[i]), 1); }
            mbar_init(smem_u32(&ms.moe), 16);
            mbar_init(smem_u32(&ms.qbar), 1);
            asm volatile("fence.mbarrier_init.release.cluster;" ::: "memory");
        }
        if (tid >= 64 && tid < 76) ms.norm[tid - 64] = 0;
        if (tid >= 96 && tid < 101) {
            const CUtensorMap* tm = tid == 96 ? &tmO : tid == 97 ? &tmWo : tid == 98 ? &tmG : tid == 99 ? &tmU : &tmOut;
            asm volatile("prefetch.tensormap [%0];" ::"l"(tm) : "memory");
        }
        if (tid == 416) {
            unsigned int t = __ldcg(&gEpoch) + 1u;
            if ((t & 0xffffu) == 0) t++;
            ms.tag = t;
        }
    }

    if (wg < 2) {
        asm volatile("setmaxnreg.inc.sync.aligned.u32 160;");
        float acc[96];
#pragma unroll
        for (int i = 0; i < 96; i++) acc[i] = 0.f;
        bar_sync(13, 288);
#pragma unroll
        for (int kc = 0; kc < 8; kc++) {
            const int s = kc % P1_STAGES;
            mbar_wait(smem_u32(&ms.p1_full[s]), (kc / P1_STAGES) & 1);
            if (tid == 0) TS(24 + kc);
            const uint32_t sa = smem_u32(smem + s * P1_STAGE_BYTES), sb = sa + 16384;
            const uint64_t da = make_desc(sa + wg * 8192, 16, 1024, 1);
            const uint64_t db = make_desc(sb, 8192, 1024, 1);
            wg_fence();
#pragma unroll
            for (int ks = 0; ks < 4; ks++) wgmma_n192(acc, da + ks * 2, db + ks * 128);
            wg_commit();
            wg_wait<1>();
            if (kc > 0 && lane == 0) mbar_arrive(smem_u32(&ms.p1_empty[(kc - 1) % P1_STAGES]));
        }
        wg_wait<0>();
        pin(acc);
        if (tid == 0) TS(1);
        bar_sync(1, 480);
        const unsigned int tag = ms.tag;
        if (tid == 0) TS(16);
        const int lr0 = wg * 64 + w4 * 16 + g, lr1 = lr0 + 8;
        const float mu0 = ms.p1.mu[lr0], mu1 = ms.p1.mu[lr1], rs0 = ms.p1.rs[lr0], rs1 = ms.p1.rs[lr1];
        const int lg0 = wg * 8 + w4 * 2;
#pragma unroll
        for (int hh = 0; hh < 4; hh++) {
            const int head = hg * 4 + hh;
            unsigned int nrm[3];
#pragma unroll
            for (int sec = 0; sec < 3; sec++) {
                float sq0 = 0.f, sq1 = 0.f;
                unsigned int vm = 0u;
                const float f0 = sec == 0 ? rs0 * QSCALE : rs0, f1 = sec == 0 ? rs1 * QSCALE : rs1;
#pragma unroll
                for (int db = 0; db < 2; db++) {
                    const int j = sec * 8 + hh * 2 + db;
                    const float2 c = *reinterpret_cast<const float2*>(&ms.p1.cs[j * 8 + 2 * t4]);
                    const float a0 = (acc[4 * j + 0] - mu0 * c.x) * f0, a1 = (acc[4 * j + 1] - mu0 * c.y) * f0;
                    const float b0 = (acc[4 * j + 2] - mu1 * c.x) * f1, b1 = (acc[4 * j + 3] - mu1 * c.y) * f1;
                    if (sec == 0) {
                        uint32_t* dst = reinterpret_cast<uint32_t*>(gQ) + ((size_t)head * S_LEN * DH + (rb * 16 + lg0) * 128) / 2;
                        dst[db * 32 + lane] = pack_f16_sat(a0, a1);
                        dst[64 + db * 32 + lane] = pack_f16_sat(b0, b1);
                    } else if (sec == 1) {
                        uint32_t* dst = reinterpret_cast<uint32_t*>(gKV) + (size_t)(head * 16 + rb) * 2048 + (lg0 >> 1) * 64;
                        dst[db * 32 + lane] = pack_f16_sat(a0, a1);
                        dst[512 + db * 32 + lane] = pack_f16_sat(b0, b1);
                    } else {
                        uint32_t* dst = reinterpret_cast<uint32_t*>(gKV) + (size_t)(head * 16 + rb) * 2048 + 1024 + db * 512 + lg0 * 32;
                        dst[lane] = pack_bf16(a0, a1);
                        dst[32 + lane] = pack_bf16(b0 * VSCALE_ODD, b1 * VSCALE_ODD);
                    }
                    if (sec < 2) {
                        sq0 = fmaf(a0, a0, fmaf(a1, a1, sq0));
                        sq1 = fmaf(b0, b0, fmaf(b1, b1, sq1));
                    } else {
                        vm = max(vm, max(max(__float_as_uint(a0) & 0x7fffffffu, __float_as_uint(a1) & 0x7fffffffu),
                                         max(__float_as_uint(b0) & 0x7fffffffu, __float_as_uint(b1) & 0x7fffffffu)));
                    }
                }
                if (sec < 2) {
                    sq0 += __shfl_xor_sync(0xffffffffu, sq0, 1); sq0 += __shfl_xor_sync(0xffffffffu, sq0, 2);
                    sq1 += __shfl_xor_sync(0xffffffffu, sq1, 1); sq1 += __shfl_xor_sync(0xffffffffu, sq1, 2);
                    vm = max(__float_as_uint(sq0) & 0x7fffffffu, __float_as_uint(sq1) & 0x7fffffffu);
                }
                nrm[sec] = __reduce_max_sync(0xffffffffu, vm);
            }
            if (lane < 3) atomicMax(&ms.norm[hh * 3 + lane], lane == 0 ? nrm[0] : lane == 1 ? nrm[1] : nrm[2]);
        }
        if (tid == 0) TS(17);
        bar_sync(2, 256);
        if (tid < 4) {
            fence_gpu();
            st_pkt(&gFlagQKV[(hg * 16 + rb) * 4 + tid], make_uint4(ms.norm[tid * 3], ms.norm[tid * 3 + 1], ms.norm[tid * 3 + 2], tag));
            if (tid == 0) TS(2);
        }
        asm volatile("setmaxnreg.dec.sync.aligned.u32 128;");
        bar_sync(15, 512);
    } else {
      asm volatile("setmaxnreg.dec.sync.aligned.u32 96;");
      if (wg == 2) {
        const int t = tid - 256;
        if (t < 4) gFlagQKV[(hg * 16 + rb) * 4 + t] = make_uint4(0u, 0u, 0u, 0u);
        bar_sync(14, 256);
        mbar_wait(smem_u32(&ms.p1_full[0]), 0);
        {
            const int row = rb * 128 + hg * 16 + (t >> 3), j = t & 7;
            const uint4* xp = reinterpret_cast<const uint4*>(x + (size_t)row * DM);
            uint4 v[8];
#pragma unroll
            for (int i = 0; i < 8; i++) v[i] = __ldg(xp + i * 8 + j);
            float s1 = 0.f;
#pragma unroll
            for (int i = 0; i < 8; i++) {
                const uint32_t w[4] = {v[i].x, v[i].y, v[i].z, v[i].w};
#pragma unroll
                for (int e = 0; e < 4; e++) s1 += bf_lo(w[e]) + bf_hi(w[e]);
            }
            s1 += __shfl_xor_sync(0xffffffffu, s1, 1); s1 += __shfl_xor_sync(0xffffffffu, s1, 2); s1 += __shfl_xor_sync(0xffffffffu, s1, 4);
            const float mu = s1 * (1.f / DM);
            float s2 = 0.f;
#pragma unroll
            for (int i = 0; i < 8; i++) {
                const uint32_t w[4] = {v[i].x, v[i].y, v[i].z, v[i].w};
#pragma unroll
                for (int e = 0; e < 4; e++) {
                    const float a = bf_lo(w[e]) - mu, b = bf_hi(w[e]) - mu;
                    s2 = fmaf(a, a, fmaf(b, b, s2));
                }
            }
            s2 += __shfl_xor_sync(0xffffffffu, s2, 1); s2 += __shfl_xor_sync(0xffffffffu, s2, 2); s2 += __shfl_xor_sync(0xffffffffu, s2, 4);
            bar_sync(11, 224);
            if (j == 0) st_pkt(&gStat1[row], make_uint4(__float_as_uint(mu), __float_as_uint(rsqrtf(s2 * (1.f / DM) + LN_EPS)), 0u, ms.tag));
        }
        const unsigned int tag = ms.tag;
        mbar_wait(smem_u32(&ms.p1_full[2]), 1);
        uint4 st[1];
        wait_pkts<1, 0xffffffffu>(&gStat1[rb * 128 + t], 0, tag, st);
        if (t == 0) TS(34);
        ms.p1.mu[t] = __uint_as_float(st[0].x);
        ms.p1.rs[t] = __uint_as_float(st[0].y);
        bar_arrive(1, 480);
        {
            const uint4 z = make_uint4(0u, 0u, 0u, 0u);
            if (t < 64) { gCand[cta * 64 + t] = z; gCandRow[cta * 64 + t] = z; }
            gPart[cta * 128 + t] = z;
            gYPart[cta * 224 + t] = z;
            if (t < 96) gYPart[cta * 224 + 128 + t] = z;
            if (t < 2) {
                reinterpret_cast<uint4*>(gFlagO)[cta * 2 + t] = z;
                reinterpret_cast<uint4*>(gFlagOut)[cta * 2 + t] = z;
            }
        }
      } else if (warp == 12) {
        if (lane == 0) {
#pragma unroll 1
            for (int kc = 0; kc < 8; kc++) {
                const int s = kc % P1_STAGES;
                if (kc >= P1_STAGES) mbar_wait(smem_u32(&ms.p1_empty[s]), 0);
                const uint32_t bar = smem_u32(&ms.p1_full[s]);
                const uint32_t sa = smem_u32(smem + s * P1_STAGE_BYTES), sb = sa + 16384;
                mbar_expect_tx(bar, P1_STAGE_BYTES);
                tma_2d(sa, &tmX, kc * 64, rb * 128, bar);
#pragma unroll
                for (int p = 0; p < 3; p++) tma_2d(sb + p * 8192, &tmW, p * 512 + hg * 64, kc * 64, bar);
            }
        }
      } else {
        const int t = tid - 416;
        bar_sync(14, 256);
        mbar_wait(smem_u32(&ms.p1_full[0]), 0);
        const int c16 = t >> 2, rs = t & 3;
        const __nv_bfloat16* wp = wqkv + (size_t)(rb * 32 + rs) * (3 * DM) + (c16 >> 3) * 512 + hg * 64 + (c16 & 7) * 8;
        uint4 v[8];
#pragma unroll
        for (int i = 0; i < 8; i++) v[i] = __ldg(reinterpret_cast<const uint4*>(wp + (size_t)i * 4 * (3 * DM)));
        float a[8] = {};
#pragma unroll
        for (int i = 0; i < 8; i++) {
            a[0] += bf_lo(v[i].x); a[1] += bf_hi(v[i].x); a[2] += bf_lo(v[i].y); a[3] += bf_hi(v[i].y);
            a[4] += bf_lo(v[i].z); a[5] += bf_hi(v[i].z); a[6] += bf_lo(v[i].w); a[7] += bf_hi(v[i].w);
        }
#pragma unroll
        for (int e = 0; e < 8; e++) { a[e] += __shfl_xor_sync(0xffffffffu, a[e], 1); a[e] += __shfl_xor_sync(0xffffffffu, a[e], 2); }
        bar_sync(11, 224);
        const unsigned int tag = ms.tag;
        const int pq = c16 * 2 + (rs & 1);
        if (rs < 2) st_pkt(&gCsPart[(hg * 16 + rb) * 48 + pq], embed_tag(rs ? a[4] : a[0], rs ? a[5] : a[1], rs ? a[6] : a[2], rs ? a[7] : a[3], tag));
        if (t < 16) { uint4 gate[1]; wait_pkts4<1>(&gCsPart[(hg * 16 + t) * 48 + 47], 0, tag, gate); }
        bar_sync(8, 96);
        {
            uint4 p[8];
            wait_pkts4<8>(&gCsPart[(hg * 16 + (rs >> 1) * 8) * 48 + pq], 48, tag, p);
            float s0 = 0.f, s1 = 0.f, s2 = 0.f, s3 = 0.f;
#pragma unroll
            for (int i = 0; i < 8; i++) {
                s0 += __uint_as_float(p[i].x); s1 += __uint_as_float(p[i].y); s2 += __uint_as_float(p[i].z); s3 += __uint_as_float(p[i].w);
            }
            s0 += __shfl_xor_sync(0xffffffffu, s0, 2); s1 += __shfl_xor_sync(0xffffffffu, s1, 2);
            s2 += __shfl_xor_sync(0xffffffffu, s2, 2); s3 += __shfl_xor_sync(0xffffffffu, s3, 2);
            if (rs < 2) *reinterpret_cast<float4*>(&ms.p1.cs[pq * 4]) = make_float4(s0, s1, s2, s3);
            if (t == 0) TS(37);
        }
        __syncwarp();
        bar_arrive(1, 480);
      }
      __syncwarp();
      bar_sync(15, 512);
      asm volatile("setmaxnreg.inc.sync.aligned.u32 128;");
    }
    if (tid == 0) TS(20);
    const unsigned int tag = ms.tag;

    const int head = hg * 4 + (rb >> 2), quarter = rb & 3;
    {
#pragma unroll
        for (int i = 0; i < 4; i++) {
            const int e = tid + i * 512;
            *reinterpret_cast<uint4*>(smem + (e >> 7) * KV_CHUNK + 8192 + (e & 127) * 16) = make_uint4((e & 8) ? 0x00003F35u : 0x00003F80u, 0, 0, 0);
        }
        fence_proxy_async_smem();
    }
    if (warp == 0) {
        uint4 n[1];
        wait_pkts<1, 0xffffffffu>(&gFlagQKV[(hg * 16 + (lane & 15)) * 4 + (rb >> 2)], 0, tag, n);
        __syncwarp();
        if (lane == 0) TS(21);
        const float q2 = __uint_as_float(__reduce_max_sync(0xffffffffu, n[0].x));
        const float k2 = __uint_as_float(__reduce_max_sync(0xffffffffu, n[0].y));
        const float vm = __uint_as_float(__reduce_max_sync(0xffffffffu, n[0].z));
        if (lane == 0) ms.fast = (q2 * k2 * 1.02f <= 812.f) && (q2 <= 1.0e6f) && (k2 <= 1.0e6f) && (vm <= 1.0e18f) && (vm >= 1.0e-18f || vm == 0.f);
    }
    __syncthreads();
    auto load_kv_chunk = [&](int j) {
        fence_proxy_async_global();
        const uint32_t bar = smem_u32(&ms.kv[j]);
        mbar_expect_tx(bar, 8192);
        bulk_g2s(smem_u32(smem + j * KV_CHUNK), reinterpret_cast<const char*>(gKV) + (size_t)(head * 16 + j) * 8192, 8192, bar);
    };
    if (lane == 0) {
        if (warp == 5) {
            fence_proxy_async_global();
            mbar_expect_tx(smem_u32(&ms.qbar), 16384);
            bulk_g2s(smem_u32(smem + SM_Q), reinterpret_cast<const char*>(gQ) + (size_t)head * 65536 + quarter * 16384, 16384, smem_u32(&ms.qbar));
        }
        if (warp < 5) load_kv_chunk(warp);
    }
    __syncwarp();
    if (tid == 0) TS(3);
    bool refilled = false;
    {
        const bool fast = ms.fast != 0;
        const uint64_t descK = make_desc(smem_u32(smem), 128, 256, 0);
        const uint64_t descV = make_desc(smem_u32(smem + 4096), 128, 2048, 0);
        mbar_wait(smem_u32(&ms.qbar), 0);
        auto run_tiles = [&](auto FAST) {
#pragma unroll 1
            for (int t = wg; t < 8; t += 4) {
                const bool last = t >= 4;
                uint32_t q[4];
                {
                    const uint32_t* Qs = reinterpret_cast<const uint32_t*>(smem + SM_Q + t * 2048 + w4 * 512);
                    q[0] = Qs[lane]; q[2] = Qs[32 + lane]; q[1] = Qs[64 + lane]; q[3] = Qs[96 + lane];
                }
                float o[12];
#pragma unroll
                for (int i = 0; i < 12; i++) o[i] = 0.f;
                [[maybe_unused]] float m0 = -INFINITY, m1 = -INFINITY;
#pragma unroll 1
                for (int j = 0; j < 16; j++) {
                    if (!last && warp == j + 5 && lane == 0) load_kv_chunk(warp);
                    __syncwarp();
                    mbar_wait(smem_u32(&ms.kv[j]), 0);
                    const uint32_t off = j * (KV_CHUNK >> 4);
                    const uint32_t vlo = (uint32_t)descV + off, vhi = (uint32_t)(descV >> 32);
                    if constexpr (decltype(FAST)::value) {
                        float s[32];
                        uint32_t h[16];
                        wg_fence();
                        wgmma_qk64_f32(s, q, descK + (uint64_t)off);
                        wgmma_qk64_f16(h, q, descK + (uint64_t)(off + 128));
                        wg_commit();
                        wg_wait<0>();
                        pin(s);
                        pin(h);
                        if (last) {
                            if (j > 0) release_kv_chunk(ms, j - 1, lane);
                            if (!refilled && j > warp) refilled = refill_kv_chunk(smem, ms, warp, cta, lane, &tmWo, &tmG, &tmU);
                        }
#pragma unroll
                        for (int kg = 0; kg < 4; kg++) {
                            uint32_t p[8];
#pragma unroll
                            for (int u = 0; u < 2; u++) {
                                const int k = kg * 2 + u;
                                p[4 * u + 0] = pack_bf16(ex2_mufu(s[4 * k]), ex2_mufu(s[4 * k + 1]));
                                p[4 * u + 1] = pack_bf16(ex2_mufu(s[4 * k + 2]), ex2_mufu(s[4 * k + 3]));
                                p[4 * u + 2] = ex2_pair_h16(h[2 * k]);
                                p[4 * u + 3] = ex2_pair_h16(h[2 * k + 1]);
                            }
                            wg_fence();
#pragma unroll
                            for (int u = 0; u < 2; u++)
                                wgmma_pv24(o, p[4 * u], p[4 * u + 1], p[4 * u + 2], p[4 * u + 3], vlo + (kg * 2 + u) * 16, vhi);
                            wg_commit();
                            wg_wait<2>();
                        }
                    } else {
                        float s[64];
                        wg_fence();
                        wgmma_qk128_f32(s, q, descK + (uint64_t)off);
                        wg_commit();
                        wg_wait<0>();
                        pin(s);
                        pin(o);
                        if (last && j > 0) release_kv_chunk(ms, j - 1, lane);
                        float n0 = m0, n1 = m1;
#pragma unroll
                        for (int i = 0; i < 16; i++) {
                            n0 = fmaxf(n0, fmaxf(s[4 * i], s[4 * i + 1]));
                            n1 = fmaxf(n1, fmaxf(s[4 * i + 2], s[4 * i + 3]));
                        }
                        n0 = fmaxf(n0, __shfl_xor_sync(0xffffffffu, n0, 1)); n0 = fmaxf(n0, __shfl_xor_sync(0xffffffffu, n0, 2));
                        n1 = fmaxf(n1, __shfl_xor_sync(0xffffffffu, n1, 1)); n1 = fmaxf(n1, __shfl_xor_sync(0xffffffffu, n1, 2));
                        const float a0 = ex2_mufu(m0 - n0), a1 = ex2_mufu(m1 - n1);
                        m0 = n0; m1 = n1;
#pragma unroll
                        for (int i = 0; i < 3; i++) { o[4 * i] *= a0; o[4 * i + 1] *= a0; o[4 * i + 2] *= a1; o[4 * i + 3] *= a1; }
                        const float e0 = n0 - LOG2C_ODD, e1 = n1 - LOG2C_ODD;
#pragma unroll
                        for (int k = 0; k < 8; k++) {
                            const uint32_t p0 = pack_bf16(ex2_mufu(s[4 * k] - n0), ex2_mufu(s[4 * k + 1] - n0));
                            const uint32_t p1 = pack_bf16(ex2_mufu(s[4 * k + 2] - n1), ex2_mufu(s[4 * k + 3] - n1));
                            const uint32_t p2 = pack_bf16(ex2_mufu(s[32 + 4 * k] - e0), ex2_mufu(s[32 + 4 * k + 1] - e0));
                            const uint32_t p3 = pack_bf16(ex2_mufu(s[32 + 4 * k + 2] - e1), ex2_mufu(s[32 + 4 * k + 3] - e1));
                            wg_fence();
                            wgmma_pv24(o, p0, p1, p2, p3, vlo + k * 16, vhi);
                            wg_commit();
                            wg_wait<0>();
                            pin(o);
                        }
                    }
                }
                wg_wait<0>();
                pin(o);
                if (last) release_kv_chunk(ms, 15, lane);
                const float l0 = __shfl_sync(0xffffffffu, o[8], lane & ~3), l1 = __shfl_sync(0xffffffffu, o[10], lane & ~3);
                const float r0 = __fdividef(1.f, l0), r1 = __fdividef(1.f, l1);
                uint32_t* Op = reinterpret_cast<uint32_t*>(gO + (size_t)(quarter * 512 + t * 64 + w4 * 16) * DM + head * DH);
                Op[g * 256 + t4] = pack_bf16(o[0] * r0, o[1] * r0);
                Op[(g + 8) * 256 + t4] = pack_bf16(o[2] * r1, o[3] * r1);
                Op[g * 256 + 4 + t4] = pack_bf16(o[4] * r0, o[5] * r0);
                Op[(g + 8) * 256 + 4 + t4] = pack_bf16(o[6] * r1, o[7] * r1);
                if (last) {
                    bar_sync(3 + wg, 128);
                    if ((tid & 127) == 0) {
                        fence_gpu();
                        st_relaxed(&gFlagO[(quarter * 8 + t - 4) * 32 + head], tag);
                        st_relaxed(&gFlagO[(quarter * 8 + t) * 32 + head], tag);
                    }
                } else if (tid == 511) {
                    bulk_prefetch_l2(reinterpret_cast<const char*>(wo) + cta * 4096, 4096);
                    bulk_prefetch_l2(reinterpret_cast<const char*>(w_gate) + cta * 14336, 14336);
                    bulk_prefetch_l2(reinterpret_cast<const char*>(w_up) + cta * 14336, 14336);
                    bulk_prefetch_l2(reinterpret_cast<const char*>(w_down) + cta * 14336, 14336);
                }
                __syncwarp();
            }
        };
        if (fast) run_tiles(std::true_type{}); else run_tiles(std::false_type{});
    }
    __syncthreads();
    if (!refilled) refill_kv_chunk(smem, ms, warp, cta, lane, &tmWo, &tmG, &tmU);
    if (tid == 0) TS(4);

    const int rb3 = cta >> 2, cb = cta & 3;
    if (wg < 2) {
        const int r0 = rb3 * 64 + w4 * 16 + g, r1 = r0 + 8;
        const int col0 = cb * 128 + wg * 64 + 2 * t4;
        uint32_t xa[8], xb[8], wr[8];
#pragma unroll
        for (int j = 0; j < 8; j++) {
            xa[j] = __ldg(reinterpret_cast<const uint32_t*>(x + (size_t)r0 * DM + col0 + j * 8));
            xb[j] = __ldg(reinterpret_cast<const uint32_t*>(x + (size_t)r1 * DM + col0 + j * 8));
            wr[j] = __ldg(reinterpret_cast<const uint32_t*>(w_r + col0 + j * 8));
        }
        const float p0 = __bfloat162float(x[(size_t)r0 * DM]), p1 = __bfloat162float(x[(size_t)r1 * DM]);
        const float pivot = __bfloat162float(x[(size_t)(rb3 * 64 + (tid >> 2)) * DM]);
        float wsum = 0.f;
        {
            const uint4 a = __ldg(reinterpret_cast<const uint4*>(w_r) + lane), b = __ldg(reinterpret_cast<const uint4*>(w_r) + 32 + lane);
            const uint32_t w[8] = {a.x, a.y, a.z, a.w, b.x, b.y, b.z, b.w};
#pragma unroll
            for (int e = 0; e < 8; e++) wsum += bf_lo(w[e]) + bf_hi(w[e]);
#pragma unroll
            for (int m = 16; m; m >>= 1) wsum += __shfl_xor_sync(0xffffffffu, wsum, m);
        }
        float acc[32];
#pragma unroll
        for (int i = 0; i < 32; i++) acc[i] = 0.f;
#pragma unroll 1
        for (int kc = 0; kc < 8; kc++) {
            mbar_wait(smem_u32(&ms.wo[kc]), 0);
            mbar_wait(smem_u32(&ms.a3[kc]), 0);
            const uint64_t da = make_desc(smem_u32(smem + SM_A3 + kc * 8192), 16, 1024, 1);
            const uint64_t db = make_desc(smem_u32(smem + (kc * 2 + wg) * KV_CHUNK), 8192, 1024, 1);
            wg_fence();
#pragma unroll
            for (int ks = 0; ks < 4; ks++) wgmma_n64(acc, da + ks * 2, db + ks * 128);
            wg_commit();
        }
        wg_wait<0>();
        pin(acc);
        if (tid == 0) TS(6);
        float s1a = 0.f, s2a = 0.f, s3a = 0.f, s1b = 0.f, s2b = 0.f, s3b = 0.f;
#pragma unroll
        for (int j = 0; j < 8; j++) {
            const uint32_t ha = pack_bf16(bf_lo(xa[j]) + acc[4 * j], bf_hi(xa[j]) + acc[4 * j + 1]);
            const uint32_t hb = pack_bf16(bf_lo(xb[j]) + acc[4 * j + 2], bf_hi(xb[j]) + acc[4 * j + 3]);
            xa[j] = ha; xb[j] = hb;
            const float w0 = bf_lo(wr[j]), w1 = bf_hi(wr[j]);
            const float da0 = bf_lo(ha) - p0, da1 = bf_hi(ha) - p0, db0 = bf_lo(hb) - p1, db1 = bf_hi(hb) - p1;
            s1a += da0 + da1; s2a = fmaf(da0, da0, fmaf(da1, da1, s2a)); s3a = fmaf(da0, w0, fmaf(da1, w1, s3a));
            s1b += db0 + db1; s2b = fmaf(db0, db0, fmaf(db1, db1, s2b)); s3b = fmaf(db0, w0, fmaf(db1, w1, s3b));
        }
#pragma unroll
        for (int m = 1; m <= 2; m <<= 1) {
            s1a += __shfl_xor_sync(0xffffffffu, s1a, m); s2a += __shfl_xor_sync(0xffffffffu, s2a, m); s3a += __shfl_xor_sync(0xffffffffu, s3a, m);
            s1b += __shfl_xor_sync(0xffffffffu, s1b, m); s2b += __shfl_xor_sync(0xffffffffu, s2b, m); s3b += __shfl_xor_sync(0xffffffffu, s3b, m);
        }
        if (t4 < 2) {
            const int lr = w4 * 16 + g + t4 * 8;
            st_pkt(&gPart[(rb3 * 64 + lr) * 8 + cb * 2 + wg],
                   make_uint4(__float_as_uint(t4 ? s1b : s1a), __float_as_uint(t4 ? s2b : s2a), __float_as_uint(t4 ? s3b : s3a), tag));
        }
        {
            const int lr = tid >> 2, sl = tid & 3;
            uint4 pv[2];
            wait_pkts<2, 0xffffffffu>(&gPart[rb3 * 512 + tid * 2], 1, tag, pv);
            float s1 = __uint_as_float(pv[0].x) + __uint_as_float(pv[1].x), s2 = __uint_as_float(pv[0].y) + __uint_as_float(pv[1].y);
            float s3 = __uint_as_float(pv[0].z) + __uint_as_float(pv[1].z);
#pragma unroll
            for (int m = 1; m <= 2; m <<= 1) {
                s1 += __shfl_xor_sync(0xffffffffu, s1, m); s2 += __shfl_xor_sync(0xffffffffu, s2, m); s3 += __shfl_xor_sync(0xffffffffu, s3, m);
            }
            if (sl == 0) {
                const float md = s1 * (1.f / DM);
                const float var = fmaxf(s2 * (1.f / DM) - md * md, 0.f);
                const float rs = rsqrtf(var + LN_EPS);
                ms.p3.mu[lr] = pivot + md;
                ms.p3.rs[lr] = rs;
                ms.p3.r[lr] = (s3 - md * wsum) * rs;
            }
        }
        bar_sync(1, 256);
        if (tid == 0) TS(7);
        {
            unsigned int i1, i2;
            warp_top2(f2ord(ms.p3.r[lane]), lane, f2ord(ms.p3.r[lane + 32]), lane + 32, i1, i2);
            if (cb == 0) {
                const int c = tid & 1, li = c ? i2 : i1;
                st_pkt(&gCand[(tid >> 1) * 64 + rb3 * 2 + c],
                       make_uint4(__float_as_uint(ms.p3.r[li]), __float_as_uint(ms.p3.mu[li]), __float_as_uint(ms.p3.rs[li]),
                                  (tag << 11) | (unsigned int)(rb3 * 64 + li)));
            }
#pragma unroll
            for (int c = 0; c < 2; c++) {
                const unsigned int li = c ? i2 : i1;
                if ((int)(li >> 4) == w4 && (int)(li & 7) == g) {
                    const bool hi = (li & 8) != 0;
                    uint4* dst = &gCandRow[(rb3 * 2 + c) * 128 + (cb * 2 + wg) * 16 + t4];
#pragma unroll
                    for (int q = 0; q < 4; q++)
                        st_pkt(dst + q * 4, make_uint4(hi ? xb[2 * q] : xa[2 * q], hi ? xb[2 * q + 1] : xa[2 * q + 1], 0u, tag));
                }
            }
        }
        {
            const int lr0 = w4 * 16 + g;
            const float mu0 = ms.p3.mu[lr0], rs0 = ms.p3.rs[lr0], mu1 = ms.p3.mu[lr0 + 8], rs1 = ms.p3.rs[lr0 + 8];
            char* so = smem + wg * KV_CHUNK;
#pragma unroll
            for (int j = 0; j < 8; j++) {
                const float a0 = bf_lo(xa[j]), a1 = bf_hi(xa[j]), b0 = bf_lo(xb[j]), b1 = bf_hi(xb[j]);
                const uint32_t la = pack_bf16((a0 - mu0) * rs0, (a1 - mu0) * rs0);
                const uint32_t lb = pack_bf16((b0 - mu1) * rs1, (b1 - mu1) * rs1);
                const int o = ((j ^ g) << 4) + t4 * 4;
                *reinterpret_cast<uint32_t*>(so + lr0 * 128 + o) = pack_bf16(a0 + bf_lo(la), a1 + bf_hi(la));
                *reinterpret_cast<uint32_t*>(so + (lr0 + 8) * 128 + o) = pack_bf16(b0 + bf_lo(lb), b1 + bf_hi(lb));
            }
            fence_proxy_async_smem();
            bar_sync(3 + wg, 128);
            if ((tid & 127) == 0) {
                tma_store_2d(&tmOut, smem_u32(so), cb * 128 + wg * 64, rb3 * 64);
                asm volatile("cp.async.bulk.wait_group 0;" ::: "memory");
                st_release(&gFlagOut[cta * 8 + wg], tag);
            }
        }
    } else {
        const int t = tid - 256;
        if (lane == 0) {
            const int kc = warp - 8;
            int it = 0;
            while (true) {
                const uint4 f = ld_pkt(reinterpret_cast<const uint4*>(&gFlagO[rb3 * 32 + kc * 4]));
                if (f.x == tag && f.y == tag && f.z == tag && f.w == tag) break;
                if (++it > SPIN_LIMIT) __trap();
                BACKOFF();
            }
            if (kc == 7) TS(5);
            fence_proxy_async_global();
            const uint32_t bar = smem_u32(&ms.a3[kc]);
            mbar_expect_tx(bar, 8192);
            tma_2d(smem_u32(smem + SM_A3 + kc * 8192), &tmO, kc * 64, rb3 * 64, bar);
        }
        __syncwarp();
        uint32_t wd[16];
        if (cta < NFFN) {
#pragma unroll
            for (int k = 0; k < 16; k++) wd[k] = __ldg(reinterpret_cast<const uint32_t*>(w_down + (size_t)(cta * 16 + k) * DM + 2 * t));
        }
        if (warp == 8) {
            uint4 cv[2];
            wait_pkts<2, 0xfffff800u>(&gCand[cta * 64 + lane * 2], 1, tag << 11, cv);
            unsigned int i1, i2;
            warp_top2(f2ord(__uint_as_float(cv[0].x)), cv[0].w & 0x7ffu, f2ord(__uint_as_float(cv[1].x)), cv[1].w & 0x7ffu, i1, i2);
#pragma unroll
            for (int c = 0; c < 2; c++) {
                const unsigned int ci = cv[c].w & 0x7ffu;
                if (ci == i1 || ci == i2) {
                    const int o = ci == i1 ? 0 : 1;
                    ms.idx[o] = (int)ci;
                    ms.cslot[o] = lane * 2 + c;
                    *reinterpret_cast<float4*>(&ms.sel[o * 4]) =
                        make_float4(__uint_as_float(cv[c].y), __uint_as_float(cv[c].z), __fdividef(1.f, 1.f + __expf(-__uint_as_float(cv[c].x))), 0.f);
                }
            }
            if (lane == 0) TS(8);
        }
        bar_sync(2, 256);
        const int idx0 = ms.idx[0], idx1 = ms.idx[1];
        float* sX = reinterpret_cast<float*>(smem + SM_A3);
        float* sH = sX + 1024;
        float* sPart = sX + 2048;
        float* sAct = sPart + 512;
        float* sR = sAct + 32;
        if (cta < NFFN) {
            {
                const int tk = t >> 7, P = t & 127;
                uint4 hv[1];
                wait_pkts<1, 0xffffffffu>(&gCandRow[ms.cslot[tk] * 128 + P], 0, tag, hv);
                const float mu = ms.sel[tk * 4], rs = ms.sel[tk * 4 + 1];
                const int col = (P >> 4) * 64 + ((P >> 2) & 3) * 16 + (P & 3) * 2;
                const uint32_t l0 = pack_bf16((bf_lo(hv[0].x) - mu) * rs, (bf_hi(hv[0].x) - mu) * rs);
                const uint32_t l1 = pack_bf16((bf_lo(hv[0].y) - mu) * rs, (bf_hi(hv[0].y) - mu) * rs);
                *reinterpret_cast<float2*>(&sX[tk * 512 + col]) = make_float2(bf_lo(l0), bf_hi(l0));
                *reinterpret_cast<float2*>(&sX[tk * 512 + col + 8]) = make_float2(bf_lo(l1), bf_hi(l1));
                *reinterpret_cast<float2*>(&sH[tk * 512 + col]) = make_float2(bf_lo(hv[0].x), bf_hi(hv[0].x));
                *reinterpret_cast<float2*>(&sH[tk * 512 + col + 8]) = make_float2(bf_lo(hv[0].y), bf_hi(hv[0].y));
            }
            mbar_wait(smem_u32(&ms.moe), 0);
            bar_sync(9, 256);
            {
                const int wv = warp - 8, kk = lane >> 3, cp = lane & 7;
                float a[2][2][2] = {};
#pragma unroll
                for (int i = 0; i < 16; i++) {
                    const int k = wv * 64 + i * 4 + kk;
                    const float x0 = sX[k], x1 = sX[512 + k];
#pragma unroll
                    for (int mat = 0; mat < 2; mat++) {
                        const uint32_t w = *reinterpret_cast<const uint32_t*>(smem + (mat * 8 + wv) * KV_CHUNK + 8192 + (i * 4 + kk) * 32 + cp * 4);
                        a[mat][0][0] = fmaf(x0, bf_lo(w), a[mat][0][0]); a[mat][0][1] = fmaf(x0, bf_hi(w), a[mat][0][1]);
                        a[mat][1][0] = fmaf(x1, bf_lo(w), a[mat][1][0]); a[mat][1][1] = fmaf(x1, bf_hi(w), a[mat][1][1]);
                    }
                }
#pragma unroll
                for (int mat = 0; mat < 2; mat++)
#pragma unroll
                    for (int tk = 0; tk < 2; tk++)
#pragma unroll
                        for (int e = 0; e < 2; e++) {
                            float v = a[mat][tk][e];
                            v += __shfl_xor_sync(0xffffffffu, v, 8);
                            v += __shfl_xor_sync(0xffffffffu, v, 16);
                            if (kk == 0) sPart[(wv * 2 + tk) * 32 + mat * 16 + 2 * cp + e] = v;
                        }
            }
            bar_sync(9, 256);
            if (t < 32) {
                const int tk = t >> 4, c = t & 15;
                float gs = 0.f, us = 0.f;
#pragma unroll
                for (int w = 0; w < 8; w++) { gs += sPart[(w * 2 + tk) * 32 + c]; us += sPart[(w * 2 + tk) * 32 + 16 + c]; }
                const float gb = bf_round(gs), ub = bf_round(us);
                const float sl = bf_round(__fdividef(gb, 1.f + __expf(-gb)));
                sAct[tk * 16 + c] = bf_round(sl * ub);
            }
            bar_sync(9, 256);
            {
                float y00 = 0.f, y01 = 0.f, y10 = 0.f, y11 = 0.f;
#pragma unroll
                for (int k = 0; k < 16; k++) {
                    const float a0 = sAct[k], a1 = sAct[16 + k];
                    y00 = fmaf(a0, bf_lo(wd[k]), y00); y01 = fmaf(a0, bf_hi(wd[k]), y01);
                    y10 = fmaf(a1, bf_lo(wd[k]), y10); y11 = fmaf(a1, bf_hi(wd[k]), y11);
                }
                st_pkt(&gYPart[((t >> 2) * NFFN + cta) * 4 + (t & 3)], embed_tag(y00, y01, y10, y11, tag));
            }
            if (t == 0) TS(9);
        }
        if (cta < 64) {
            const int pc = t & 3, part = t >> 2;
            float y[4] = {0.f, 0.f, 0.f, 0.f};
            if (part < 56) {
                uint4 yv[2];
                wait_pkts4<2>(&gYPart[(cta * NFFN + part) * 4 + pc], 56 * 4, tag, yv);
                y[0] = __uint_as_float(yv[0].x) + __uint_as_float(yv[1].x); y[1] = __uint_as_float(yv[0].y) + __uint_as_float(yv[1].y);
                y[2] = __uint_as_float(yv[0].z) + __uint_as_float(yv[1].z); y[3] = __uint_as_float(yv[0].w) + __uint_as_float(yv[1].w);
            }
            if (t >= 224 && t < 226) {
                const int orow = (t & 1) ? idx1 : idx0, oc = cta * 8;
                wait_flag(&gFlagOut[((orow >> 6) * 4 + (oc >> 7)) * 8 + ((oc >> 6) & 1)], tag);
            }
            __syncwarp();
#pragma unroll
            for (int e = 0; e < 4; e++) {
                y[e] += __shfl_xor_sync(0xffffffffu, y[e], 4); y[e] += __shfl_xor_sync(0xffffffffu, y[e], 8); y[e] += __shfl_xor_sync(0xffffffffu, y[e], 16);
            }
            if (lane < 4) *reinterpret_cast<float4*>(&sR[(warp - 8) * 16 + lane * 4]) = make_float4(y[0], y[1], y[2], y[3]);
            bar_sync(9, 256);
            if (t < 16) {
                const int opc = t >> 2, oe = t & 3, otk = oe >> 1, ocol = (cta * 4 + opc) * 2 + (oe & 1);
                float s = 0.f;
#pragma unroll
                for (int w = 0; w < 8; w++) s += sR[w * 16 + t];
                const float yb = bf_round(bf_round(s) * ms.sel[otk * 4 + 2]);
                out[(size_t)(otk ? idx1 : idx0) * DM + ocol] = __float2bfloat16(sH[otk * 512 + ocol] + bf_round(sX[otk * 512 + ocol] + yb));
            }
            if (cta == 0 && t == 0) {
                *reinterpret_cast<volatile unsigned int*>(&gEpoch) = tag;
            }
            if (t == 0) TS(10);
        }
    }
}

__device__ __nv_bfloat16 fbA[S_LEN * DM], fbQKV[S_LEN * 3 * DM], fbO[S_LEN * DM], fbH[S_LEN * DM];
__device__ float fbR[S_LEN], fbAct[2 * FF];
__device__ int fbIdx[2];

__device__ __forceinline__ float block_sum(float v, float* red) {
#pragma unroll
    for (int m = 16; m; m >>= 1) v += __shfl_xor_sync(0xffffffffu, v, m);
    __syncthreads();
    if ((threadIdx.x & 31) == 0) red[threadIdx.x >> 5] = v;
    __syncthreads();
    float s = 0.f;
    for (int i = 0; i < (int)(blockDim.x >> 5); i++) s += red[i];
    return s;
}
__global__ void fb_ln(const __nv_bfloat16* __restrict__ x, __nv_bfloat16* __restrict__ y, const __nv_bfloat16* w_r, __nv_bfloat16* out) {
    __shared__ float red[16];
    const int row = blockIdx.x, c = threadIdx.x;
    const float v = __bfloat162float(x[(size_t)row * DM + c]);
    const float mu = block_sum(v, red) * (1.f / DM);
    const float var = block_sum((v - mu) * (v - mu), red) * (1.f / DM);
    const float ln = bf_round((v - mu) * rsqrtf(var + LN_EPS));
    y[(size_t)row * DM + c] = __float2bfloat16(ln);
    if (w_r) {
        const float r = block_sum(ln * __bfloat162float(w_r[c]), red);
        if (c == 0) fbR[row] = r;
        out[(size_t)row * DM + c] = __float2bfloat16(v + ln);
    }
}
__global__ void fb_gemm(const __nv_bfloat16* __restrict__ A, const __nv_bfloat16* __restrict__ B, const __nv_bfloat16* R,
                        __nv_bfloat16* __restrict__ C, int N, int K) {
    __shared__ float sa[16][17], sb[16][17];
    const int tx = threadIdx.x & 15, ty = threadIdx.x >> 4, row = blockIdx.y * 16 + ty, col = blockIdx.x * 16 + tx;
    float acc = 0.f;
    for (int k0 = 0; k0 < K; k0 += 16) {
        sa[ty][tx] = __bfloat162float(A[(size_t)row * K + k0 + tx]);
        sb[ty][tx] = __bfloat162float(B[(size_t)(k0 + ty) * N + col]);
        __syncthreads();
#pragma unroll
        for (int k = 0; k < 16; k++) acc = fmaf(sa[ty][k], sb[k][tx], acc);
        __syncthreads();
    }
    if (R) acc += __bfloat162float(R[(size_t)row * N + col]);
    C[(size_t)row * N + col] = __float2bfloat16(acc);
}
__global__ void fb_attn() {
    const int head = blockIdx.y, row = blockIdx.x * blockDim.x + threadIdx.x;
    float q[DH], o[DH], m = -INFINITY, l = 0.f;
    for (int d = 0; d < DH; d++) { q[d] = __bfloat162float(fbQKV[(size_t)row * 3 * DM + head * DH + d]) * 0.25f; o[d] = 0.f; }
    for (int j = 0; j < S_LEN; j++) {
        const __nv_bfloat16* kp = fbQKV + (size_t)j * 3 * DM + DM + head * DH;
        float s = 0.f;
        for (int d = 0; d < DH; d++) s = fmaf(q[d], __bfloat162float(kp[d]), s);
        const float mn = fmaxf(m, s), a = __expf(m - mn), p = __expf(s - mn);
        l = l * a + p;
        for (int d = 0; d < DH; d++) o[d] = o[d] * a + p * __bfloat162float(kp[DM + d]);
        m = mn;
    }
    for (int d = 0; d < DH; d++) fbO[(size_t)row * DM + head * DH + d] = __float2bfloat16(o[d] / l);
}
__global__ void fb_top2() {
    const int lane = threadIdx.x;
    unsigned int k1 = 0, i1 = 0xffffffffu, k2 = 0, i2 = 0xffffffffu;
    for (int j = lane; j < S_LEN; j += 32) {
        const unsigned int k = f2ord(fbR[j]);
        if (i1 == 0xffffffffu || k > k1) { k2 = k1; i2 = i1; k1 = k; i1 = j; }
        else if (i2 == 0xffffffffu || k > k2) { k2 = k; i2 = j; }
    }
    unsigned int a, b;
    warp_top2(k1, i1, k2, i2, a, b);
    if (lane == 0) { fbIdx[0] = a; fbIdx[1] = b; }
}
__global__ void fb_ffn1(const __nv_bfloat16* __restrict__ wg, const __nv_bfloat16* __restrict__ wu) {
    const int f = blockIdx.x * blockDim.x + threadIdx.x, tk = blockIdx.y;
    const __nv_bfloat16* xs = fbA + (size_t)fbIdx[tk] * DM;
    float g = 0.f, u = 0.f;
    for (int k = 0; k < DM; k++) {
        const float xv = __bfloat162float(xs[k]);
        g = fmaf(xv, __bfloat162float(wg[(size_t)k * FF + f]), g);
        u = fmaf(xv, __bfloat162float(wu[(size_t)k * FF + f]), u);
    }
    g = bf_round(g); u = bf_round(u);
    fbAct[tk * FF + f] = bf_round(bf_round(g / (1.f + __expf(-g))) * u);
}
__global__ void fb_ffn2(const __nv_bfloat16* __restrict__ wd, __nv_bfloat16* __restrict__ out) {
    const int c = blockIdx.x * blockDim.x + threadIdx.x, tk = blockIdx.y, row = fbIdx[tk];
    float y = 0.f;
    for (int f = 0; f < FF; f++) y = fmaf(fbAct[tk * FF + f], __bfloat162float(wd[(size_t)f * DM + c]), y);
    const float yb = bf_round(bf_round(y) / (1.f + __expf(-fbR[row])));
    out[(size_t)row * DM + c] = __float2bfloat16(__bfloat162float(fbH[(size_t)row * DM + c]) + bf_round(__bfloat162float(fbA[(size_t)row * DM + c]) + yb));
}

typedef CUresult (*EncodeFn)(CUtensorMap*, CUtensorMapDataType, cuuint32_t, void*, const cuuint64_t*, const cuuint64_t*,
                             const cuuint32_t*, const cuuint32_t*, CUtensorMapInterleave, CUtensorMapSwizzle,
                             CUtensorMapL2promotion, CUtensorMapFloatOOBfill);

void make_map(EncodeFn enc, CUtensorMap* tm, const void* base, uint64_t cols, uint64_t rows, uint32_t box_c, uint32_t box_r, bool swz) {
    cuuint64_t dims[2] = {cols, rows};
    cuuint64_t strides[1] = {cols * 2};
    cuuint32_t box[2] = {box_c, box_r};
    cuuint32_t es[2] = {1, 1};
    enc(tm, CU_TENSOR_MAP_DATA_TYPE_BFLOAT16, 2, const_cast<void*>(base), dims, strides, box, es, CU_TENSOR_MAP_INTERLEAVE_NONE,
        swz ? CU_TENSOR_MAP_SWIZZLE_128B : CU_TENSOR_MAP_SWIZZLE_NONE, CU_TENSOR_MAP_L2_PROMOTION_L2_256B,
        CU_TENSOR_MAP_FLOAT_OOB_FILL_NONE);
}

}

extern "C" void kernel_launch(void* const* d_in, const int* in_sizes, int n_in, void* d_out, int out_size) {
    const __nv_bfloat16* x = (const __nv_bfloat16*)d_in[0];
    const __nv_bfloat16* wqkv = (const __nv_bfloat16*)d_in[1];
    const __nv_bfloat16* wo = (const __nv_bfloat16*)d_in[2];
    const __nv_bfloat16* w_r = (const __nv_bfloat16*)d_in[4];
    const __nv_bfloat16* w_gate = (const __nv_bfloat16*)d_in[5];
    const __nv_bfloat16* w_up = (const __nv_bfloat16*)d_in[6];
    const __nv_bfloat16* w_down = (const __nv_bfloat16*)d_in[7];
    __nv_bfloat16* out = (__nv_bfloat16*)d_out;
    cudaStream_t st = cudaStreamPerThread;

    static EncodeFn enc = nullptr;
    static int mode = -1;
    static void *pO = nullptr, *pfbA = nullptr, *pfbQKV = nullptr, *pfbO = nullptr, *pfbH = nullptr;
    if (mode < 0) {
        void* fn = nullptr;
        cudaDriverEntryPointQueryResult qr;
        cudaGetDriverEntryPoint("cuTensorMapEncodeTiled", &fn, cudaEnableDefault, &qr);
        enc = (EncodeFn)fn;
        cudaGetSymbolAddress(&pO, gO);
        cudaGetSymbolAddress(&pfbA, fbA); cudaGetSymbolAddress(&pfbQKV, fbQKV);
        cudaGetSymbolAddress(&pfbO, fbO); cudaGetSymbolAddress(&pfbH, fbH);
        int dev = 0, sms = 0, occ = 0;
        cudaGetDevice(&dev);
        cudaDeviceGetAttribute(&sms, cudaDevAttrMultiProcessorCount, dev);
        const cudaError_t e = cudaFuncSetAttribute(mega_kernel, cudaFuncAttributeMaxDynamicSharedMemorySize, SMEM_TOTAL);
        if (e == cudaSuccess) cudaOccupancyMaxActiveBlocksPerMultiprocessor(&occ, mega_kernel, 512, SMEM_TOTAL);
        (void)cudaGetLastError();
        mode = (enc != nullptr && e == cudaSuccess && occ * sms >= NCTA) ? 1 : 0;
    }
    if (mode == 1) {
        CUtensorMap tmX, tmW, tmO, tmWo, tmG, tmU, tmOut;
        make_map(enc, &tmX, x, DM, S_LEN, 64, 128, true);
        make_map(enc, &tmW, wqkv, 3 * DM, DM, 64, 64, true);
        make_map(enc, &tmO, pO, DM, S_LEN, 64, 64, true);
        make_map(enc, &tmWo, wo, DM, DM, 64, 64, true);
        make_map(enc, &tmG, w_gate, FF, DM, 16, 64, false);
        make_map(enc, &tmU, w_up, FF, DM, 16, 64, false);
        make_map(enc, &tmOut, out, DM, S_LEN, 64, 64, true);
        mega_kernel<<<NCTA, 512, SMEM_TOTAL, st>>>(tmX, tmW, tmO, tmWo, tmG, tmU, tmOut, x, wqkv, wo, w_r, w_gate, w_up, w_down, out);
    } else {
        __nv_bfloat16 *A = (__nv_bfloat16*)pfbA, *QKV = (__nv_bfloat16*)pfbQKV, *O = (__nv_bfloat16*)pfbO, *H = (__nv_bfloat16*)pfbH;
        fb_ln<<<S_LEN, DM, 0, st>>>(x, A, nullptr, nullptr);
        fb_gemm<<<dim3(3 * DM / 16, S_LEN / 16), 256, 0, st>>>(A, wqkv, nullptr, QKV, 3 * DM, DM);
        fb_attn<<<dim3(S_LEN / 128, NH), 128, 0, st>>>();
        fb_gemm<<<dim3(DM / 16, S_LEN / 16), 256, 0, st>>>(O, wo, x, H, DM, DM);
        fb_ln<<<S_LEN, DM, 0, st>>>(H, A, w_r, out);
        fb_top2<<<1, 32, 0, st>>>();
        fb_ffn1<<<dim3(FF / 128, 2), 128, 0, st>>>(w_gate, w_up);
        fb_ffn2<<<dim3(DM / 128, 2), 128, 0, st>>>(w_down, out);
    }
}
```
